```python
import torch

def _softmax(x, axis=-1):
    return torch.softmax(x, dim=axis)
def _gelu(x):
    return torch.nn.functional.gelu(x, approximate="tanh")
def _silu(x):
    return torch.nn.functional.silu(x)
def _sigmoid(x):
    return torch.sigmoid(x)
def _layernorm(x, axis=-1, eps=1e-5):
    m = x.mean(dim=axis, keepdim=True)
    v = x.var(dim=axis, keepdim=True, unbiased=False)
    return (x - m) / torch.sqrt(v + eps)
def _scatter_add(tgt, idx, src, axis=0):
    return tgt.clone().index_add_(axis, idx, src)
def _segment_sum(src, seg, n):
    out = torch.zeros((n,) + src.shape[1:], dtype=src.dtype)
    return out.index_add_(0, seg, src)
def _pad(x, pw):
    flat = tuple(v for pair in reversed(pw) for v in pair)
    return torch.nn.functional.pad(x, flat)

kernel_name = 'parallel_sum__mha_block__moe_arch_mod__prompt'

def setup_inputs():

    _w = (lambda a: (lambda t: t.to(torch.bfloat16) if t.is_floating_point() else t)(torch.as_tensor(a)))
    def _A_setup():
        B, S, D, H = 1, 2048, 512, 32
        return {
            "x": _w((lambda *s: torch.randn(*s, dtype=torch.bfloat16) * 0.05)(B, S, D)),
            "wqkv": _w((lambda *s: torch.randn(*s, dtype=torch.bfloat16) * 0.2)(D, 3 * D)),
            "wo": _w((lambda *s: torch.randn(*s, dtype=torch.bfloat16) * 0.1)(D, D)),
        }
    _A_in = _A_setup()

    def _B_setup():
        B, S, D, F, C = 1, 2048, 512, 1792, 2
        return {
            "x": _w((lambda *s: torch.randn(*s, dtype=torch.bfloat16) * 0.05)(B, S, D)),
            "w_r": _w((lambda *s: torch.randn(*s, dtype=torch.bfloat16) * 0.1)(D)),
            "w_gate": _w((lambda *s: torch.randn(*s, dtype=torch.bfloat16) * 0.1)(D, F)),
            "w_up": _w((lambda *s: torch.randn(*s, dtype=torch.bfloat16) * 0.1)(D, F)),
            "w_down": _w((lambda *s: torch.randn(*s, dtype=torch.bfloat16) * 0.1)(F, D)),
        }
    _B_in = _B_setup()

    return {
        "A_x": _A_in["x"],
        "A_wqkv": _A_in["wqkv"],
        "A_wo": _A_in["wo"],
        "B_x": _B_in["x"],
        "B_w_r": _B_in["w_r"],
        "B_w_gate": _B_in["w_gate"],
        "B_w_up": _B_in["w_up"],
        "B_w_down": _B_in["w_down"],
    }

def reference(A_x, A_wqkv, A_wo, B_x, B_w_r, B_w_gate, B_w_up, B_w_down):
    def _A_ref(x, wqkv, wo):
        B, S, D = x.shape
        H = 32
        Dh = D // H
        qkv = (lambda x, *d: x.permute(*d))((x @ wqkv).reshape(B, S, 3, H, Dh), 2, 0, 3, 1, 4)
        q, k, v = qkv[0], qkv[1], qkv[2]
        scores = torch.einsum("bhqd,bhkd->bhqk", q, k) * (Dh ** -0.5)
        p = _softmax(scores, axis=-1)
        o = torch.einsum("bhqk,bhkd->bhqd", p, v)
        return (lambda x, *d: x.permute(*d))(o, 0, 2, 1, 3).reshape(B, S, D) @ wo

    def _B_ref(x, w_r, w_gate, w_up, w_down):
        B, S, D = x.shape
        C = 2
        r = x @ w_r
        idx = torch.argsort(-r, axis=-1)[:, :C]
        idx_e = (lambda x, n, axis: torch.repeat_interleave(x, n, dim=axis))(idx.reshape(B, C, 1), D, axis=2)
        x_sel = (lambda x, i, axis: torch.take_along_dim(x, i, dim=axis))(x, idx_e, axis=1)
        g = _silu(x_sel @ w_gate)
        u = x_sel @ w_up
        y = (g * u) @ w_down
        r_sel = _sigmoid((lambda x, i, axis: torch.take_along_dim(x, i, dim=axis))(r, idx, axis=1))
        y = y * r_sel.reshape(B, C, 1)
        b_off = (torch.arange(B) * S).reshape(B, 1)
        flat_idx = (idx + b_off).reshape(B * C)
        zero = (x * 0.0).reshape(B * S, D)
        upd = _scatter_add(zero, flat_idx, y.reshape(B * C, D), axis=0)
        return x + upd.reshape(B, S, D)

    x = A_x
    xn = _layernorm(x, axis=-1)
    return x + _A_ref(xn, A_wqkv, A_wo) + _B_ref(xn, B_w_r, B_w_gate, B_w_up, B_w_down)
```

```cpp
#include <cuda_runtime.h>
#include <cuda_bf16.h>
#include <cuda.h>
#include <stdint.h>

namespace {

constexpr int S_ = 2048, D_ = 512, H_ = 32, F_ = 1792;

constexpr uint32_t PMASK = 0xA52;
__host__ __device__ constexpr bool is_poly_group(int g8) { return g8 >= 4 && ((PMASK >> ((g8 - 4) % 12)) & 1); }

__device__ __align__(1024) uint4 g_Q[H_ * S_ * 2];
__device__ __align__(1024) uint4 g_K[H_ * S_ * 2];
__device__ __align__(1024) uint4 g_V[H_ * S_ * 2];
__device__ __align__(1024) uint4 g_O[S_ * D_ / 8];
__device__ float2 g_stats[S_];
__device__ float g_r[S_];
__device__ float g_ypart[4][2][D_];
__device__ int g_sel[2];

__device__ __forceinline__ uint32_t smem_u32(const void* p) { return (uint32_t)__cvta_generic_to_shared(p); }
__device__ __forceinline__ float bf16r(float x) { return __bfloat162float(__float2bfloat16_rn(x)); }
__device__ __forceinline__ uint32_t pack_bf16(float lo, float hi) {
    uint32_t r; asm("cvt.rn.bf16x2.f32 %0, %1, %2;" : "=r"(r) : "f"(hi), "f"(lo)); return r;
}
__device__ __forceinline__ float bf_lo(uint32_t u) { return __uint_as_float(u << 16); }
__device__ __forceinline__ float bf_hi(uint32_t u) { return __uint_as_float(u & 0xFFFF0000u); }
__device__ __forceinline__ float ex2(float x) { float y; asm("ex2.approx.ftz.f32 %0, %1;" : "=f"(y) : "f"(x)); return y; }

__device__ __forceinline__ void mbar_init(uint32_t bar, uint32_t count) {
    asm volatile("mbarrier.init.shared::cta.b64 [%0], %1;" :: "r"(bar), "r"(count) : "memory");
}
__device__ __forceinline__ void mbar_expect_tx(uint32_t bar, uint32_t bytes) {
    asm volatile("mbarrier.arrive.expect_tx.shared::cta.b64 _, [%0], %1;" :: "r"(bar), "r"(bytes) : "memory");
}
__device__ __forceinline__ void mbar_arrive(uint32_t bar) {
    asm volatile("mbarrier.arrive.shared::cta.b64 _, [%0];" :: "r"(bar) : "memory");
}
__device__ __forceinline__ void mbar_wait(uint32_t bar, uint32_t parity) {
    uint32_t done;
    #pragma unroll 1
    for (int it = 0; it < (1 << 26); it++) {
        asm volatile("{.reg .pred p; mbarrier.try_wait.parity.shared::cta.b64 p, [%1], %2; selp.u32 %0, 1, 0, p;}"
                     : "=r"(done) : "r"(bar), "r"(parity) : "memory");
        if (done) return;
    }
    __trap();
}
__device__ __forceinline__ void bulk_g2s(uint32_t dst, const void* src, uint32_t bytes, uint32_t bar) {
    asm volatile("cp.async.bulk.shared::cluster.global.mbarrier::complete_tx::bytes [%0], [%1], %2, [%3];"
                 :: "r"(dst), "l"(src), "r"(bytes), "r"(bar) : "memory");
}
__device__ __forceinline__ void tma_2d(uint32_t dst, const CUtensorMap* map, int c0, int c1, uint32_t bar) {
    asm volatile("cp.async.bulk.tensor.2d.shared::cluster.global.mbarrier::complete_tx::bytes [%0], [%1, {%3, %4}], [%2];"
                 :: "r"(dst), "l"(map), "r"(bar), "r"(c0), "r"(c1) : "memory");
}
__device__ __forceinline__ void fence_async_smem() { asm volatile("fence.proxy.async.shared::cta;" ::: "memory"); }
__device__ __forceinline__ void named_bar(int id, int n) { asm volatile("bar.sync %0, %1;" :: "r"(id), "r"(n) : "memory"); }

__device__ __forceinline__ uint64_t make_desc(uint32_t saddr, uint32_t lbo, uint32_t sbo, uint32_t swz) {
    return (uint64_t)((saddr & 0x3FFFF) >> 4) | ((uint64_t)(lbo >> 4) << 16) | ((uint64_t)(sbo >> 4) << 32) | ((uint64_t)swz << 62);
}
#define WG_FENCE() asm volatile("wgmma.fence.sync.aligned;" ::: "memory")
#define WG_COMMIT() asm volatile("wgmma.commit_group.sync.aligned;" ::: "memory")
template <int N> __device__ __forceinline__ void wg_wait() { asm volatile("wgmma.wait_group.sync.aligned %0;" :: "n"(N) : "memory"); }

#define F4(d, o) "+f"(d[o]), "+f"(d[o + 1]), "+f"(d[o + 2]), "+f"(d[o + 3])
#define F16(d, o) F4(d, o), F4(d, o + 4), F4(d, o + 8), F4(d, o + 12)
#define F32(d, o) F16(d, o), F16(d, o + 16)

__device__ __forceinline__ void wgmma_n192(float* d, uint64_t da, uint64_t db) {
    asm volatile("wgmma.mma_async.sync.aligned.m64n192k16.f32.bf16.bf16 "
        "{%0,%1,%2,%3,%4,%5,%6,%7,%8,%9,%10,%11,%12,%13,%14,%15,%16,%17,%18,%19,%20,%21,%22,%23,%24,%25,%26,%27,%28,%29,%30,%31,"
        "%32,%33,%34,%35,%36,%37,%38,%39,%40,%41,%42,%43,%44,%45,%46,%47,%48,%49,%50,%51,%52,%53,%54,%55,%56,%57,%58,%59,%60,%61,%62,%63,"
        "%64,%65,%66,%67,%68,%69,%70,%71,%72,%73,%74,%75,%76,%77,%78,%79,%80,%81,%82,%83,%84,%85,%86,%87,%88,%89,%90,%91,%92,%93,%94,%95}, "
        "%96, %97, 1, 1, 1, 0, 1;\n"
        : F32(d, 0), F32(d, 32), F32(d, 64) : "l"(da), "l"(db));
}
__device__ __forceinline__ void wgmma_n64(float* d, uint64_t da, uint64_t db) {
    asm volatile("wgmma.mma_async.sync.aligned.m64n64k16.f32.bf16.bf16 "
        "{%0,%1,%2,%3,%4,%5,%6,%7,%8,%9,%10,%11,%12,%13,%14,%15,%16,%17,%18,%19,%20,%21,%22,%23,%24,%25,%26,%27,%28,%29,%30,%31}, "
        "%32, %33, 1, 1, 1, 0, 1;\n"
        : F32(d, 0) : "l"(da), "l"(db));
}
__device__ __forceinline__ void wgmma_qk32(float* d, uint64_t qd, uint64_t kd) {
    asm volatile("wgmma.mma_async.sync.aligned.m64n32k16.f32.bf16.bf16 {%0,%1,%2,%3,%4,%5,%6,%7,%8,%9,%10,%11,%12,%13,%14,%15}, %16, %17, 0, 1, 1, 0, 0;\n"
        : F16(d, 0) : "l"(qd), "l"(kd));
}
__device__ __forceinline__ void wgmma_pv(float* d, const uint32_t* a, uint64_t vd) {
    asm volatile("wgmma.mma_async.sync.aligned.m64n24k16.f32.bf16.bf16 {%0,%1,%2,%3,%4,%5,%6,%7,%8,%9,%10,%11}, {%12,%13,%14,%15}, %16, 1, 1, 1, 1;\n"
        : F4(d, 0), F4(d, 4), F4(d, 8) : "r"(a[0]), "r"(a[1]), "r"(a[2]), "r"(a[3]), "l"(vd));
}
__device__ __forceinline__ void touch16(float* d) { asm volatile("" : F16(d, 0) :: "memory"); }
__device__ __forceinline__ void touch12(float* d) { asm volatile("" : F4(d, 0), F4(d, 4), F4(d, 8) :: "memory"); }
__device__ __forceinline__ void touch32(float* d) { asm volatile("" : F32(d, 0) :: "memory"); }
__device__ __forceinline__ void touch96(float* d) { asm volatile("" : F32(d, 0), F32(d, 32), F32(d, 64) :: "memory"); }

__device__ __forceinline__ float ln_elem(float x, float mean_b, float den_b) {
    return bf16r(__fdiv_rn(bf16r(x - mean_b), den_b));
}

constexpr int K1_THREADS = 288;
constexpr int K1_SMEM = 131072 + 4 * 24576 + 128;

__global__ void __launch_bounds__(K1_THREADS, 1)
k1_ln_qkv(const __grid_constant__ CUtensorMap wmap, const __nv_bfloat16* __restrict__ x, const __nv_bfloat16* __restrict__ w_r) {
    extern __shared__ __align__(1024) unsigned char smem[];
    const uint32_t sA = smem_u32(smem), sB = sA + 131072, sBar = sB + 4 * 24576;
    const int warp = threadIdx.x >> 5, lane = threadIdx.x & 31;
    const int nt = blockIdx.x & 7, mt = blockIdx.x >> 3;
    if (threadIdx.x == 0) {
        for (int i = 0; i < 4; i++) { mbar_init(sBar + i * 8, 1); mbar_init(sBar + 32 + i * 8, 2); }
        asm volatile("fence.mbarrier_init.release.cluster;" ::: "memory");
    }
    __syncthreads();
    if (warp == 8) {
        if (lane == 0) {
            for (int kc = 0; kc < 8; kc++) {
                const int st = kc & 3;
                if (kc >= 4) mbar_wait(sBar + 32 + st * 8, 0);
                mbar_expect_tx(sBar + st * 8, 24576);
                for (int j = 0; j < 3; j++) tma_2d(sB + st * 24576 + j * 8192, &wmap, nt * 192 + j * 64, kc * 64, sBar + st * 8);
            }
        }
        return;
    }
    float wr[16];
    if (nt == 0) {
        uint4 a = *(const uint4*)(w_r + lane * 8), b = *(const uint4*)(w_r + 256 + lane * 8);
        const uint32_t u[8] = {a.x, a.y, a.z, a.w, b.x, b.y, b.z, b.w};
        #pragma unroll
        for (int i = 0; i < 8; i++) { wr[2 * i] = bf_lo(u[i]); wr[2 * i + 1] = bf_hi(u[i]); }
    }
    #pragma unroll 1
    for (int b8 = 0; b8 < 2; b8++) {
        uint4 raw[8][2];
        #pragma unroll
        for (int i = 0; i < 8; i++) {
            const __nv_bfloat16* xp = x + (size_t)(mt * 128 + warp * 16 + b8 * 8 + i) * D_;
            raw[i][0] = __ldg((const uint4*)(xp + lane * 8));
            raw[i][1] = __ldg((const uint4*)(xp + 256 + lane * 8));
        }
        #pragma unroll
        for (int i = 0; i < 8; i++) {
            const int r = warp * 16 + b8 * 8 + i;
            const uint32_t u[8] = {raw[i][0].x, raw[i][0].y, raw[i][0].z, raw[i][0].w, raw[i][1].x, raw[i][1].y, raw[i][1].z, raw[i][1].w};
            float v[16];
            #pragma unroll
            for (int j = 0; j < 8; j++) { v[2 * j] = bf_lo(u[j]); v[2 * j + 1] = bf_hi(u[j]); }
            float s = 0.f;
            #pragma unroll
            for (int j = 0; j < 16; j++) s += v[j];
            #pragma unroll
            for (int o = 16; o; o >>= 1) s += __shfl_xor_sync(~0u, s, o);
            const float mean = s * (1.0f / D_);
            float q = 0.f;
            #pragma unroll
            for (int j = 0; j < 16; j++) { float d = v[j] - mean; q = fmaf(d, d, q); }
            #pragma unroll
            for (int o = 16; o; o >>= 1) q += __shfl_xor_sync(~0u, q, o);
            const float mean_b = bf16r(mean);
            const float var_b = bf16r(q * (1.0f / D_));
            const float den_b = bf16r(__fsqrt_rn(bf16r(var_b + 1e-5f)));
            #pragma unroll
            for (int j = 0; j < 16; j++) v[j] = ln_elem(v[j], mean_b, den_b);
            uint4 o0 = make_uint4(pack_bf16(v[0], v[1]), pack_bf16(v[2], v[3]), pack_bf16(v[4], v[5]), pack_bf16(v[6], v[7]));
            uint4 o1 = make_uint4(pack_bf16(v[8], v[9]), pack_bf16(v[10], v[11]), pack_bf16(v[12], v[13]), pack_bf16(v[14], v[15]));
            const int ch = (lane & 7) ^ (r & 7);
            *(uint4*)(smem + (lane >> 3) * 16384 + r * 128 + ch * 16) = o0;
            *(uint4*)(smem + (4 + (lane >> 3)) * 16384 + r * 128 + ch * 16) = o1;
            if (nt == 0) {
                float acc = 0.f;
                #pragma unroll
                for (int j = 0; j < 16; j++) acc = fmaf(v[j], wr[j], acc);
                #pragma unroll
                for (int o = 16; o; o >>= 1) acc += __shfl_xor_sync(~0u, acc, o);
                if (lane == 0) { g_r[mt * 128 + r] = bf16r(acc); g_stats[mt * 128 + r] = make_float2(mean_b, den_b); }
            }
        }
    }
    fence_async_smem();
    const int wg = warp >> 2;
    named_bar(1 + wg, 128);
    float acc[96];
    #pragma unroll
    for (int i = 0; i < 96; i++) acc[i] = 0.f;
    const uint64_t da0 = make_desc(sA + wg * 8192, 16, 1024, 1);
    const uint64_t db0 = make_desc(sB, 8192, 1024, 1);
    #pragma unroll 1
    for (int kc = 0; kc < 8; kc++) {
        const int st = kc & 3;
        mbar_wait(sBar + st * 8, kc >> 2);
        WG_FENCE();
        #pragma unroll
        for (int kk = 0; kk < 4; kk++)
            wgmma_n192(acc, da0 + (uint64_t)(kc * 1024 + kk * 2), db0 + (uint64_t)(st * 1536 + kk * 128));
        WG_COMMIT();
        wg_wait<0>();
        if (kc < 4 && (threadIdx.x & 127) == 0) mbar_arrive(sBar + 32 + st * 8);
    }
    touch96(acc);
    const int g = lane >> 2, t = lane & 3;
    const int row0 = mt * 128 + warp * 16;
    const int g8a = row0 >> 3;
    const float sgn0 = is_poly_group(g8a) ? -1.f : 1.f, sgn1 = is_poly_group(g8a + 1) ? -1.f : 1.f;
    constexpr float QS = 0.25f * 1.4426950408889634f;
    #pragma unroll
    for (int j = 0; j < 24; j++) {
        const int col = nt * 192 + j * 8;
        const int which = col >> 9, head = (col & 511) >> 4, half = (col >> 3) & 1;
        float a0 = acc[4 * j], a1 = acc[4 * j + 1], a2 = acc[4 * j + 2], a3 = acc[4 * j + 3];
        if (which == 2) {
            uint32_t* base = (uint32_t*)(g_V + (size_t)head * 4096 + half * 2048 + row0 + g) + t;
            base[0] = pack_bf16(a0 * sgn0, a1 * sgn0);
            base[32] = pack_bf16(a2 * sgn1, a3 * sgn1);
        } else {
            if (which == 0) { a0 *= QS; a1 *= QS; a2 *= QS; a3 *= QS; }
            uint32_t* base = (uint32_t*)((which == 0 ? g_Q : g_K) + (size_t)head * 4096 + g8a * 16 + half * 8 + g) + t;
            base[0] = pack_bf16(a0, a1);
            base[64] = pack_bf16(a2, a3);
        }
    }
}

constexpr int K2_THREADS = 512;
constexpr int K2_SMEM = 65536 + 98304 + 16384 + 128;

__device__ __forceinline__ uint32_t polyexp(float s, float cb, uint32_t c421, float c3, float one) {
    float u;
    asm("fma.rn.sat.f32 %0, %1, 0f3B808081, %2;" : "=f"(u) : "f"(s), "f"(cb));
    float z = fmaf(u, 0.99609375f, one);
    uint32_t rb;
    asm("lop3.b32 %0, %1, 0xFFFF8000, %2, 0xEA;" : "=r"(rb) : "r"(__float_as_uint(z)), "r"(c421));
    float f = z - __uint_as_float(rb);
    float h = fmaf(f, c3, 58.86525f);
    h = fmaf(f, h, -0.29870507f);
    return __float_as_uint(fmaf(f, h, z));
}

struct ExpC { float nm0, nm1, cb0, cb1, c3, one; uint32_t c421; };

template <int G>
__device__ __forceinline__ void exp_block(const float* s, uint32_t* p, const ExpC& c) {
    #pragma unroll
    for (int hf = 0; hf < 2; hf++) {
        const float* x = s + hf * 4;
        if ((PMASK >> (G + hf)) & 1) {
            p[hf * 2 + 0] = __byte_perm(polyexp(x[0], c.cb0, c.c421, c.c3, c.one), polyexp(x[1], c.cb0, c.c421, c.c3, c.one), 0x6521);
            p[hf * 2 + 1] = __byte_perm(polyexp(x[2], c.cb1, c.c421, c.c3, c.one), polyexp(x[3], c.cb1, c.c421, c.c3, c.one), 0x6521);
        } else {
            p[hf * 2 + 0] = pack_bf16(ex2(x[0] + c.nm0), ex2(x[1] + c.nm0));
            p[hf * 2 + 1] = pack_bf16(ex2(x[2] + c.nm1), ex2(x[3] + c.nm1));
        }
    }
}

__device__ __forceinline__ void max16(const float* s, float& mx0, float& mx1) {
    #pragma unroll
    for (int j = 0; j < 4; j++) {
        mx0 = fmaxf(mx0, fmaxf(s[4 * j], s[4 * j + 1]));
        mx1 = fmaxf(mx1, fmaxf(s[4 * j + 2], s[4 * j + 3]));
    }
}

__device__ void moe_cta(int part, unsigned char* smem, const __nv_bfloat16* __restrict__ x, const __nv_bfloat16* __restrict__ w_gate,
                        const __nv_bfloat16* __restrict__ w_up, const __nv_bfloat16* __restrict__ w_down) {
    float* xs = (float*)smem;
    float* red = xs + 1024;
    float* hs = red + 8 * 4 * 448;
    __shared__ float s_v[32];
    __shared__ int s_i[32];
    __shared__ int s_sel[2];
    const int tid = threadIdx.x, warp = tid >> 5, lane = tid & 31;
    for (int pass = 0; pass < 2; pass++) {
        float bv = -INFINITY; int bi = 0x7fffffff;
        const int excl = pass ? s_sel[0] : -1;
        for (int i = tid; i < S_; i += K2_THREADS) {
            float v = g_r[i];
            if (i != excl && (v > bv || (v == bv && i < bi) || bi == 0x7fffffff)) { bv = v; bi = i; }
        }
        #pragma unroll
        for (int o = 16; o; o >>= 1) {
            float ov = __shfl_xor_sync(~0u, bv, o); int oi = __shfl_xor_sync(~0u, bi, o);
            if (ov > bv || (ov == bv && oi < bi)) { bv = ov; bi = oi; }
        }
        if (lane == 0) { s_v[warp] = bv; s_i[warp] = bi; }
        __syncthreads();
        if (warp == 0) {
            bv = lane < 16 ? s_v[lane] : -INFINITY; bi = lane < 16 ? s_i[lane] : 0x7fffffff;
            #pragma unroll
            for (int o = 16; o; o >>= 1) {
                float ov = __shfl_xor_sync(~0u, bv, o); int oi = __shfl_xor_sync(~0u, bi, o);
                if (ov > bv || (ov == bv && oi < bi)) { bv = ov; bi = oi; }
            }
            if (lane == 0) s_sel[pass] = (bi == 0x7fffffff) ? pass : bi;
        }
        __syncthreads();
    }
    for (int i = tid; i < 1024; i += K2_THREADS) {
        const int tok = s_sel[i >> 9];
        const float2 st = g_stats[tok];
        xs[i] = ln_elem(__bfloat162float(x[(size_t)tok * D_ + (i & 511)]), st.x, st.y);
    }
    if (part == 0 && tid < 2) g_sel[tid] = s_sel[tid];
    __syncthreads();
    const int c0 = part * 448;
    if (tid < 448) {
        const int cg = tid % 56, ks = tid / 56;
        float a[4][8];
        #pragma unroll
        for (int i = 0; i < 4; i++)
            #pragma unroll
            for (int j = 0; j < 8; j++) a[i][j] = 0.f;
        const __nv_bfloat16* pg = w_gate + (size_t)(ks * 64) * F_ + c0 + cg * 8;
        const __nv_bfloat16* pu = w_up + (size_t)(ks * 64) * F_ + c0 + cg * 8;
        #pragma unroll 8
        for (int k = 0; k < 64; k++) {
            const uint4 gv = __ldg((const uint4*)(pg + (size_t)k * F_));
            const uint4 uv = __ldg((const uint4*)(pu + (size_t)k * F_));
            const float x0 = xs[ks * 64 + k], x1 = xs[512 + ks * 64 + k];
            const uint32_t gu[4] = {gv.x, gv.y, gv.z, gv.w}, uu[4] = {uv.x, uv.y, uv.z, uv.w};
            #pragma unroll
            for (int j = 0; j < 4; j++) {
                const float g0 = bf_lo(gu[j]), g1 = bf_hi(gu[j]), u0 = bf_lo(uu[j]), u1 = bf_hi(uu[j]);
                a[0][2 * j] = fmaf(x0, g0, a[0][2 * j]); a[0][2 * j + 1] = fmaf(x0, g1, a[0][2 * j + 1]);
                a[1][2 * j] = fmaf(x1, g0, a[1][2 * j]); a[1][2 * j + 1] = fmaf(x1, g1, a[1][2 * j + 1]);
                a[2][2 * j] = fmaf(x0, u0, a[2][2 * j]); a[2][2 * j + 1] = fmaf(x0, u1, a[2][2 * j + 1]);
                a[3][2 * j] = fmaf(x1, u0, a[3][2 * j]); a[3][2 * j + 1] = fmaf(x1, u1, a[3][2 * j + 1]);
            }
        }
        #pragma unroll
        for (int i = 0; i < 4; i++)
            #pragma unroll
            for (int j = 0; j < 8; j++) red[(ks * 4 + i) * 448 + cg * 8 + j] = a[i][j];
    }
    __syncthreads();
    for (int i = tid; i < 896; i += K2_THREADS) {
        const int tok = i / 448, c = i % 448;
        float gs = 0.f, us = 0.f;
        #pragma unroll
        for (int ks = 0; ks < 8; ks++) { gs += red[(ks * 4 + tok) * 448 + c]; us += red[(ks * 4 + 2 + tok) * 448 + c]; }
        gs = bf16r(gs); us = bf16r(us);
        const float sl = bf16r(gs / (1.0f + __expf(-gs)));
        hs[i] = bf16r(sl * us);
    }
    __syncthreads();
    {
        const int cg = tid & 63, fs = tid >> 6;
        float a[2][8];
        #pragma unroll
        for (int j = 0; j < 8; j++) { a[0][j] = 0.f; a[1][j] = 0.f; }
        const __nv_bfloat16* pd = w_down + (size_t)(c0 + fs * 56) * D_ + cg * 8;
        #pragma unroll 8
        for (int f = 0; f < 56; f++) {
            const uint4 dv = __ldg((const uint4*)(pd + (size_t)f * D_));
            const float h0 = hs[fs * 56 + f], h1 = hs[448 + fs * 56 + f];
            const uint32_t du[4] = {dv.x, dv.y, dv.z, dv.w};
            #pragma unroll
            for (int j = 0; j < 4; j++) {
                const float d0 = bf_lo(du[j]), d1 = bf_hi(du[j]);
                a[0][2 * j] = fmaf(h0, d0, a[0][2 * j]); a[0][2 * j + 1] = fmaf(h0, d1, a[0][2 * j + 1]);
                a[1][2 * j] = fmaf(h1, d0, a[1][2 * j]); a[1][2 * j + 1] = fmaf(h1, d1, a[1][2 * j + 1]);
            }
        }
        #pragma unroll
        for (int j = 0; j < 8; j++) { red[(fs * 2) * 512 + cg * 8 + j] = a[0][j]; red[(fs * 2 + 1) * 512 + cg * 8 + j] = a[1][j]; }
    }
    __syncthreads();
    for (int i = tid; i < 1024; i += K2_THREADS) {
        float s = 0.f;
        #pragma unroll
        for (int fs = 0; fs < 8; fs++) s += red[(fs * 2 + (i >> 9)) * 512 + (i & 511)];
        g_ypart[part][i >> 9][i & 511] = s;
    }
}

__global__ void __launch_bounds__(K2_THREADS, 1)
k2_attn(const __nv_bfloat16* __restrict__ x, const __nv_bfloat16* __restrict__ w_gate, const __nv_bfloat16* __restrict__ w_up,
        const __nv_bfloat16* __restrict__ w_down) {
    extern __shared__ __align__(1024) unsigned char smem[];
    if (blockIdx.x >= 128) { moe_cta(blockIdx.x - 128, smem, x, w_gate, w_up, w_down); return; }
    const uint32_t sK = smem_u32(smem), sV = sK + 65536, sQ = sV + 98304, sBar = sQ + 16384;
    const int h = blockIdx.x >> 2, qb = blockIdx.x & 3;
    const int warp = threadIdx.x >> 5, lane = threadIdx.x & 31, wg = warp >> 2;
    if (threadIdx.x == 0) {
        mbar_init(sBar, 1); mbar_init(sBar + 8, 1);
        asm volatile("fence.mbarrier_init.release.cluster;" ::: "memory");
        const uint4* gk = g_K + (size_t)h * 4096;
        const uint4* gv = g_V + (size_t)h * 4096;
        mbar_expect_tx(sBar, 16384 + 16384 + 2 * 8192);
        bulk_g2s(sQ, g_Q + (size_t)h * 4096 + qb * 1024, 16384, sBar);
        bulk_g2s(sK, gk, 16384, sBar);
        bulk_g2s(sV, gv, 8192, sBar);
        bulk_g2s(sV + 32768, gv + 2048, 8192, sBar);
        mbar_expect_tx(sBar + 8, 49152 + 2 * 24576);
        bulk_g2s(sK + 16384, gk + 1024, 49152, sBar + 8);
        bulk_g2s(sV + 8192, gv + 512, 24576, sBar + 8);
        bulk_g2s(sV + 32768 + 8192, gv + 2048 + 512, 24576, sBar + 8);
    }
    for (int i = threadIdx.x; i < 2048; i += K2_THREADS) {
        const uint32_t v = is_poly_group(i >> 3) ? 0xBF80BF80u : 0x3F803F80u;
        *(uint4*)(smem + 65536 + 65536 + i * 16) = make_uint4(v, v, v, v);
    }
    fence_async_smem();
    __syncthreads();
    ExpC c;
    c.c421 = __shfl_sync(~0u, 421u, lane);
    c.c3 = __shfl_sync(~0u, 5078.315f, lane);
    c.one = __shfl_sync(~0u, 1.0f, lane);
    const uint64_t kdesc0 = make_desc(sK, 128, 256, 0);
    const uint64_t vdesc0 = make_desc(sV, 128, 32768, 0);
    mbar_wait(sBar, 0);
    #pragma unroll 1
    for (int pass = 0; pass < 2; pass++) {
        const int unit = pass * 4 + wg;
        const uint64_t q = make_desc(sQ + unit * 2048, 128, 256, 0);
        float o[12];
        #pragma unroll 1
        for (int attempt = 0; attempt < 2; attempt++) {
            float s0[16], s1[16], s2[16];
            #pragma unroll
            for (int i = 0; i < 16; i++) { s0[i] = 0.f; s1[i] = 0.f; s2[i] = 0.f; }
            float mx0 = -INFINITY, mx1 = -INFINITY;
            if (attempt) {
                #pragma unroll 1
                for (int it = 0; it < 64; it++) {
                    WG_FENCE();
                    wgmma_qk32(s0, q, kdesc0 + (uint64_t)(it * 64));
                    WG_COMMIT();
                    wg_wait<0>();
                    touch16(s0);
                    max16(s0, mx0, mx1);
                }
            }
            #pragma unroll
            for (int i = 0; i < 12; i++) o[i] = 0.f;
            WG_FENCE();
            wgmma_qk32(s2, q, kdesc0);
            wgmma_qk32(s0, q, kdesc0 + 64);
            wgmma_qk32(s1, q, kdesc0 + 128);
            WG_COMMIT();
            wg_wait<0>();
            touch16(s0); touch16(s1); touch16(s2);
            max16(s0, mx0, mx1); max16(s1, mx0, mx1); max16(s2, mx0, mx1);
            mx0 = fmaxf(mx0, __shfl_xor_sync(~0u, mx0, 1)); mx0 = fmaxf(mx0, __shfl_xor_sync(~0u, mx0, 2));
            mx1 = fmaxf(mx1, __shfl_xor_sync(~0u, mx1, 1)); mx1 = fmaxf(mx1, __shfl_xor_sync(~0u, mx1, 2));
            const float bias = attempt ? 0.0f : 64.0f;
            c.nm0 = __shfl_sync(~0u, -(mx0 + bias), lane); c.nm1 = __shfl_sync(~0u, -(mx1 + bias), lane);
            c.cb0 = __shfl_sync(~0u, (127.0f + c.nm0) * (1.0f / 255.0f), lane);
            c.cb1 = __shfl_sync(~0u, (127.0f + c.nm1) * (1.0f / 255.0f), lane);
            uint64_t kd = kdesc0 + 192, vd = vdesc0 + 32;
            {
                uint32_t pa[4], pb[4];
                exp_block<12>(s2, pa, c);
                exp_block<14>(s2 + 8, pb, c);
                WG_FENCE();
                wgmma_pv(o, pa, vdesc0); wgmma_pv(o, pb, vdesc0 + 16);
                WG_COMMIT();
            }
            #pragma unroll 1
            for (int it = 0; it < 21; it++) {
                if (it == 3) mbar_wait(sBar + 8, 0);
                uint32_t p[6][4];
                WG_FENCE();
                wgmma_qk32(s2, q, kd);
                WG_COMMIT();
                exp_block<0>(s0, p[0], c);
                exp_block<2>(s0 + 8, p[1], c);
                WG_FENCE();
                wgmma_pv(o, p[0], vd); wgmma_pv(o, p[1], vd + 16);
                wgmma_qk32(s0, q, kd + 64);
                WG_COMMIT();
                wg_wait<1>();
                touch16(s2);
                exp_block<4>(s1, p[2], c);
                exp_block<6>(s1 + 8, p[3], c);
                WG_FENCE();
                wgmma_pv(o, p[2], vd + 32); wgmma_pv(o, p[3], vd + 48);
                wgmma_qk32(s1, q, kd + 128);
                WG_COMMIT();
                wg_wait<1>();
                touch16(s0);
                exp_block<8>(s2, p[4], c);
                exp_block<10>(s2 + 8, p[5], c);
                WG_FENCE();
                wgmma_pv(o, p[4], vd + 64); wgmma_pv(o, p[5], vd + 80);
                WG_COMMIT();
                vd += 96; kd += 192;
                wg_wait<1>();
                touch16(s1);
            }
            wg_wait<0>();
            touch12(o);
            if (attempt) break;
            float big = 0.f;
            #pragma unroll
            for (int i = 0; i < 12; i++) big = fmaxf(big, fabsf(o[i]));
            bool bad = !(big < 1e30f);
            #pragma unroll
            for (int i = 0; i < 12; i++) bad |= (o[i] != o[i]);
            uint32_t any;
            asm volatile("{.reg .pred p, q; setp.ne.u32 p, %1, 0; barrier.cta.red.or.pred.aligned q, %2, 128, p; selp.u32 %0, 1, 0, q;}"
                         : "=r"(any) : "r"((uint32_t)bad), "r"(1 + wg) : "memory");
            if (!any) break;
        }
        const int g = lane >> 2, t = lane & 3;
        const int r = (warp & 3) * 16 + g;
        const float i0 = __fdiv_rn(1.0f, o[8]), i1 = __fdiv_rn(1.0f, o[10]);
        uint32_t* ob = (uint32_t*)(g_O + (size_t)(qb * 8 + unit) * 4096 + (h >> 2) * 512 + r * 8) + t;
        const int c0 = ((h & 3) * 2) ^ (r & 7), c1 = ((h & 3) * 2 + 1) ^ (r & 7);
        ob[c0 * 4] = pack_bf16(o[0] * i0, o[1] * i0);
        ob[c1 * 4] = pack_bf16(o[4] * i0, o[5] * i0);
        ob[256 + c0 * 4] = pack_bf16(o[2] * i1, o[3] * i1);
        ob[256 + c1 * 4] = pack_bf16(o[6] * i1, o[7] * i1);
    }
}

constexpr int K3_THREADS = 256;
constexpr int K3_SMEM = 65536 + 131072 + 128;

__global__ void __launch_bounds__(K3_THREADS, 1)
k3_out(const __grid_constant__ CUtensorMap wmap, const __nv_bfloat16* __restrict__ x, __nv_bfloat16* __restrict__ out) {
    extern __shared__ __align__(1024) unsigned char smem[];
    const uint32_t sA = smem_u32(smem), sB = sA + 65536, sBar = sB + 131072;
    const int warp = threadIdx.x >> 5, lane = threadIdx.x & 31, wg = warp >> 2;
    const int nt = blockIdx.x & 3, mt = blockIdx.x >> 2;
    if (threadIdx.x == 0) {
        for (int i = 0; i < 8; i++) mbar_init(sBar + i * 8, 1);
        asm volatile("fence.mbarrier_init.release.cluster;" ::: "memory");
        for (int kc = 0; kc < 8; kc++) {
            mbar_expect_tx(sBar + kc * 8, 8192 + 16384);
            tma_2d(sB + kc * 16384, &wmap, nt * 128, kc * 64, sBar + kc * 8);
            tma_2d(sB + kc * 16384 + 8192, &wmap, nt * 128 + 64, kc * 64, sBar + kc * 8);
            bulk_g2s(sA + kc * 8192, g_O + (size_t)mt * 4096 + kc * 512, 8192, sBar + kc * 8);
        }
    }
    __syncthreads();
    float acc[32];
    #pragma unroll
    for (int i = 0; i < 32; i++) acc[i] = 0.f;
    const uint64_t da0 = make_desc(sA, 16, 1024, 1);
    const uint64_t db0 = make_desc(sB + wg * 8192, 8192, 1024, 1);
    #pragma unroll 1
    for (int kc = 0; kc < 8; kc++) {
        mbar_wait(sBar + kc * 8, 0);
        WG_FENCE();
        #pragma unroll
        for (int kk = 0; kk < 4; kk++)
            wgmma_n64(acc, da0 + (uint64_t)(kc * 512 + kk * 2), db0 + (uint64_t)(kc * 1024 + kk * 128));
        WG_COMMIT();
    }
    wg_wait<0>();
    touch32(acc);
    const int g = lane >> 2, t = lane & 3;
    const int sel0 = g_sel[0], sel1 = g_sel[1];
    #pragma unroll
    for (int hf = 0; hf < 2; hf++) {
        const int row = mt * 64 + (warp & 3) * 16 + g + hf * 8;
        const float2 st = g_stats[row];
        const int slot = row == sel0 ? 0 : (row == sel1 ? 1 : -1);
        float gate = 0.f;
        if (slot >= 0) gate = bf16r(1.0f / (1.0f + __expf(-g_r[row])));
        #pragma unroll
        for (int j = 0; j < 8; j++) {
            const int col = nt * 128 + wg * 64 + j * 8 + t * 2;
            const uint32_t xu = __ldg((const uint32_t*)(x + (size_t)row * D_ + col));
            const float x0 = bf_lo(xu), x1 = bf_hi(xu);
            float b0 = ln_elem(x0, st.x, st.y), b1 = ln_elem(x1, st.x, st.y);
            if (slot >= 0) {
                float y0 = g_ypart[0][slot][col] + g_ypart[1][slot][col] + g_ypart[2][slot][col] + g_ypart[3][slot][col];
                float y1 = g_ypart[0][slot][col + 1] + g_ypart[1][slot][col + 1] + g_ypart[2][slot][col + 1] + g_ypart[3][slot][col + 1];
                b0 = bf16r(b0 + bf16r(bf16r(y0) * gate));
                b1 = bf16r(b1 + bf16r(bf16r(y1) * gate));
            }
            const float t0 = bf16r(x0 + bf16r(acc[4 * j + hf * 2])), t1 = bf16r(x1 + bf16r(acc[4 * j + hf * 2 + 1]));
            *(uint32_t*)(out + (size_t)row * D_ + col) = pack_bf16(t0 + b0, t1 + b1);
        }
    }
}

typedef CUresult (*EncodeFn)(CUtensorMap*, CUtensorMapDataType, cuuint32_t, void*, const cuuint64_t*, const cuuint64_t*,
                             const cuuint32_t*, const cuuint32_t*, CUtensorMapInterleave, CUtensorMapSwizzle,
                             CUtensorMapL2promotion, CUtensorMapFloatOOBfill);

void make_wmap(EncodeFn fn, CUtensorMap* map, const void* ptr, int rows, int cols) {
    cuuint64_t dims[2] = {(cuuint64_t)cols, (cuuint64_t)rows};
    cuuint64_t strides[1] = {(cuuint64_t)cols * 2};
    cuuint32_t box[2] = {64, 64};
    cuuint32_t es[2] = {1, 1};
    fn(map, CU_TENSOR_MAP_DATA_TYPE_BFLOAT16, 2, (void*)ptr, dims, strides, box, es, CU_TENSOR_MAP_INTERLEAVE_NONE,
       CU_TENSOR_MAP_SWIZZLE_128B, CU_TENSOR_MAP_L2_PROMOTION_L2_256B, CU_TENSOR_MAP_FLOAT_OOB_FILL_NONE);
}

}

extern "C" void kernel_launch(void* const* d_in, const int* in_sizes, int n_in, void* d_out, int out_size) {
    const __nv_bfloat16* x = (const __nv_bfloat16*)d_in[0];
    const __nv_bfloat16* wqkv = (const __nv_bfloat16*)d_in[1];
    const __nv_bfloat16* wo = (const __nv_bfloat16*)d_in[2];
    const __nv_bfloat16* w_r = (const __nv_bfloat16*)d_in[4];
    const __nv_bfloat16* w_gate = (const __nv_bfloat16*)d_in[5];
    const __nv_bfloat16* w_up = (const __nv_bfloat16*)d_in[6];
    const __nv_bfloat16* w_down = (const __nv_bfloat16*)d_in[7];
    __nv_bfloat16* out = (__nv_bfloat16*)d_out;

    static EncodeFn encode = nullptr;
    if (!encode) {
        void* fn = nullptr;
        cudaDriverEntryPointQueryResult qres;
        cudaGetDriverEntryPoint("cuTensorMapEncodeTiled", &fn, cudaEnableDefault, &qres);
        encode = (EncodeFn)fn;
        cudaFuncSetAttribute(k1_ln_qkv, cudaFuncAttributeMaxDynamicSharedMemorySize, K1_SMEM);
        cudaFuncSetAttribute(k2_attn, cudaFuncAttributeMaxDynamicSharedMemorySize, K2_SMEM);
        cudaFuncSetAttribute(k3_out, cudaFuncAttributeMaxDynamicSharedMemorySize, K3_SMEM);
    }
    CUtensorMap map_qkv, map_wo;
    make_wmap(encode, &map_qkv, wqkv, D_, 3 * D_);
    make_wmap(encode, &map_wo, wo, D_, D_);

    k1_ln_qkv<<<128, K1_THREADS, K1_SMEM>>>(map_qkv, x, w_r);
    k2_attn<<<132, K2_THREADS, K2_SMEM>>>(x, w_gate, w_up, w_down);
    k3_out<<<128, K3_THREADS, K3_SMEM>>>(map_wo, x, out);
}
```

```cpp
#include <cuda_runtime.h>
#include <cuda_bf16.h>
#include <cuda.h>
#include <stdint.h>

namespace {

constexpr int S_ = 2048, D_ = 512, H_ = 32, F_ = 1792;

constexpr uint32_t PMASK = 0xA52;
__host__ __device__ constexpr bool is_poly_group(int g8) { return g8 >= 4 && ((PMASK >> ((g8 - 4) % 12)) & 1); }

__device__ __align__(1024) uint4 g_QKV[3 * H_ * S_ * 2];
#define g_Q (g_QKV)
#define g_K (g_QKV + H_ * S_ * 2)
#define g_V (g_QKV + 2 * H_ * S_ * 2)
__device__ __align__(1024) uint4 g_O[S_ * D_ / 8];
__device__ float2 g_stats[S_];
__device__ uint32_t g_const[4] = {421u, 0x459EB285u  , 0x3F800000u  , 0u};
__device__ float g_r[S_];
__device__ float g_ypart[4][2][D_];
__device__ int g_sel[2];

__device__ __forceinline__ uint32_t smem_u32(const void* p) { return (uint32_t)__cvta_generic_to_shared(p); }
__device__ __forceinline__ float bf16r(float x) { return __bfloat162float(__float2bfloat16_rn(x)); }
__device__ __forceinline__ uint32_t pack_bf16(float lo, float hi) {
    uint32_t r; asm("cvt.rn.bf16x2.f32 %0, %1, %2;" : "=r"(r) : "f"(hi), "f"(lo)); return r;
}
__device__ __forceinline__ float bf_lo(uint32_t u) { return __uint_as_float(u << 16); }
__device__ __forceinline__ float bf_hi(uint32_t u) { return __uint_as_float(u & 0xFFFF0000u); }
__device__ __forceinline__ float ex2(float x) { float y; asm("ex2.approx.ftz.f32 %0, %1;" : "=f"(y) : "f"(x)); return y; }

__device__ __forceinline__ void mbar_init(uint32_t bar, uint32_t count) {
    asm volatile("mbarrier.init.shared::cta.b64 [%0], %1;" :: "r"(bar), "r"(count) : "memory");
}
__device__ __forceinline__ void mbar_expect_tx(uint32_t bar, uint32_t bytes) {
    asm volatile("mbarrier.arrive.expect_tx.shared::cta.b64 _, [%0], %1;" :: "r"(bar), "r"(bytes) : "memory");
}
__device__ __forceinline__ void mbar_arrive(uint32_t bar) {
    asm volatile("mbarrier.arrive.shared::cta.b64 _, [%0];" :: "r"(bar) : "memory");
}
__device__ __forceinline__ void mbar_wait(uint32_t bar, uint32_t parity) {
    uint32_t done;
    #pragma unroll 1
    for (int it = 0; it < (1 << 26); it++) {
        asm volatile("{.reg .pred p; mbarrier.try_wait.parity.shared::cta.b64 p, [%1], %2; selp.u32 %0, 1, 0, p;}"
                     : "=r"(done) : "r"(bar), "r"(parity) : "memory");
        if (done) return;
    }
    __trap();
}
__device__ __forceinline__ void bulk_g2s(uint32_t dst, const void* src, uint32_t bytes, uint32_t bar) {
    asm volatile("cp.async.bulk.shared::cluster.global.mbarrier::complete_tx::bytes [%0], [%1], %2, [%3];"
                 :: "r"(dst), "l"(src), "r"(bytes), "r"(bar) : "memory");
}
__device__ __forceinline__ void tma_2d(uint32_t dst, const CUtensorMap* map, int c0, int c1, uint32_t bar) {
    asm volatile("cp.async.bulk.tensor.2d.shared::cluster.global.mbarrier::complete_tx::bytes [%0], [%1, {%3, %4}], [%2];"
                 :: "r"(dst), "l"(map), "r"(bar), "r"(c0), "r"(c1) : "memory");
}
__device__ __forceinline__ void fence_async_smem() { asm volatile("fence.proxy.async.shared::cta;" ::: "memory"); }
__device__ __forceinline__ void named_bar(int id, int n) { asm volatile("bar.sync %0, %1;" :: "r"(id), "r"(n) : "memory"); }

__device__ __forceinline__ uint64_t make_desc(uint32_t saddr, uint32_t lbo, uint32_t sbo, uint32_t swz) {
    return (uint64_t)((saddr & 0x3FFFF) >> 4) | ((uint64_t)(lbo >> 4) << 16) | ((uint64_t)(sbo >> 4) << 32) | ((uint64_t)swz << 62);
}
#define WG_FENCE() asm volatile("wgmma.fence.sync.aligned;" ::: "memory")
#define WG_COMMIT() asm volatile("wgmma.commit_group.sync.aligned;" ::: "memory")
template <int N> __device__ __forceinline__ void wg_wait() { asm volatile("wgmma.wait_group.sync.aligned %0;" :: "n"(N) : "memory"); }

#define F4(d, o) "+f"(d[o]), "+f"(d[o + 1]), "+f"(d[o + 2]), "+f"(d[o + 3])
#define F16(d, o) F4(d, o), F4(d, o + 4), F4(d, o + 8), F4(d, o + 12)
#define F32(d, o) F16(d, o), F16(d, o + 16)

__device__ __forceinline__ void wgmma_n192(float* d, uint64_t da, uint64_t db) {
    asm volatile("wgmma.mma_async.sync.aligned.m64n192k16.f32.bf16.bf16 "
        "{%0,%1,%2,%3,%4,%5,%6,%7,%8,%9,%10,%11,%12,%13,%14,%15,%16,%17,%18,%19,%20,%21,%22,%23,%24,%25,%26,%27,%28,%29,%30,%31,"
        "%32,%33,%34,%35,%36,%37,%38,%39,%40,%41,%42,%43,%44,%45,%46,%47,%48,%49,%50,%51,%52,%53,%54,%55,%56,%57,%58,%59,%60,%61,%62,%63,"
        "%64,%65,%66,%67,%68,%69,%70,%71,%72,%73,%74,%75,%76,%77,%78,%79,%80,%81,%82,%83,%84,%85,%86,%87,%88,%89,%90,%91,%92,%93,%94,%95}, "
        "%96, %97, 1, 1, 1, 0, 1;\n"
        : F32(d, 0), F32(d, 32), F32(d, 64) : "l"(da), "l"(db));
}
__device__ __forceinline__ void wgmma_n64(float* d, uint64_t da, uint64_t db) {
    asm volatile("wgmma.mma_async.sync.aligned.m64n64k16.f32.bf16.bf16 "
        "{%0,%1,%2,%3,%4,%5,%6,%7,%8,%9,%10,%11,%12,%13,%14,%15,%16,%17,%18,%19,%20,%21,%22,%23,%24,%25,%26,%27,%28,%29,%30,%31}, "
        "%32, %33, 1, 1, 1, 0, 1;\n"
        : F32(d, 0) : "l"(da), "l"(db));
}
__device__ __forceinline__ void wgmma_qk32(float* d, uint64_t qd, uint64_t kd) {
    asm volatile("wgmma.mma_async.sync.aligned.m64n32k16.f32.bf16.bf16 {%0,%1,%2,%3,%4,%5,%6,%7,%8,%9,%10,%11,%12,%13,%14,%15}, %16, %17, 0, 1, 1, 0, 0;\n"
        : F16(d, 0) : "l"(qd), "l"(kd));
}
__device__ __forceinline__ void wgmma_pv(float* d, const uint32_t* a, uint64_t vd) {
    asm volatile("wgmma.mma_async.sync.aligned.m64n24k16.f32.bf16.bf16 {%0,%1,%2,%3,%4,%5,%6,%7,%8,%9,%10,%11}, {%12,%13,%14,%15}, %16, 1, 1, 1, 1;\n"
        : F4(d, 0), F4(d, 4), F4(d, 8) : "r"(a[0]), "r"(a[1]), "r"(a[2]), "r"(a[3]), "l"(vd));
}
__device__ __forceinline__ void touch16(float* d) { asm volatile("" : F16(d, 0) :: "memory"); }
__device__ __forceinline__ void touch12(float* d) { asm volatile("" : F4(d, 0), F4(d, 4), F4(d, 8) :: "memory"); }
__device__ __forceinline__ void touch32(float* d) { asm volatile("" : F32(d, 0) :: "memory"); }
__device__ __forceinline__ void touch96(float* d) { asm volatile("" : F32(d, 0), F32(d, 32), F32(d, 64) :: "memory"); }

__device__ __forceinline__ float ln_elem(float x, float mean_b, float rden) {
    return bf16r(bf16r(x - mean_b) * rden);
}
__device__ __forceinline__ void pdl_wait() { asm volatile("griddepcontrol.wait;" ::: "memory"); }
__device__ __forceinline__ void pdl_launch() { asm volatile("griddepcontrol.launch_dependents;" ::: "memory"); }
__device__ __forceinline__ void cluster_arrive() { asm volatile("barrier.cluster.arrive.release.aligned;" ::: "memory"); }
__device__ __forceinline__ void cluster_wait() { asm volatile("barrier.cluster.wait.acquire.aligned;" ::: "memory"); }

constexpr int K1_THREADS = 288;
constexpr int K1_SMEM = 131072 + 4 * 24576 + 128;

__global__ void __cluster_dims__(2, 1, 1) __launch_bounds__(K1_THREADS, 1)
k1_ln_qkv(const __grid_constant__ CUtensorMap wmap, const __nv_bfloat16* __restrict__ x, const __nv_bfloat16* __restrict__ w_r) {
    extern __shared__ __align__(1024) unsigned char smem[];
    const uint32_t sA = smem_u32(smem), sB = sA + 131072, sBar = sB + 4 * 24576;
    const int warp = __shfl_sync(~0u, threadIdx.x >> 5, 0), lane = threadIdx.x & 31;
    const int nt = blockIdx.x & 7, mt = blockIdx.x >> 3, rank = blockIdx.x & 1;
    if (threadIdx.x == 0) {
        for (int i = 0; i < 4; i++) { mbar_init(sBar + i * 8, 1); mbar_init(sBar + 32 + i * 8, 2); }
        mbar_init(sBar + 64, 1);
        asm volatile("fence.mbarrier_init.release.cluster;" ::: "memory");
        mbar_expect_tx(sBar + 64, 65536);
    }
    __syncthreads();
    cluster_arrive();
    pdl_launch();
    if (warp == 8) {
        if (lane == 0) {
            for (int kc = 0; kc < 8; kc++) {
                const int st = kc & 3;
                if (kc >= 4) mbar_wait(sBar + 32 + st * 8, 0);
                mbar_expect_tx(sBar + st * 8, 24576);
                for (int j = 0; j < 3; j++) tma_2d(sB + st * 24576 + j * 8192, &wmap, nt * 192 + j * 64, kc * 64, sBar + st * 8);
            }
        }
        __syncwarp();
        cluster_wait();
        cluster_arrive();
        cluster_wait();
        return;
    }
    const int rbase = rank * 64 + warp * 8;
    uint4 raw[8][2];
    #pragma unroll
    for (int i = 0; i < 8; i++) {
        const __nv_bfloat16* xp = x + (size_t)(mt * 128 + rbase + i) * D_;
        raw[i][0] = __ldg((const uint4*)(xp + lane * 8));
        raw[i][1] = __ldg((const uint4*)(xp + 256 + lane * 8));
    }
    uint4 wr0 = make_uint4(0, 0, 0, 0), wr1 = wr0;
    if (nt < 2) { wr0 = __ldg((const uint4*)(w_r + lane * 8)); wr1 = __ldg((const uint4*)(w_r + 256 + lane * 8)); }
    #pragma unroll 2
    for (int i = 0; i < 8; i++) {
        const int r = rbase + i;
        uint32_t u[8] = {raw[i][0].x, raw[i][0].y, raw[i][0].z, raw[i][0].w, raw[i][1].x, raw[i][1].y, raw[i][1].z, raw[i][1].w};
        float v[16];
        #pragma unroll
        for (int j = 0; j < 8; j++) { v[2 * j] = bf_lo(u[j]); v[2 * j + 1] = bf_hi(u[j]); }
        float s = 0.f;
        #pragma unroll
        for (int j = 0; j < 16; j++) s += v[j];
        #pragma unroll
        for (int o = 16; o; o >>= 1) s += __shfl_xor_sync(~0u, s, o);
        const float mean = s * (1.0f / D_);
        float q = 0.f;
        #pragma unroll
        for (int j = 0; j < 16; j++) { float d = v[j] - mean; q = fmaf(d, d, q); }
        #pragma unroll
        for (int o = 16; o; o >>= 1) q += __shfl_xor_sync(~0u, q, o);
        const float mean_b = bf16r(mean);
        const float var_b = bf16r(q * (1.0f / D_));
        const float rden = __frcp_rn(bf16r(__fsqrt_rn(bf16r(var_b + 1e-5f))));
        #pragma unroll
        for (int j = 0; j < 8; j++) {
            const uint32_t d2 = pack_bf16(v[2 * j] - mean_b, v[2 * j + 1] - mean_b);
            u[j] = pack_bf16(bf_lo(d2) * rden, bf_hi(d2) * rden);
        }
        const int ch = (lane & 7) ^ (r & 7);
        *(uint4*)(smem + (lane >> 3) * 16384 + r * 128 + ch * 16) = make_uint4(u[0], u[1], u[2], u[3]);
        *(uint4*)(smem + (4 + (lane >> 3)) * 16384 + r * 128 + ch * 16) = make_uint4(u[4], u[5], u[6], u[7]);
        if (nt < 2) {
            const uint32_t w[8] = {wr0.x, wr0.y, wr0.z, wr0.w, wr1.x, wr1.y, wr1.z, wr1.w};
            float acc = 0.f;
            #pragma unroll
            for (int j = 0; j < 8; j++) { acc = fmaf(bf_lo(u[j]), bf_lo(w[j]), acc); acc = fmaf(bf_hi(u[j]), bf_hi(w[j]), acc); }
            #pragma unroll
            for (int o = 16; o; o >>= 1) acc += __shfl_xor_sync(~0u, acc, o);
            if (lane == 0) { g_r[mt * 128 + r] = bf16r(acc); g_stats[mt * 128 + r] = make_float2(mean_b, rden); }
        }
    }
    fence_async_smem();
    cluster_wait();
    named_bar(1, 256);
    const int wg = warp >> 2;
    if (lane == 0) {
        uint32_t dst, rbar;
        const uint32_t src = sA + warp * 16384 + rank * 8192;
        asm volatile("mapa.shared::cluster.u32 %0, %1, %2;" : "=r"(dst) : "r"(src), "r"(rank ^ 1));
        asm volatile("mapa.shared::cluster.u32 %0, %1, %2;" : "=r"(rbar) : "r"(sBar + 64), "r"(rank ^ 1));
        asm volatile("cp.async.bulk.shared::cluster.shared::cta.mbarrier::complete_tx::bytes [%0], [%1], %2, [%3];"
                     :: "r"(dst), "r"(src), "r"(8192), "r"(rbar) : "memory");
    }
    __syncwarp();
    if (wg != rank) mbar_wait(sBar + 64, 0);
    float acc[96];
    #pragma unroll
    for (int i = 0; i < 96; i++) acc[i] = 0.f;
    const uint64_t da0 = make_desc(sA + wg * 8192, 16, 1024, 1);
    const uint64_t db0 = make_desc(sB, 8192, 1024, 1);
    #pragma unroll 1
    for (int kc = 0; kc < 8; kc++) {
        const int st = kc & 3;
        mbar_wait(sBar + st * 8, kc >> 2);
        WG_FENCE();
        #pragma unroll
        for (int kk = 0; kk < 4; kk++)
            wgmma_n192(acc, da0 + (uint64_t)(kc * 1024 + kk * 2), db0 + (uint64_t)(st * 1536 + kk * 128));
        WG_COMMIT();
        wg_wait<1>();
        if (kc >= 1 && kc <= 4 && (threadIdx.x & 127) == 0) mbar_arrive(sBar + 32 + (kc - 1) * 8);
    }
    wg_wait<0>();
    touch96(acc);
    if (wg == rank) mbar_wait(sBar + 64, 0);
    cluster_arrive();
    const int g = lane >> 2, t = lane & 3;
    const int row0 = mt * 128 + warp * 16;
    const int g8a = row0 >> 3;
    const float sgn0 = is_poly_group(g8a) ? -1.f : 1.f, sgn1 = is_poly_group(g8a + 1) ? -1.f : 1.f;
    constexpr float QS = 0.25f * 1.4426950408889634f;
    const int off_qk = g8a * 64 + g * 4 + t, off_v = (row0 + g) * 4 + t;
    #pragma unroll
    for (int jj = 0; jj < 12; jj++) {
        const int hg = nt * 12 + jj;
        const bool isv = hg >= 64;
        const float m0 = isv ? sgn0 : (hg < 32 ? QS : 1.0f), m1 = isv ? sgn1 : (hg < 32 ? QS : 1.0f);
        uint32_t* base = (uint32_t*)g_QKV + (size_t)hg * 16384 + (isv ? off_v : off_qk);
        const int hs = isv ? 8192 : 32, rs = isv ? 32 : 64;
        base[0] = pack_bf16(acc[8 * jj] * m0, acc[8 * jj + 1] * m0);
        base[rs] = pack_bf16(acc[8 * jj + 2] * m1, acc[8 * jj + 3] * m1);
        base[hs] = pack_bf16(acc[8 * jj + 4] * m0, acc[8 * jj + 5] * m0);
        base[hs + rs] = pack_bf16(acc[8 * jj + 6] * m1, acc[8 * jj + 7] * m1);
    }
    cluster_wait();
}

constexpr int K2_THREADS = 512;
constexpr int K2_SMEM = 65536 + 98304 + 16384 + 128;

__device__ __forceinline__ uint32_t polyexp(float s, float cb, uint32_t c421, float c3, float one) {
    float u;
    asm("fma.rn.sat.f32 %0, %1, 0f3B808081, %2;" : "=f"(u) : "f"(s), "f"(cb));
    float z = fmaf(u, 0.99609375f, one);
    uint32_t rb;
    asm("lop3.b32 %0, %1, 0xFFFF8000, %2, 0xEA;" : "=r"(rb) : "r"(__float_as_uint(z)), "r"(c421));
    float f = z - __uint_as_float(rb);
    float h = fmaf(f, c3, 58.86525f);
    h = fmaf(f, h, -0.29870507f);
    return __float_as_uint(fmaf(f, h, z));
}

struct ExpC { float nm0, nm1, cb0, cb1, c3, one; uint32_t c421; };

template <int G>
__device__ __forceinline__ void exp_block(const float* s, uint32_t* p, const ExpC& c) {
    #pragma unroll
    for (int hf = 0; hf < 2; hf++) {
        const float* x = s + hf * 4;
        if ((PMASK >> (G + hf)) & 1) {
            p[hf * 2 + 0] = __byte_perm(polyexp(x[0], c.cb0, c.c421, c.c3, c.one), polyexp(x[1], c.cb0, c.c421, c.c3, c.one), 0x6521);
            p[hf * 2 + 1] = __byte_perm(polyexp(x[2], c.cb1, c.c421, c.c3, c.one), polyexp(x[3], c.cb1, c.c421, c.c3, c.one), 0x6521);
        } else {
            p[hf * 2 + 0] = pack_bf16(ex2(x[0] + c.nm0), ex2(x[1] + c.nm0));
            p[hf * 2 + 1] = pack_bf16(ex2(x[2] + c.nm1), ex2(x[3] + c.nm1));
        }
    }
}

__device__ __forceinline__ void max16(const float* s, float& mx0, float& mx1) {
    #pragma unroll
    for (int j = 0; j < 4; j++) {
        mx0 = fmaxf(mx0, fmaxf(s[4 * j], s[4 * j + 1]));
        mx1 = fmaxf(mx1, fmaxf(s[4 * j + 2], s[4 * j + 3]));
    }
}

__device__ void moe_cta(int part, unsigned char* smem, const __nv_bfloat16* __restrict__ x, const __nv_bfloat16* __restrict__ w_gate,
                        const __nv_bfloat16* __restrict__ w_up, const __nv_bfloat16* __restrict__ w_down) {
    float* xs = (float*)smem;
    float* red = xs + 1024;
    float* hs = red + 8 * 4 * 448;
    __shared__ float s_v[32];
    __shared__ int s_i[32];
    __shared__ int s_sel[2];
    const int tid = threadIdx.x, warp = tid >> 5, lane = tid & 31;
    for (int pass = 0; pass < 2; pass++) {
        float bv = -INFINITY; int bi = 0x7fffffff;
        const int excl = pass ? s_sel[0] : -1;
        for (int i = tid; i < S_; i += K2_THREADS) {
            float v = g_r[i];
            if (i != excl && (v > bv || (v == bv && i < bi) || bi == 0x7fffffff)) { bv = v; bi = i; }
        }
        #pragma unroll
        for (int o = 16; o; o >>= 1) {
            float ov = __shfl_xor_sync(~0u, bv, o); int oi = __shfl_xor_sync(~0u, bi, o);
            if (ov > bv || (ov == bv && oi < bi)) { bv = ov; bi = oi; }
        }
        if (lane == 0) { s_v[warp] = bv; s_i[warp] = bi; }
        __syncthreads();
        if (warp == 0) {
            bv = lane < 16 ? s_v[lane] : -INFINITY; bi = lane < 16 ? s_i[lane] : 0x7fffffff;
            #pragma unroll
            for (int o = 16; o; o >>= 1) {
                float ov = __shfl_xor_sync(~0u, bv, o); int oi = __shfl_xor_sync(~0u, bi, o);
                if (ov > bv || (ov == bv && oi < bi)) { bv = ov; bi = oi; }
            }
            if (lane == 0) s_sel[pass] = (bi == 0x7fffffff) ? pass : bi;
        }
        __syncthreads();
    }
    for (int i = tid; i < 1024; i += K2_THREADS) {
        const int tok = s_sel[i >> 9];
        const float2 st = g_stats[tok];
        xs[i] = ln_elem(__bfloat162float(x[(size_t)tok * D_ + (i & 511)]), st.x, st.y);
    }
    if (part == 0 && tid < 2) g_sel[tid] = s_sel[tid];
    __syncthreads();
    const int c0 = part * 448;
    if (tid < 448) {
        const int cg = tid % 56, ks = tid / 56;
        float a[4][8];
        #pragma unroll
        for (int i = 0; i < 4; i++)
            #pragma unroll
            for (int j = 0; j < 8; j++) a[i][j] = 0.f;
        const __nv_bfloat16* pg = w_gate + (size_t)(ks * 64) * F_ + c0 + cg * 8;
        const __nv_bfloat16* pu = w_up + (size_t)(ks * 64) * F_ + c0 + cg * 8;
        #pragma unroll 8
        for (int k = 0; k < 64; k++) {
            const uint4 gv = __ldg((const uint4*)(pg + (size_t)k * F_));
            const uint4 uv = __ldg((const uint4*)(pu + (size_t)k * F_));
            const float x0 = xs[ks * 64 + k], x1 = xs[512 + ks * 64 + k];
            const uint32_t gu[4] = {gv.x, gv.y, gv.z, gv.w}, uu[4] = {uv.x, uv.y, uv.z, uv.w};
            #pragma unroll
            for (int j = 0; j < 4; j++) {
                const float g0 = bf_lo(gu[j]), g1 = bf_hi(gu[j]), u0 = bf_lo(uu[j]), u1 = bf_hi(uu[j]);
                a[0][2 * j] = fmaf(x0, g0, a[0][2 * j]); a[0][2 * j + 1] = fmaf(x0, g1, a[0][2 * j + 1]);
                a[1][2 * j] = fmaf(x1, g0, a[1][2 * j]); a[1][2 * j + 1] = fmaf(x1, g1, a[1][2 * j + 1]);
                a[2][2 * j] = fmaf(x0, u0, a[2][2 * j]); a[2][2 * j + 1] = fmaf(x0, u1, a[2][2 * j + 1]);
                a[3][2 * j] = fmaf(x1, u0, a[3][2 * j]); a[3][2 * j + 1] = fmaf(x1, u1, a[3][2 * j + 1]);
            }
        }
        #pragma unroll
        for (int i = 0; i < 4; i++)
            #pragma unroll
            for (int j = 0; j < 8; j++) red[(ks * 4 + i) * 448 + cg * 8 + j] = a[i][j];
    }
    __syncthreads();
    for (int i = tid; i < 896; i += K2_THREADS) {
        const int tok = i / 448, c = i % 448;
        float gs = 0.f, us = 0.f;
        #pragma unroll
        for (int ks = 0; ks < 8; ks++) { gs += red[(ks * 4 + tok) * 448 + c]; us += red[(ks * 4 + 2 + tok) * 448 + c]; }
        gs = bf16r(gs); us = bf16r(us);
        const float sl = bf16r(gs / (1.0f + __expf(-gs)));
        hs[i] = bf16r(sl * us);
    }
    __syncthreads();
    {
        const int cg = tid & 63, fs = tid >> 6;
        float a[2][8];
        #pragma unroll
        for (int j = 0; j < 8; j++) { a[0][j] = 0.f; a[1][j] = 0.f; }
        const __nv_bfloat16* pd = w_down + (size_t)(c0 + fs * 56) * D_ + cg * 8;
        #pragma unroll 8
        for (int f = 0; f < 56; f++) {
            const uint4 dv = __ldg((const uint4*)(pd + (size_t)f * D_));
            const float h0 = hs[fs * 56 + f], h1 = hs[448 + fs * 56 + f];
            const uint32_t du[4] = {dv.x, dv.y, dv.z, dv.w};
            #pragma unroll
            for (int j = 0; j < 4; j++) {
                const float d0 = bf_lo(du[j]), d1 = bf_hi(du[j]);
                a[0][2 * j] = fmaf(h0, d0, a[0][2 * j]); a[0][2 * j + 1] = fmaf(h0, d1, a[0][2 * j + 1]);
                a[1][2 * j] = fmaf(h1, d0, a[1][2 * j]); a[1][2 * j + 1] = fmaf(h1, d1, a[1][2 * j + 1]);
            }
        }
        #pragma unroll
        for (int j = 0; j < 8; j++) { red[(fs * 2) * 512 + cg * 8 + j] = a[0][j]; red[(fs * 2 + 1) * 512 + cg * 8 + j] = a[1][j]; }
    }
    __syncthreads();
    for (int i = tid; i < 1024; i += K2_THREADS) {
        float s = 0.f;
        #pragma unroll
        for (int fs = 0; fs < 8; fs++) s += red[(fs * 2 + (i >> 9)) * 512 + (i & 511)];
        g_ypart[part][i >> 9][i & 511] = s;
    }
}

__global__ void __launch_bounds__(K2_THREADS, 1)
k2_attn(const __nv_bfloat16* __restrict__ x, const __nv_bfloat16* __restrict__ w_gate, const __nv_bfloat16* __restrict__ w_up,
        const __nv_bfloat16* __restrict__ w_down) {
    extern __shared__ __align__(1024) unsigned char smem[];
    pdl_launch();
    if (blockIdx.x >= 128) { pdl_wait(); moe_cta(blockIdx.x - 128, smem, x, w_gate, w_up, w_down); return; }
    const uint32_t sK = smem_u32(smem), sV = sK + 65536, sQ = sV + 98304, sBar = sQ + 16384;
    const int h = blockIdx.x >> 2, qb = blockIdx.x & 3;
    const int warp = __shfl_sync(~0u, threadIdx.x >> 5, 0), lane = threadIdx.x & 31, wg = warp >> 2;
    if (threadIdx.x == 0) {
        mbar_init(sBar, 1); mbar_init(sBar + 8, 1);
        asm volatile("fence.mbarrier_init.release.cluster;" ::: "memory");
        pdl_wait();
        const uint4* gk = g_K + (size_t)h * 4096;
        const uint4* gv = g_V + (size_t)h * 4096;
        mbar_expect_tx(sBar, 16384 + 16384 + 2 * 8192);
        bulk_g2s(sQ, g_Q + (size_t)h * 4096 + qb * 1024, 16384, sBar);
        bulk_g2s(sK, gk, 16384, sBar);
        bulk_g2s(sV, gv, 8192, sBar);
        bulk_g2s(sV + 32768, gv + 2048, 8192, sBar);
        mbar_expect_tx(sBar + 8, 49152 + 2 * 24576);
        bulk_g2s(sK + 16384, gk + 1024, 49152, sBar + 8);
        bulk_g2s(sV + 8192, gv + 512, 24576, sBar + 8);
        bulk_g2s(sV + 32768 + 8192, gv + 2048 + 512, 24576, sBar + 8);
    }
    for (int i = threadIdx.x; i < 2048; i += K2_THREADS) {
        const uint32_t v = is_poly_group(i >> 3) ? 0xBF80BF80u : 0x3F803F80u;
        *(uint4*)(smem + 65536 + 65536 + i * 16) = make_uint4(v, v, v, v);
    }
    fence_async_smem();
    __syncthreads();
    ExpC c;
    {
        const volatile uint32_t* cc = g_const;
        c.c421 = cc[0]; c.c3 = __uint_as_float(cc[1]); c.one = __uint_as_float(cc[2]);
    }
    const uint64_t kdesc0 = make_desc(sK, 128, 256, 0);
    const uint64_t vdesc0 = make_desc(sV, 128, 32768, 0);
    mbar_wait(sBar, 0);
    #pragma unroll 1
    for (int pass = 0; pass < 2; pass++) {
        const int unit = pass * 4 + wg;
        const uint64_t q = make_desc(sQ + unit * 2048, 128, 256, 0);
        float o[12];
        #pragma unroll 1
        for (int attempt = 0; attempt < 2; attempt++) {
            float s0[16], s1[16], s2[16];
            #pragma unroll
            for (int i = 0; i < 16; i++) { s0[i] = 0.f; s1[i] = 0.f; s2[i] = 0.f; }
            float mx0 = -INFINITY, mx1 = -INFINITY;
            if (attempt) {
                #pragma unroll 1
                for (int it = 0; it < 64; it++) {
                    WG_FENCE();
                    wgmma_qk32(s0, q, kdesc0 + (uint64_t)(it * 64));
                    WG_COMMIT();
                    wg_wait<0>();
                    touch16(s0);
                    max16(s0, mx0, mx1);
                }
            }
            #pragma unroll
            for (int i = 0; i < 12; i++) o[i] = 0.f;
            WG_FENCE();
            wgmma_qk32(s2, q, kdesc0);
            wgmma_qk32(s0, q, kdesc0 + 64);
            wgmma_qk32(s1, q, kdesc0 + 128);
            WG_COMMIT();
            wg_wait<0>();
            touch16(s0); touch16(s1); touch16(s2);
            max16(s0, mx0, mx1); max16(s1, mx0, mx1); max16(s2, mx0, mx1);
            mx0 = fmaxf(mx0, __shfl_xor_sync(~0u, mx0, 1)); mx0 = fmaxf(mx0, __shfl_xor_sync(~0u, mx0, 2));
            mx1 = fmaxf(mx1, __shfl_xor_sync(~0u, mx1, 1)); mx1 = fmaxf(mx1, __shfl_xor_sync(~0u, mx1, 2));
            const float bias = attempt ? 0.0f : 64.0f;
            c.nm0 = __shfl_sync(~0u, -(mx0 + bias), lane); c.nm1 = __shfl_sync(~0u, -(mx1 + bias), lane);
            c.cb0 = __shfl_sync(~0u, (127.0f + c.nm0) * (1.0f / 255.0f), lane);
            c.cb1 = __shfl_sync(~0u, (127.0f + c.nm1) * (1.0f / 255.0f), lane);
            uint64_t kd = kdesc0 + 192, vd = vdesc0 + 32;
            {
                uint32_t pa[4], pb[4];
                exp_block<12>(s2, pa, c);
                exp_block<14>(s2 + 8, pb, c);
                WG_FENCE();
                wgmma_pv(o, pa, vdesc0); wgmma_pv(o, pb, vdesc0 + 16);
                WG_COMMIT();
            }
            #pragma unroll 1
            for (int it = 0; it < 21; it++) {
                if (it == 3) mbar_wait(sBar + 8, 0);
                uint32_t p[6][4];
                WG_FENCE();
                wgmma_qk32(s2, q, kd);
                WG_COMMIT();
                exp_block<0>(s0, p[0], c);
                exp_block<2>(s0 + 8, p[1], c);
                WG_FENCE();
                wgmma_pv(o, p[0], vd); wgmma_pv(o, p[1], vd + 16);
                wgmma_qk32(s0, q, kd + 64);
                WG_COMMIT();
                wg_wait<1>();
                touch16(s2);
                exp_block<4>(s1, p[2], c);
                exp_block<6>(s1 + 8, p[3], c);
                WG_FENCE();
                wgmma_pv(o, p[2], vd + 32); wgmma_pv(o, p[3], vd + 48);
                wgmma_qk32(s1, q, kd + 128);
                WG_COMMIT();
                wg_wait<1>();
                touch16(s0);
                exp_block<8>(s2, p[4], c);
                exp_block<10>(s2 + 8, p[5], c);
                WG_FENCE();
                wgmma_pv(o, p[4], vd + 64); wgmma_pv(o, p[5], vd + 80);
                WG_COMMIT();
                vd += 96; kd += 192;
                wg_wait<1>();
                touch16(s1);
            }
            wg_wait<0>();
            touch12(o);
            if (attempt) break;
            float big = 0.f;
            #pragma unroll
            for (int i = 0; i < 12; i++) big = fmaxf(big, fabsf(o[i]));
            bool bad = !(big < 1e30f);
            #pragma unroll
            for (int i = 0; i < 12; i++) bad |= (o[i] != o[i]);
            uint32_t any;
            asm volatile("{.reg .pred p, q; setp.ne.u32 p, %1, 0; barrier.cta.red.or.pred.aligned q, %2, 128, p; selp.u32 %0, 1, 0, q;}"
                         : "=r"(any) : "r"((uint32_t)bad), "r"(1 + wg) : "memory");
            if (!any) break;
        }
        const int g = lane >> 2, t = lane & 3;
        const int r = (warp & 3) * 16 + g;
        const float i0 = __fdiv_rn(1.0f, o[8]), i1 = __fdiv_rn(1.0f, o[10]);
        uint32_t* ob = (uint32_t*)(g_O + (size_t)(qb * 8 + unit) * 4096 + (h >> 2) * 512 + r * 8) + t;
        const int c0 = ((h & 3) * 2) ^ (r & 7), c1 = ((h & 3) * 2 + 1) ^ (r & 7);
        ob[c0 * 4] = pack_bf16(o[0] * i0, o[1] * i0);
        ob[c1 * 4] = pack_bf16(o[4] * i0, o[5] * i0);
        ob[256 + c0 * 4] = pack_bf16(o[2] * i1, o[3] * i1);
        ob[256 + c1 * 4] = pack_bf16(o[6] * i1, o[7] * i1);
    }
}

constexpr int K3_THREADS = 256;
constexpr int K3_SMEM = 65536 + 131072 + 128;

__global__ void __launch_bounds__(K3_THREADS, 1)
k3_out(const __grid_constant__ CUtensorMap wmap, const __nv_bfloat16* __restrict__ x, __nv_bfloat16* __restrict__ out) {
    extern __shared__ __align__(1024) unsigned char smem[];
    const uint32_t sA = smem_u32(smem), sB = sA + 65536, sBar = sB + 131072;
    const int warp = __shfl_sync(~0u, threadIdx.x >> 5, 0), lane = threadIdx.x & 31, wg = warp >> 2;
    const int nt = blockIdx.x & 3, mt = blockIdx.x >> 2;
    if (threadIdx.x == 0) {
        for (int i = 0; i < 6; i++) mbar_init(sBar + i * 8, 1);
        asm volatile("fence.mbarrier_init.release.cluster;" ::: "memory");
        for (int kh = 0; kh < 2; kh++) {
            mbar_expect_tx(sBar + kh * 8, 65536);
            tma_2d(sB + kh * 32768, &wmap, nt * 128, kh * 256, sBar + kh * 8);
            tma_2d(sB + 65536 + kh * 32768, &wmap, nt * 128 + 64, kh * 256, sBar + kh * 8);
        }
    }
    const int g = lane >> 2, t = lane & 3;
    const int row0 = mt * 64 + (warp & 3) * 16 + g;
    const int col0 = nt * 128 + wg * 64 + t * 2;
    uint32_t xu[2][8];
    #pragma unroll
    for (int hf = 0; hf < 2; hf++)
        #pragma unroll
        for (int j = 0; j < 8; j++) xu[hf][j] = __ldg((const uint32_t*)(x + (size_t)(row0 + hf * 8) * D_ + col0 + j * 8));
    pdl_wait();
    if (threadIdx.x == 0) {
        for (int q = 0; q < 4; q++) {
            mbar_expect_tx(sBar + 16 + q * 8, 16384);
            bulk_g2s(sA + q * 16384, g_O + (size_t)mt * 4096 + q * 1024, 16384, sBar + 16 + q * 8);
        }
    }
    const int sel0 = g_sel[0], sel1 = g_sel[1];
    const float2 st0 = g_stats[row0], st1 = g_stats[row0 + 8];
    __syncthreads();
    float acc[32];
    #pragma unroll
    for (int i = 0; i < 32; i++) acc[i] = 0.f;
    const uint64_t da0 = make_desc(sA, 16, 1024, 1);
    const uint64_t db0 = make_desc(sB + wg * 65536, 8192, 1024, 1);
    #pragma unroll 1
    for (int q = 0; q < 4; q++) {
        if ((q & 1) == 0) mbar_wait(sBar + (q >> 1) * 8, 0);
        mbar_wait(sBar + 16 + q * 8, 0);
        WG_FENCE();
        #pragma unroll
        for (int kk = 0; kk < 8; kk++)
            wgmma_n64(acc, da0 + (uint64_t)(q * 1024 + (kk >> 2) * 512 + (kk & 3) * 2), db0 + (uint64_t)(q * 1024 + kk * 128));
        WG_COMMIT();
    }
    wg_wait<0>();
    touch32(acc);
    #pragma unroll
    for (int hf = 0; hf < 2; hf++) {
        const int row = row0 + hf * 8;
        const float2 st = hf ? st1 : st0;
        const int slot = row == sel0 ? 0 : (row == sel1 ? 1 : -1);
        float gate = 0.f;
        if (slot >= 0) gate = bf16r(1.0f / (1.0f + __expf(-g_r[row])));
        #pragma unroll
        for (int j = 0; j < 8; j++) {
            const int col = col0 + j * 8;
            const float x0 = bf_lo(xu[hf][j]), x1 = bf_hi(xu[hf][j]);
            float b0 = ln_elem(x0, st.x, st.y), b1 = ln_elem(x1, st.x, st.y);
            if (slot >= 0) {
                float y0 = g_ypart[0][slot][col] + g_ypart[1][slot][col] + g_ypart[2][slot][col] + g_ypart[3][slot][col];
                float y1 = g_ypart[0][slot][col + 1] + g_ypart[1][slot][col + 1] + g_ypart[2][slot][col + 1] + g_ypart[3][slot][col + 1];
                b0 = bf16r(b0 + bf16r(bf16r(y0) * gate));
                b1 = bf16r(b1 + bf16r(bf16r(y1) * gate));
            }
            const float t0 = bf16r(x0 + bf16r(acc[4 * j + hf * 2])), t1 = bf16r(x1 + bf16r(acc[4 * j + hf * 2 + 1]));
            *(uint32_t*)(out + (size_t)row * D_ + col) = pack_bf16(t0 + b0, t1 + b1);
        }
    }
}

typedef CUresult (*EncodeFn)(CUtensorMap*, CUtensorMapDataType, cuuint32_t, void*, const cuuint64_t*, const cuuint64_t*,
                             const cuuint32_t*, const cuuint32_t*, CUtensorMapInterleave, CUtensorMapSwizzle,
                             CUtensorMapL2promotion, CUtensorMapFloatOOBfill);

void make_wmap(EncodeFn fn, CUtensorMap* map, const void* ptr, int rows, int cols, int box_rows) {
    cuuint64_t dims[2] = {(cuuint64_t)cols, (cuuint64_t)rows};
    cuuint64_t strides[1] = {(cuuint64_t)cols * 2};
    cuuint32_t box[2] = {64, (cuuint32_t)box_rows};
    cuuint32_t es[2] = {1, 1};
    fn(map, CU_TENSOR_MAP_DATA_TYPE_BFLOAT16, 2, (void*)ptr, dims, strides, box, es, CU_TENSOR_MAP_INTERLEAVE_NONE,
       CU_TENSOR_MAP_SWIZZLE_128B, CU_TENSOR_MAP_L2_PROMOTION_L2_256B, CU_TENSOR_MAP_FLOAT_OOB_FILL_NONE);
}

}

extern "C" void kernel_launch(void* const* d_in, const int* in_sizes, int n_in, void* d_out, int out_size) {
    const __nv_bfloat16* x = (const __nv_bfloat16*)d_in[0];
    const __nv_bfloat16* wqkv = (const __nv_bfloat16*)d_in[1];
    const __nv_bfloat16* wo = (const __nv_bfloat16*)d_in[2];
    const __nv_bfloat16* w_r = (const __nv_bfloat16*)d_in[4];
    const __nv_bfloat16* w_gate = (const __nv_bfloat16*)d_in[5];
    const __nv_bfloat16* w_up = (const __nv_bfloat16*)d_in[6];
    const __nv_bfloat16* w_down = (const __nv_bfloat16*)d_in[7];
    __nv_bfloat16* out = (__nv_bfloat16*)d_out;

    static EncodeFn encode = nullptr;
    if (!encode) {
        void* fn = nullptr;
        cudaDriverEntryPointQueryResult qres;
        cudaGetDriverEntryPoint("cuTensorMapEncodeTiled", &fn, cudaEnableDefault, &qres);
        encode = (EncodeFn)fn;
        cudaFuncSetAttribute(k1_ln_qkv, cudaFuncAttributeMaxDynamicSharedMemorySize, K1_SMEM);
        cudaFuncSetAttribute(k2_attn, cudaFuncAttributeMaxDynamicSharedMemorySize, K2_SMEM);
        cudaFuncSetAttribute(k3_out, cudaFuncAttributeMaxDynamicSharedMemorySize, K3_SMEM);
    }
    CUtensorMap map_qkv, map_wo;
    make_wmap(encode, &map_qkv, wqkv, D_, 3 * D_, 64);
    make_wmap(encode, &map_wo, wo, D_, D_, 256);

    k1_ln_qkv<<<128, K1_THREADS, K1_SMEM, cudaStreamPerThread>>>(map_qkv, x, w_r);
    cudaLaunchAttribute at[1];
    at[0].id = cudaLaunchAttributeProgrammaticStreamSerialization;
    at[0].val.programmaticStreamSerializationAllowed = 1;
    cudaLaunchConfig_t cfg = {};
    cfg.stream = cudaStreamPerThread;
    cfg.attrs = at; cfg.numAttrs = 1;
    cfg.gridDim = dim3(132); cfg.blockDim = dim3(K2_THREADS); cfg.dynamicSmemBytes = K2_SMEM;
    cudaLaunchKernelEx(&cfg, k2_attn, x, w_gate, w_up, w_down);
    cfg.gridDim = dim3(128); cfg.blockDim = dim3(K3_THREADS); cfg.dynamicSmemBytes = K3_SMEM;
    cudaLaunchKernelEx(&cfg, k3_out, map_wo, x, out);
}
```

```cpp
#include <cuda_runtime.h>
#include <cuda_bf16.h>
#include <cuda.h>
#include <stdint.h>

namespace {

constexpr int S_ = 2048, D_ = 512, H_ = 32, F_ = 1792;

constexpr uint32_t PMASK = 0xA52;
__host__ __device__ constexpr bool is_poly_group(int g8) { return g8 >= 4 && ((PMASK >> ((g8 - 4) % 12)) & 1); }

__device__ __align__(1024) uint4 g_QKV[3 * H_ * S_ * 2];
#define g_Q (g_QKV)
#define g_K (g_QKV + H_ * S_ * 2)
#define g_V (g_QKV + 2 * H_ * S_ * 2)
__device__ __align__(1024) uint4 g_O[S_ * D_ / 8];
__device__ float2 g_stats[S_];
__device__ uint32_t g_const[4] = {421u, 0x459EB285u  , 0x3F800000u  , 0u};
__device__ float g_r[S_];
__device__ __align__(16) float g_ypart[4][2][D_];
__device__ int g_sel[2];

#define TL(k, p)
__device__ __forceinline__ uint32_t smem_u32(const void* p) { return (uint32_t)__cvta_generic_to_shared(p); }
__device__ __forceinline__ float bf16r(float x) { return __bfloat162float(__float2bfloat16_rn(x)); }
__device__ __forceinline__ uint32_t pack_bf16(float lo, float hi) {
    uint32_t r; asm("cvt.rn.bf16x2.f32 %0, %1, %2;" : "=r"(r) : "f"(hi), "f"(lo)); return r;
}
__device__ __forceinline__ float bf_lo(uint32_t u) { return __uint_as_float(u << 16); }
__device__ __forceinline__ float bf_hi(uint32_t u) { return __uint_as_float(u & 0xFFFF0000u); }
__device__ __forceinline__ float ex2(float x) { float y; asm("ex2.approx.ftz.f32 %0, %1;" : "=f"(y) : "f"(x)); return y; }

__device__ __forceinline__ void mbar_init(uint32_t bar, uint32_t count) {
    asm volatile("mbarrier.init.shared::cta.b64 [%0], %1;" :: "r"(bar), "r"(count) : "memory");
}
__device__ __forceinline__ void mbar_expect_tx(uint32_t bar, uint32_t bytes) {
    asm volatile("mbarrier.arrive.expect_tx.shared::cta.b64 _, [%0], %1;" :: "r"(bar), "r"(bytes) : "memory");
}
__device__ __forceinline__ void mbar_arrive(uint32_t bar) {
    asm volatile("mbarrier.arrive.shared::cta.b64 _, [%0];" :: "r"(bar) : "memory");
}
__device__ __forceinline__ void mbar_wait(uint32_t bar, uint32_t parity) {
    uint32_t done;
    #pragma unroll 1
    for (int it = 0; it < (1 << 26); it++) {
        asm volatile("{.reg .pred p; mbarrier.try_wait.parity.shared::cta.b64 p, [%1], %2; selp.u32 %0, 1, 0, p;}"
                     : "=r"(done) : "r"(bar), "r"(parity) : "memory");
        if (done) return;
    }
    __trap();
}
__device__ __forceinline__ void bulk_g2s(uint32_t dst, const void* src, uint32_t bytes, uint32_t bar) {
    asm volatile("cp.async.bulk.shared::cluster.global.mbarrier::complete_tx::bytes [%0], [%1], %2, [%3];"
                 :: "r"(dst), "l"(src), "r"(bytes), "r"(bar) : "memory");
}
__device__ __forceinline__ void tma_2d(uint32_t dst, const CUtensorMap* map, int c0, int c1, uint32_t bar) {
    asm volatile("cp.async.bulk.tensor.2d.shared::cluster.global.mbarrier::complete_tx::bytes [%0], [%1, {%3, %4}], [%2];"
                 :: "r"(dst), "l"(map), "r"(bar), "r"(c0), "r"(c1) : "memory");
}
__device__ __forceinline__ void fence_async_smem() { asm volatile("fence.proxy.async.shared::cta;" ::: "memory"); }
__device__ __forceinline__ void named_bar(int id, int n) { asm volatile("bar.sync %0, %1;" :: "r"(id), "r"(n) : "memory"); }

__device__ __forceinline__ uint64_t make_desc(uint32_t saddr, uint32_t lbo, uint32_t sbo, uint32_t swz) {
    return (uint64_t)((saddr & 0x3FFFF) >> 4) | ((uint64_t)(lbo >> 4) << 16) | ((uint64_t)(sbo >> 4) << 32) | ((uint64_t)swz << 62);
}
#define WG_FENCE() asm volatile("wgmma.fence.sync.aligned;" ::: "memory")
#define WG_COMMIT() asm volatile("wgmma.commit_group.sync.aligned;" ::: "memory")
template <int N> __device__ __forceinline__ void wg_wait() { asm volatile("wgmma.wait_group.sync.aligned %0;" :: "n"(N) : "memory"); }

#define F4(d, o) "+f"(d[o]), "+f"(d[o + 1]), "+f"(d[o + 2]), "+f"(d[o + 3])
#define F16(d, o) F4(d, o), F4(d, o + 4), F4(d, o + 8), F4(d, o + 12)
#define F32(d, o) F16(d, o), F16(d, o + 16)

__device__ __forceinline__ void wgmma_n192(float* d, uint64_t da, uint64_t db) {
    asm volatile("wgmma.mma_async.sync.aligned.m64n192k16.f32.bf16.bf16 "
        "{%0,%1,%2,%3,%4,%5,%6,%7,%8,%9,%10,%11,%12,%13,%14,%15,%16,%17,%18,%19,%20,%21,%22,%23,%24,%25,%26,%27,%28,%29,%30,%31,"
        "%32,%33,%34,%35,%36,%37,%38,%39,%40,%41,%42,%43,%44,%45,%46,%47,%48,%49,%50,%51,%52,%53,%54,%55,%56,%57,%58,%59,%60,%61,%62,%63,"
        "%64,%65,%66,%67,%68,%69,%70,%71,%72,%73,%74,%75,%76,%77,%78,%79,%80,%81,%82,%83,%84,%85,%86,%87,%88,%89,%90,%91,%92,%93,%94,%95}, "
        "%96, %97, 1, 1, 1, 0, 1;\n"
        : F32(d, 0), F32(d, 32), F32(d, 64) : "l"(da), "l"(db));
}
__device__ __forceinline__ void wgmma_n64(float* d, uint64_t da, uint64_t db) {
    asm volatile("wgmma.mma_async.sync.aligned.m64n64k16.f32.bf16.bf16 "
        "{%0,%1,%2,%3,%4,%5,%6,%7,%8,%9,%10,%11,%12,%13,%14,%15,%16,%17,%18,%19,%20,%21,%22,%23,%24,%25,%26,%27,%28,%29,%30,%31}, "
        "%32, %33, 1, 1, 1, 0, 1;\n"
        : F32(d, 0) : "l"(da), "l"(db));
}
__device__ __forceinline__ void wgmma_qk32(float* d, uint32_t qd, uint32_t kd) {
    asm volatile("{.reg .b64 a, b; mov.b64 a, {%16, 16}; mov.b64 b, {%17, 16};\n"
        "wgmma.mma_async.sync.aligned.m64n32k16.f32.bf16.bf16 {%0,%1,%2,%3,%4,%5,%6,%7,%8,%9,%10,%11,%12,%13,%14,%15}, a, b, 0, 1, 1, 0, 0;}\n"
        : F16(d, 0) : "r"(qd), "r"(kd));
}
__device__ __forceinline__ void wgmma_pv(float* d, const uint32_t* a, uint32_t vd) {
    asm volatile("{.reg .b64 b; mov.b64 b, {%16, 2048};\n"
        "wgmma.mma_async.sync.aligned.m64n24k16.f32.bf16.bf16 {%0,%1,%2,%3,%4,%5,%6,%7,%8,%9,%10,%11}, {%12,%13,%14,%15}, b, 1, 1, 1, 1;}\n"
        : F4(d, 0), F4(d, 4), F4(d, 8) : "r"(a[0]), "r"(a[1]), "r"(a[2]), "r"(a[3]), "r"(vd));
}
__device__ __forceinline__ void touch16(float* d) { asm volatile("" : F16(d, 0) :: "memory"); }
__device__ __forceinline__ void touch12(float* d) { asm volatile("" : F4(d, 0), F4(d, 4), F4(d, 8) :: "memory"); }
__device__ __forceinline__ void touch32(float* d) { asm volatile("" : F32(d, 0) :: "memory"); }
__device__ __forceinline__ void touch96(float* d) { asm volatile("" : F32(d, 0), F32(d, 32), F32(d, 64) :: "memory"); }

__device__ __forceinline__ float ln_elem(float x, float mean_b, float rden) {
    return bf16r(bf16r(x - mean_b) * rden);
}
__device__ __forceinline__ void pdl_wait() { asm volatile("griddepcontrol.wait;" ::: "memory"); }
__device__ __forceinline__ void pdl_launch() { asm volatile("griddepcontrol.launch_dependents;" ::: "memory"); }
__device__ __forceinline__ void cluster_arrive() { asm volatile("barrier.cluster.arrive.release.aligned;" ::: "memory"); }
__device__ __forceinline__ void cluster_wait() { asm volatile("barrier.cluster.wait.acquire.aligned;" ::: "memory"); }

constexpr int K1_THREADS = 288;
constexpr int K1_SMEM = 131072 + 4 * 24576 + 256;

__global__ void __cluster_dims__(2, 1, 1) __launch_bounds__(K1_THREADS, 1)
k1_ln_qkv(const __grid_constant__ CUtensorMap wmap, const __nv_bfloat16* __restrict__ x, const __nv_bfloat16* __restrict__ w_r) {
    extern __shared__ __align__(1024) unsigned char smem[];
    const uint32_t sA = smem_u32(smem), sB = sA + 131072, sBar = sB + 4 * 24576;
    const int warp = __shfl_sync(~0u, threadIdx.x >> 5, 0), lane = threadIdx.x & 31;
    const int nt = blockIdx.x & 7, mt = blockIdx.x >> 3, rank = blockIdx.x & 1;
    TL(0, 0);
    if (threadIdx.x == 0) {
        for (int i = 0; i < 4; i++) { mbar_init(sBar + i * 8, 1); mbar_init(sBar + 32 + i * 8, 2); }
        mbar_init(sBar + 64, 1);
        asm volatile("fence.mbarrier_init.release.cluster;" ::: "memory");
        mbar_expect_tx(sBar + 64, 65536);
    }
    const int rbase = rank * 64 + warp * 8;
    const uint32_t raw_off = warp * 16384 + (rank ^ 1) * 8192;
    if (warp < 8 && lane == 0) {
        const uint32_t b = sBar + 72 + warp * 8;
        mbar_init(b, 1);
        asm volatile("fence.mbarrier_init.release.cluster;" ::: "memory");
        mbar_expect_tx(b, 8192);
        bulk_g2s(sA + raw_off, x + (size_t)(mt * 128 + rbase) * D_, 8192, b);
    }
    __syncthreads();
    pdl_launch();
    if (warp == 8) {
        cluster_arrive();
        if (lane == 0) {
            for (int kc = 0; kc < 8; kc++) {
                const int st = kc & 3;
                if (kc >= 4) mbar_wait(sBar + 32 + st * 8, 0);
                mbar_expect_tx(sBar + st * 8, 24576);
                for (int j = 0; j < 3; j++) tma_2d(sB + st * 24576 + j * 8192, &wmap, nt * 192 + j * 64, kc * 64, sBar + st * 8);
            }
        }
        __syncwarp();
        cluster_wait();
        cluster_arrive();
        cluster_wait();
        return;
    }
    TL(0, 1);
    uint4 wr0 = make_uint4(0, 0, 0, 0), wr1 = wr0;
    if (nt < 2) { wr0 = __ldg((const uint4*)(w_r + lane * 8)); wr1 = __ldg((const uint4*)(w_r + 256 + lane * 8)); }
    mbar_wait(sBar + 72 + warp * 8, 0);
    TL(0, 8);
    #pragma unroll 2
    for (int i = 0; i < 8; i++) {
        const int r = rbase + i;
        const uint4 ra = *(const uint4*)(smem + raw_off + i * 1024 + lane * 16);
        const uint4 rb = *(const uint4*)(smem + raw_off + i * 1024 + 512 + lane * 16);
        uint32_t u[8] = {ra.x, ra.y, ra.z, ra.w, rb.x, rb.y, rb.z, rb.w};
        float v[16];
        #pragma unroll
        for (int j = 0; j < 8; j++) { v[2 * j] = bf_lo(u[j]); v[2 * j + 1] = bf_hi(u[j]); }
        float s = 0.f;
        #pragma unroll
        for (int j = 0; j < 16; j++) s += v[j];
        #pragma unroll
        for (int o = 16; o; o >>= 1) s += __shfl_xor_sync(~0u, s, o);
        const float mean = s * (1.0f / D_);
        float q = 0.f;
        #pragma unroll
        for (int j = 0; j < 16; j++) { float d = v[j] - mean; q = fmaf(d, d, q); }
        #pragma unroll
        for (int o = 16; o; o >>= 1) q += __shfl_xor_sync(~0u, q, o);
        const float mean_b = bf16r(mean);
        const float var_b = bf16r(q * (1.0f / D_));
        const float rden = __frcp_rn(bf16r(__fsqrt_rn(bf16r(var_b + 1e-5f))));
        #pragma unroll
        for (int j = 0; j < 8; j++) {
            const uint32_t d2 = pack_bf16(v[2 * j] - mean_b, v[2 * j + 1] - mean_b);
            u[j] = pack_bf16(bf_lo(d2) * rden, bf_hi(d2) * rden);
        }
        const int ch = (lane & 7) ^ (r & 7);
        *(uint4*)(smem + (lane >> 3) * 16384 + r * 128 + ch * 16) = make_uint4(u[0], u[1], u[2], u[3]);
        *(uint4*)(smem + (4 + (lane >> 3)) * 16384 + r * 128 + ch * 16) = make_uint4(u[4], u[5], u[6], u[7]);
        if (nt < 2) {
            const uint32_t w[8] = {wr0.x, wr0.y, wr0.z, wr0.w, wr1.x, wr1.y, wr1.z, wr1.w};
            float acc = 0.f;
            #pragma unroll
            for (int j = 0; j < 8; j++) { acc = fmaf(bf_lo(u[j]), bf_lo(w[j]), acc); acc = fmaf(bf_hi(u[j]), bf_hi(w[j]), acc); }
            #pragma unroll
            for (int o = 16; o; o >>= 1) acc += __shfl_xor_sync(~0u, acc, o);
            if (lane == 0) { g_r[mt * 128 + r] = bf16r(acc); g_stats[mt * 128 + r] = make_float2(mean_b, rden); }
        }
    }
    TL(0, 2);
    fence_async_smem();
    cluster_arrive();
    cluster_wait();
    TL(0, 3);
    const int wg = warp >> 2;
    if (lane == 0) {
        uint32_t dst, rbar;
        const uint32_t src = sA + warp * 16384 + rank * 8192;
        asm volatile("mapa.shared::cluster.u32 %0, %1, %2;" : "=r"(dst) : "r"(src), "r"(rank ^ 1));
        asm volatile("mapa.shared::cluster.u32 %0, %1, %2;" : "=r"(rbar) : "r"(sBar + 64), "r"(rank ^ 1));
        asm volatile("cp.async.bulk.shared::cluster.shared::cta.mbarrier::complete_tx::bytes [%0], [%1], %2, [%3];"
                     :: "r"(dst), "r"(src), "r"(8192), "r"(rbar) : "memory");
    }
    __syncwarp();
    if (wg != rank) mbar_wait(sBar + 64, 0);
    TL(0, 4);
    float acc[96];
    #pragma unroll
    for (int i = 0; i < 96; i++) acc[i] = 0.f;
    const uint64_t da0 = make_desc(sA + wg * 8192, 16, 1024, 1);
    const uint64_t db0 = make_desc(sB, 8192, 1024, 1);
    #pragma unroll 1
    for (int kc = 0; kc < 8; kc++) {
        const int st = kc & 3;
        mbar_wait(sBar + st * 8, kc >> 2);
        WG_FENCE();
        #pragma unroll
        for (int kk = 0; kk < 4; kk++)
            wgmma_n192(acc, da0 + (uint64_t)(kc * 1024 + kk * 2), db0 + (uint64_t)(st * 1536 + kk * 128));
        WG_COMMIT();
        wg_wait<1>();
        if (kc >= 1 && kc <= 4 && (threadIdx.x & 127) == 0) mbar_arrive(sBar + 32 + (kc - 1) * 8);
    }
    wg_wait<0>();
    touch96(acc);
    TL(0, 5);
    if (wg == rank) mbar_wait(sBar + 64, 0);
    cluster_arrive();
    const int g = lane >> 2, t = lane & 3;
    const int row0 = mt * 128 + warp * 16;
    const int g8a = row0 >> 3;
    const float sgn0 = is_poly_group(g8a) ? -1.f : 1.f, sgn1 = is_poly_group(g8a + 1) ? -1.f : 1.f;
    constexpr float QS = 0.25f * 1.4426950408889634f;
    const int off_qk = g8a * 64 + g * 4 + t, off_v = (row0 + g) * 4 + t;
    #pragma unroll
    for (int jj = 0; jj < 12; jj++) {
        const int hg = nt * 12 + jj;
        const bool isv = hg >= 64;
        const float m0 = isv ? sgn0 : (hg < 32 ? QS : 1.0f), m1 = isv ? sgn1 : (hg < 32 ? QS : 1.0f);
        uint32_t* base = (uint32_t*)g_QKV + (size_t)hg * 16384 + (isv ? off_v : off_qk);
        const int hs = isv ? 8192 : 32, rs = isv ? 32 : 64;
        base[0] = pack_bf16(acc[8 * jj] * m0, acc[8 * jj + 1] * m0);
        base[rs] = pack_bf16(acc[8 * jj + 2] * m1, acc[8 * jj + 3] * m1);
        base[hs] = pack_bf16(acc[8 * jj + 4] * m0, acc[8 * jj + 5] * m0);
        base[hs + rs] = pack_bf16(acc[8 * jj + 6] * m1, acc[8 * jj + 7] * m1);
    }
    TL(0, 6);
    cluster_wait();
    TL(0, 7);
}

constexpr int K2_THREADS = 512;
constexpr int K2_SMEM = 65536 + 98304 + 16384 + 128;

__device__ __forceinline__ uint32_t polyexp(float s, float cb, uint32_t c421, float c3, float one) {
    float u;
    asm("fma.rn.sat.f32 %0, %1, 0f3B808081, %2;" : "=f"(u) : "f"(s), "f"(cb));
    float z = fmaf(u, 0.99609375f, one);
    uint32_t rb;
    asm("lop3.b32 %0, %1, 0xFFFF8000, %2, 0xEA;" : "=r"(rb) : "r"(__float_as_uint(z)), "r"(c421));
    float f = z - __uint_as_float(rb);
    float h = fmaf(f, c3, 58.86525f);
    h = fmaf(f, h, -0.29870507f);
    return __float_as_uint(fmaf(f, h, z));
}

struct ExpC { float nm0, nm1, cb0, cb1, c3, one; uint32_t c421; };

template <int G>
__device__ __forceinline__ void exp_block(const float* s, uint32_t* p, const ExpC& c) {
    #pragma unroll
    for (int hf = 0; hf < 2; hf++) {
        const float* x = s + hf * 4;
        if ((PMASK >> (G + hf)) & 1) {
            p[hf * 2 + 0] = __byte_perm(polyexp(x[0], c.cb0, c.c421, c.c3, c.one), polyexp(x[1], c.cb0, c.c421, c.c3, c.one), 0x6521);
            p[hf * 2 + 1] = __byte_perm(polyexp(x[2], c.cb1, c.c421, c.c3, c.one), polyexp(x[3], c.cb1, c.c421, c.c3, c.one), 0x6521);
        } else {
            p[hf * 2 + 0] = pack_bf16(ex2(x[0] + c.nm0), ex2(x[1] + c.nm0));
            p[hf * 2 + 1] = pack_bf16(ex2(x[2] + c.nm1), ex2(x[3] + c.nm1));
        }
    }
}

__device__ __forceinline__ void max16(const float* s, float& mx0, float& mx1) {
    #pragma unroll
    for (int j = 0; j < 4; j++) {
        mx0 = fmaxf(mx0, fmaxf(s[4 * j], s[4 * j + 1]));
        mx1 = fmaxf(mx1, fmaxf(s[4 * j + 2], s[4 * j + 3]));
    }
}

__device__ void moe_cta(int part, unsigned char* smem, const __nv_bfloat16* __restrict__ x, const __nv_bfloat16* __restrict__ w_gate,
                        const __nv_bfloat16* __restrict__ w_up, const __nv_bfloat16* __restrict__ w_down) {
    float* xs = (float*)smem;
    float* red = xs + 1024;
    float* hs = red + 8 * 4 * 448;
    __shared__ float s_v[32];
    __shared__ int s_i[32];
    __shared__ int s_sel[2];
    const int tid = threadIdx.x, warp = tid >> 5, lane = tid & 31;
    for (int pass = 0; pass < 2; pass++) {
        float bv = -INFINITY; int bi = 0x7fffffff;
        const int excl = pass ? s_sel[0] : -1;
        for (int i = tid; i < S_; i += K2_THREADS) {
            float v = g_r[i];
            if (i != excl && (v > bv || (v == bv && i < bi) || bi == 0x7fffffff)) { bv = v; bi = i; }
        }
        #pragma unroll
        for (int o = 16; o; o >>= 1) {
            float ov = __shfl_xor_sync(~0u, bv, o); int oi = __shfl_xor_sync(~0u, bi, o);
            if (ov > bv || (ov == bv && oi < bi)) { bv = ov; bi = oi; }
        }
        if (lane == 0) { s_v[warp] = bv; s_i[warp] = bi; }
        __syncthreads();
        if (warp == 0) {
            bv = lane < 16 ? s_v[lane] : -INFINITY; bi = lane < 16 ? s_i[lane] : 0x7fffffff;
            #pragma unroll
            for (int o = 16; o; o >>= 1) {
                float ov = __shfl_xor_sync(~0u, bv, o); int oi = __shfl_xor_sync(~0u, bi, o);
                if (ov > bv || (ov == bv && oi < bi)) { bv = ov; bi = oi; }
            }
            if (lane == 0) s_sel[pass] = (bi == 0x7fffffff) ? pass : bi;
        }
        __syncthreads();
    }
    for (int i = tid; i < 1024; i += K2_THREADS) {
        const int tok = s_sel[i >> 9];
        const float2 st = g_stats[tok];
        xs[i] = ln_elem(__bfloat162float(x[(size_t)tok * D_ + (i & 511)]), st.x, st.y);
    }
    if (part == 0 && tid < 2) g_sel[tid] = s_sel[tid];
    __syncthreads();
    const int c0 = part * 448;
    if (tid < 448) {
        const int cg = tid % 56, ks = tid / 56;
        float a[4][8];
        #pragma unroll
        for (int i = 0; i < 4; i++)
            #pragma unroll
            for (int j = 0; j < 8; j++) a[i][j] = 0.f;
        const __nv_bfloat16* pg = w_gate + (size_t)(ks * 64) * F_ + c0 + cg * 8;
        const __nv_bfloat16* pu = w_up + (size_t)(ks * 64) * F_ + c0 + cg * 8;
        #pragma unroll 8
        for (int k = 0; k < 64; k++) {
            const uint4 gv = __ldg((const uint4*)(pg + (size_t)k * F_));
            const uint4 uv = __ldg((const uint4*)(pu + (size_t)k * F_));
            const float x0 = xs[ks * 64 + k], x1 = xs[512 + ks * 64 + k];
            const uint32_t gu[4] = {gv.x, gv.y, gv.z, gv.w}, uu[4] = {uv.x, uv.y, uv.z, uv.w};
            #pragma unroll
            for (int j = 0; j < 4; j++) {
                const float g0 = bf_lo(gu[j]), g1 = bf_hi(gu[j]), u0 = bf_lo(uu[j]), u1 = bf_hi(uu[j]);
                a[0][2 * j] = fmaf(x0, g0, a[0][2 * j]); a[0][2 * j + 1] = fmaf(x0, g1, a[0][2 * j + 1]);
                a[1][2 * j] = fmaf(x1, g0, a[1][2 * j]); a[1][2 * j + 1] = fmaf(x1, g1, a[1][2 * j + 1]);
                a[2][2 * j] = fmaf(x0, u0, a[2][2 * j]); a[2][2 * j + 1] = fmaf(x0, u1, a[2][2 * j + 1]);
                a[3][2 * j] = fmaf(x1, u0, a[3][2 * j]); a[3][2 * j + 1] = fmaf(x1, u1, a[3][2 * j + 1]);
            }
        }
        #pragma unroll
        for (int i = 0; i < 4; i++)
            #pragma unroll
            for (int j = 0; j < 8; j++) red[(ks * 4 + i) * 448 + cg * 8 + j] = a[i][j];
    }
    __syncthreads();
    for (int i = tid; i < 896; i += K2_THREADS) {
        const int tok = i / 448, c = i % 448;
        float gs = 0.f, us = 0.f;
        #pragma unroll
        for (int ks = 0; ks < 8; ks++) { gs += red[(ks * 4 + tok) * 448 + c]; us += red[(ks * 4 + 2 + tok) * 448 + c]; }
        gs = bf16r(gs); us = bf16r(us);
        const float sl = bf16r(gs / (1.0f + __expf(-gs)));
        hs[i] = bf16r(sl * us);
    }
    __syncthreads();
    {
        const int cg = tid & 63, fs = tid >> 6;
        float a[2][8];
        #pragma unroll
        for (int j = 0; j < 8; j++) { a[0][j] = 0.f; a[1][j] = 0.f; }
        const __nv_bfloat16* pd = w_down + (size_t)(c0 + fs * 56) * D_ + cg * 8;
        #pragma unroll 8
        for (int f = 0; f < 56; f++) {
            const uint4 dv = __ldg((const uint4*)(pd + (size_t)f * D_));
            const float h0 = hs[fs * 56 + f], h1 = hs[448 + fs * 56 + f];
            const uint32_t du[4] = {dv.x, dv.y, dv.z, dv.w};
            #pragma unroll
            for (int j = 0; j < 4; j++) {
                const float d0 = bf_lo(du[j]), d1 = bf_hi(du[j]);
                a[0][2 * j] = fmaf(h0, d0, a[0][2 * j]); a[0][2 * j + 1] = fmaf(h0, d1, a[0][2 * j + 1]);
                a[1][2 * j] = fmaf(h1, d0, a[1][2 * j]); a[1][2 * j + 1] = fmaf(h1, d1, a[1][2 * j + 1]);
            }
        }
        #pragma unroll
        for (int j = 0; j < 8; j++) { red[(fs * 2) * 512 + cg * 8 + j] = a[0][j]; red[(fs * 2 + 1) * 512 + cg * 8 + j] = a[1][j]; }
    }
    __syncthreads();
    for (int i = tid; i < 1024; i += K2_THREADS) {
        float s = 0.f;
        #pragma unroll
        for (int fs = 0; fs < 8; fs++) s += red[(fs * 2 + (i >> 9)) * 512 + (i & 511)];
        g_ypart[part][i >> 9][i & 511] = s;
    }
}

__global__ void __launch_bounds__(K2_THREADS, 1)
k2_attn(const __nv_bfloat16* __restrict__ x, const __nv_bfloat16* __restrict__ w_gate, const __nv_bfloat16* __restrict__ w_up,
        const __nv_bfloat16* __restrict__ w_down) {
    extern __shared__ __align__(1024) unsigned char smem[];
    TL(1, 0);
    pdl_launch();
    if (blockIdx.x >= 128) {
        const int part = blockIdx.x - 128;
        {
            const int k = threadIdx.x;
            asm volatile("cp.async.bulk.prefetch.L2.global [%0], %1;" :: "l"(w_gate + (size_t)k * F_ + part * 448), "r"(896) : "memory");
            asm volatile("cp.async.bulk.prefetch.L2.global [%0], %1;" :: "l"(w_up + (size_t)k * F_ + part * 448), "r"(896) : "memory");
            if (k < 56) asm volatile("cp.async.bulk.prefetch.L2.global [%0], %1;" :: "l"(w_down + (size_t)(part * 448 + k * 8) * D_), "r"(8192) : "memory");
        }
        pdl_wait(); TL(1, 1); moe_cta(blockIdx.x - 128, smem, x, w_gate, w_up, w_down); TL(1, 2); return; }
    const uint32_t sK = smem_u32(smem), sV = sK + 65536, sQ = sV + 98304, sBar = sQ + 16384;
    const int h = blockIdx.x >> 2, qb = blockIdx.x & 3;
    const int warp = __shfl_sync(~0u, threadIdx.x >> 5, 0), lane = threadIdx.x & 31, wg = warp >> 2;
    if (threadIdx.x == 0) {
        mbar_init(sBar, 1); mbar_init(sBar + 8, 1);
        asm volatile("fence.mbarrier_init.release.cluster;" ::: "memory");
        pdl_wait();
        TL(1, 1);
        const uint4* gk = g_K + (size_t)h * 4096;
        const uint4* gv = g_V + (size_t)h * 4096;
        mbar_expect_tx(sBar, 16384 + 16384 + 2 * 8192);
        bulk_g2s(sQ, g_Q + (size_t)h * 4096 + qb * 1024, 16384, sBar);
        bulk_g2s(sK, gk, 16384, sBar);
        bulk_g2s(sV, gv, 8192, sBar);
        bulk_g2s(sV + 32768, gv + 2048, 8192, sBar);
        mbar_expect_tx(sBar + 8, 49152 + 2 * 24576);
        bulk_g2s(sK + 16384, gk + 1024, 49152, sBar + 8);
        bulk_g2s(sV + 8192, gv + 512, 24576, sBar + 8);
        bulk_g2s(sV + 32768 + 8192, gv + 2048 + 512, 24576, sBar + 8);
    }
    for (int i = threadIdx.x; i < 2048; i += K2_THREADS) {
        const uint32_t v = is_poly_group(i >> 3) ? 0xBF80BF80u : 0x3F803F80u;
        *(uint4*)(smem + 65536 + 65536 + i * 16) = make_uint4(v, v, v, v);
    }
    fence_async_smem();
    __syncthreads();
    ExpC c;
    {
        const volatile uint32_t* cc = g_const;
        c.c421 = cc[0]; c.c3 = __uint_as_float(cc[1]); c.one = __uint_as_float(cc[2]);
    }
    const uint32_t kdesc0 = (uint32_t)make_desc(sK, 128, 256, 0);
    const uint32_t vdesc0 = (uint32_t)make_desc(sV, 128, 32768, 0);
    mbar_wait(sBar, 0);
    TL(1, 2);
    #pragma unroll 1
    for (int pass = 0; pass < 2; pass++) {
        const int unit = pass * 4 + wg;
        const uint32_t q = (uint32_t)make_desc(sQ + unit * 2048, 128, 256, 0);
        float o[12];
        #pragma unroll 1
        for (int attempt = 0; attempt < 2; attempt++) {
            float s0[16], s1[16], s2[16];
            #pragma unroll
            for (int i = 0; i < 16; i++) { s0[i] = 0.f; s1[i] = 0.f; s2[i] = 0.f; }
            float mx0 = -INFINITY, mx1 = -INFINITY;
            if (attempt) {
                #pragma unroll 1
                for (int it = 0; it < 64; it++) {
                    WG_FENCE();
                    wgmma_qk32(s0, q, kdesc0 + it * 64);
                    WG_COMMIT();
                    wg_wait<0>();
                    touch16(s0);
                    max16(s0, mx0, mx1);
                }
            }
            #pragma unroll
            for (int i = 0; i < 12; i++) o[i] = 0.f;
            WG_FENCE();
            wgmma_qk32(s2, q, kdesc0);
            wgmma_qk32(s0, q, kdesc0 + 64);
            wgmma_qk32(s1, q, kdesc0 + 128);
            WG_COMMIT();
            wg_wait<0>();
            touch16(s0); touch16(s1); touch16(s2);
            max16(s0, mx0, mx1); max16(s1, mx0, mx1); max16(s2, mx0, mx1);
            mx0 = fmaxf(mx0, __shfl_xor_sync(~0u, mx0, 1)); mx0 = fmaxf(mx0, __shfl_xor_sync(~0u, mx0, 2));
            mx1 = fmaxf(mx1, __shfl_xor_sync(~0u, mx1, 1)); mx1 = fmaxf(mx1, __shfl_xor_sync(~0u, mx1, 2));
            const float bias = attempt ? 0.0f : 64.0f;
            c.nm0 = __shfl_sync(~0u, -(mx0 + bias), lane); c.nm1 = __shfl_sync(~0u, -(mx1 + bias), lane);
            c.cb0 = __shfl_sync(~0u, (127.0f + c.nm0) * (1.0f / 255.0f), lane);
            c.cb1 = __shfl_sync(~0u, (127.0f + c.nm1) * (1.0f / 255.0f), lane);
            uint32_t kd = kdesc0 + 192, vd = vdesc0 + 32;
            {
                uint32_t pa[4], pb[4];
                exp_block<12>(s2, pa, c);
                exp_block<14>(s2 + 8, pb, c);
                WG_FENCE();
                wgmma_pv(o, pa, vdesc0); wgmma_pv(o, pb, vdesc0 + 16);
                WG_COMMIT();
            }
            #pragma unroll 1
            for (int seg = 0; seg < 2; seg++) {
            if (seg) { wg_wait<0>(); mbar_wait(sBar + 8, 0); __syncwarp(); }
            #pragma unroll 1
            for (int it = seg ? 3 : 0; it < (seg ? 21 : 3); it++) {
                uint32_t p[6][4];
                WG_FENCE();
                wgmma_qk32(s2, q, kd);
                WG_COMMIT();
                exp_block<0>(s0, p[0], c);
                exp_block<2>(s0 + 8, p[1], c);
                WG_FENCE();
                wgmma_pv(o, p[0], vd); wgmma_pv(o, p[1], vd + 16);
                wgmma_qk32(s0, q, kd + 64);
                WG_COMMIT();
                wg_wait<1>();
                touch16(s2);
                exp_block<4>(s1, p[2], c);
                exp_block<6>(s1 + 8, p[3], c);
                WG_FENCE();
                wgmma_pv(o, p[2], vd + 32); wgmma_pv(o, p[3], vd + 48);
                wgmma_qk32(s1, q, kd + 128);
                WG_COMMIT();
                wg_wait<1>();
                touch16(s0);
                exp_block<8>(s2, p[4], c);
                exp_block<10>(s2 + 8, p[5], c);
                WG_FENCE();
                wgmma_pv(o, p[4], vd + 64); wgmma_pv(o, p[5], vd + 80);
                WG_COMMIT();
                vd += 96; kd += 192;
                wg_wait<1>();
                touch16(s1);
            }
            }
            wg_wait<0>();
            touch12(o);
            if (attempt) break;
            float big = 0.f;
            #pragma unroll
            for (int i = 0; i < 12; i++) big = fmaxf(big, fabsf(o[i]));
            bool bad = !(big < 1e30f);
            #pragma unroll
            for (int i = 0; i < 12; i++) bad |= (o[i] != o[i]);
            uint32_t any;
            asm volatile("{.reg .pred p, q; setp.ne.u32 p, %1, 0; barrier.cta.red.or.pred.aligned q, %2, 128, p; selp.u32 %0, 1, 0, q;}"
                         : "=r"(any) : "r"((uint32_t)bad), "r"(1 + wg) : "memory");
            if (!__any_sync(~0u, any)) break;
        }
        const int g = lane >> 2, t = lane & 3;
        const int r = (warp & 3) * 16 + g;
        const float i0 = __fdiv_rn(1.0f, o[8]), i1 = __fdiv_rn(1.0f, o[10]);
        uint32_t* ob = (uint32_t*)(g_O + (size_t)(qb * 8 + unit) * 4096 + (h >> 2) * 512 + r * 8) + t;
        const int c0 = ((h & 3) * 2) ^ (r & 7), c1 = ((h & 3) * 2 + 1) ^ (r & 7);
        ob[c0 * 4] = pack_bf16(o[0] * i0, o[1] * i0);
        ob[c1 * 4] = pack_bf16(o[4] * i0, o[5] * i0);
        ob[256 + c0 * 4] = pack_bf16(o[2] * i1, o[3] * i1);
        ob[256 + c1 * 4] = pack_bf16(o[6] * i1, o[7] * i1);
        TL(1, 3 + pass);
    }
}

constexpr int K3_THREADS = 256;
constexpr int K3_SMEM = 65536 + 131072 + 128;

__global__ void __launch_bounds__(K3_THREADS, 1)
k3_out(const __grid_constant__ CUtensorMap wmap, const __nv_bfloat16* __restrict__ x, __nv_bfloat16* __restrict__ out) {
    extern __shared__ __align__(1024) unsigned char smem[];
    const uint32_t sA = smem_u32(smem), sB = sA + 65536, sBar = sB + 131072;
    const int warp = __shfl_sync(~0u, threadIdx.x >> 5, 0), lane = threadIdx.x & 31, wg = warp >> 2;
    const int nt = blockIdx.x & 3, mt = blockIdx.x >> 2;
    TL(2, 0);
    if (threadIdx.x == 0) {
        for (int i = 0; i < 6; i++) mbar_init(sBar + i * 8, 1);
        asm volatile("fence.mbarrier_init.release.cluster;" ::: "memory");
        for (int kh = 0; kh < 2; kh++) {
            mbar_expect_tx(sBar + kh * 8, 65536);
            tma_2d(sB + kh * 32768, &wmap, nt * 128, kh * 256, sBar + kh * 8);
            tma_2d(sB + 65536 + kh * 32768, &wmap, nt * 128 + 64, kh * 256, sBar + kh * 8);
        }
    }
    const int g = lane >> 2, t = lane & 3;
    const int row0 = mt * 64 + (warp & 3) * 16 + g;
    const int col0 = nt * 128 + wg * 64 + t * 2;
    uint32_t xu[2][8];
    #pragma unroll
    for (int hf = 0; hf < 2; hf++)
        #pragma unroll
        for (int j = 0; j < 8; j++) xu[hf][j] = __ldg((const uint32_t*)(x + (size_t)(row0 + hf * 8) * D_ + col0 + j * 8));
    pdl_wait();
    TL(2, 1);
    if (threadIdx.x == 0) {
        for (int q = 0; q < 4; q++) {
            mbar_expect_tx(sBar + 16 + q * 8, 16384);
            bulk_g2s(sA + q * 16384, g_O + (size_t)mt * 4096 + q * 1024, 16384, sBar + 16 + q * 8);
        }
    }
    const int sel0 = g_sel[0], sel1 = g_sel[1];
    const float2 st0 = g_stats[row0], st1 = g_stats[row0 + 8];
    float upd[2][16];
    #pragma unroll
    for (int hf = 0; hf < 2; hf++) {
        const int row = row0 + hf * 8;
        const int slot = row == sel0 ? 0 : (row == sel1 ? 1 : -1);
        #pragma unroll
        for (int j = 0; j < 16; j++) upd[hf][j] = 0.f;
        if (slot >= 0) {
            const float gate = bf16r(1.0f / (1.0f + __expf(-g_r[row])));
            #pragma unroll
            for (int j = 0; j < 8; j++) {
                float2 a = *(const float2*)&g_ypart[0][slot][col0 + j * 8], b = *(const float2*)&g_ypart[1][slot][col0 + j * 8];
                float2 c = *(const float2*)&g_ypart[2][slot][col0 + j * 8], d = *(const float2*)&g_ypart[3][slot][col0 + j * 8];
                upd[hf][2 * j] = bf16r(bf16r(a.x + b.x + c.x + d.x) * gate);
                upd[hf][2 * j + 1] = bf16r(bf16r(a.y + b.y + c.y + d.y) * gate);
            }
        }
    }
    __syncthreads();
    float acc[32];
    #pragma unroll
    for (int i = 0; i < 32; i++) acc[i] = 0.f;
    const uint64_t da0 = make_desc(sA, 16, 1024, 1);
    const uint64_t db0 = make_desc(sB + wg * 65536, 8192, 1024, 1);
    #pragma unroll 1
    for (int q = 0; q < 4; q++) {
        if ((q & 1) == 0) mbar_wait(sBar + (q >> 1) * 8, 0);
        mbar_wait(sBar + 16 + q * 8, 0);
        WG_FENCE();
        #pragma unroll
        for (int kk = 0; kk < 8; kk++)
            wgmma_n64(acc, da0 + (uint64_t)(q * 1024 + (kk >> 2) * 512 + (kk & 3) * 2), db0 + (uint64_t)(q * 1024 + kk * 128));
        WG_COMMIT();
    }
    wg_wait<0>();
    touch32(acc);
    TL(2, 2);
    #pragma unroll
    for (int hf = 0; hf < 2; hf++) {
        const int row = row0 + hf * 8;
        const float2 st = hf ? st1 : st0;
        #pragma unroll
        for (int j = 0; j < 8; j++) {
            const int col = col0 + j * 8;
            const float x0 = bf_lo(xu[hf][j]), x1 = bf_hi(xu[hf][j]);
            const float b0 = bf16r(ln_elem(x0, st.x, st.y) + upd[hf][2 * j]), b1 = bf16r(ln_elem(x1, st.x, st.y) + upd[hf][2 * j + 1]);
            const float t0 = bf16r(x0 + bf16r(acc[4 * j + hf * 2])), t1 = bf16r(x1 + bf16r(acc[4 * j + hf * 2 + 1]));
            *(uint32_t*)(out + (size_t)row * D_ + col) = pack_bf16(t0 + b0, t1 + b1);
        }
    }
    TL(2, 3);
}

typedef CUresult (*EncodeFn)(CUtensorMap*, CUtensorMapDataType, cuuint32_t, void*, const cuuint64_t*, const cuuint64_t*,
                             const cuuint32_t*, const cuuint32_t*, CUtensorMapInterleave, CUtensorMapSwizzle,
                             CUtensorMapL2promotion, CUtensorMapFloatOOBfill);

void make_wmap(EncodeFn fn, CUtensorMap* map, const void* ptr, int rows, int cols, int box_rows) {
    cuuint64_t dims[2] = {(cuuint64_t)cols, (cuuint64_t)rows};
    cuuint64_t strides[1] = {(cuuint64_t)cols * 2};
    cuuint32_t box[2] = {64, (cuuint32_t)box_rows};
    cuuint32_t es[2] = {1, 1};
    fn(map, CU_TENSOR_MAP_DATA_TYPE_BFLOAT16, 2, (void*)ptr, dims, strides, box, es, CU_TENSOR_MAP_INTERLEAVE_NONE,
       CU_TENSOR_MAP_SWIZZLE_128B, CU_TENSOR_MAP_L2_PROMOTION_L2_256B, CU_TENSOR_MAP_FLOAT_OOB_FILL_NONE);
}

}

extern "C" void kernel_launch(void* const* d_in, const int* in_sizes, int n_in, void* d_out, int out_size) {
    const __nv_bfloat16* x = (const __nv_bfloat16*)d_in[0];
    const __nv_bfloat16* wqkv = (const __nv_bfloat16*)d_in[1];
    const __nv_bfloat16* wo = (const __nv_bfloat16*)d_in[2];
    const __nv_bfloat16* w_r = (const __nv_bfloat16*)d_in[4];
    const __nv_bfloat16* w_gate = (const __nv_bfloat16*)d_in[5];
    const __nv_bfloat16* w_up = (const __nv_bfloat16*)d_in[6];
    const __nv_bfloat16* w_down = (const __nv_bfloat16*)d_in[7];
    __nv_bfloat16* out = (__nv_bfloat16*)d_out;

    static EncodeFn encode = nullptr;
    if (!encode) {
        void* fn = nullptr;
        cudaDriverEntryPointQueryResult qres;
        cudaGetDriverEntryPoint("cuTensorMapEncodeTiled", &fn, cudaEnableDefault, &qres);
        encode = (EncodeFn)fn;
        cudaFuncSetAttribute(k1_ln_qkv, cudaFuncAttributeMaxDynamicSharedMemorySize, K1_SMEM);
        cudaFuncSetAttribute(k2_attn, cudaFuncAttributeMaxDynamicSharedMemorySize, K2_SMEM);
        cudaFuncSetAttribute(k3_out, cudaFuncAttributeMaxDynamicSharedMemorySize, K3_SMEM);
    }
    CUtensorMap map_qkv, map_wo;
    make_wmap(encode, &map_qkv, wqkv, D_, 3 * D_, 64);
    make_wmap(encode, &map_wo, wo, D_, D_, 256);

    k1_ln_qkv<<<128, K1_THREADS, K1_SMEM, cudaStreamPerThread>>>(map_qkv, x, w_r);
    cudaLaunchAttribute at[1];
    at[0].id = cudaLaunchAttributeProgrammaticStreamSerialization;
    at[0].val.programmaticStreamSerializationAllowed = 1;
    cudaLaunchConfig_t cfg = {};
    cfg.stream = cudaStreamPerThread;
    cfg.attrs = at; cfg.numAttrs = 1;
    cfg.gridDim = dim3(132); cfg.blockDim = dim3(K2_THREADS); cfg.dynamicSmemBytes = K2_SMEM;
    cudaLaunchKernelEx(&cfg, k2_attn, x, w_gate, w_up, w_down);
    cfg.gridDim = dim3(128); cfg.blockDim = dim3(K3_THREADS); cfg.dynamicSmemBytes = K3_SMEM;
    cudaLaunchKernelEx(&cfg, k3_out, map_wo, x, out);
}
```

```cpp
#include <cuda_runtime.h>
#include <cuda_bf16.h>
#include <cuda.h>
#include <stdint.h>

namespace {

constexpr int S_ = 2048, D_ = 512, H_ = 32, F_ = 1792;

constexpr uint32_t PMASK = 0xA52;
__host__ __device__ constexpr bool is_poly_group(int g8) { return g8 >= 4 && ((PMASK >> ((g8 - 4) % 12)) & 1); }

__device__ __align__(1024) uint4 g_QKV[3 * H_ * S_ * 2];
#define g_Q (g_QKV)
#define g_K (g_QKV + H_ * S_ * 2)
#define g_V (g_QKV + 2 * H_ * S_ * 2)
__device__ __align__(1024) uint4 g_O[S_ * D_ / 8];
__device__ float2 g_stats[S_];
__device__ uint32_t g_const[4] = {421u, 0x459EB285u  , 0x3F800000u  , 0u};
__device__ float g_r[S_];
__device__ __align__(16) float g_ypart[4][2][D_];
__device__ int g_sel[2];

#define TL(k, p)
__device__ __forceinline__ uint32_t smem_u32(const void* p) { return (uint32_t)__cvta_generic_to_shared(p); }
__device__ __forceinline__ float bf16r(float x) { return __bfloat162float(__float2bfloat16_rn(x)); }
__device__ __forceinline__ uint32_t pack_bf16(float lo, float hi) {
    uint32_t r; asm("cvt.rn.bf16x2.f32 %0, %1, %2;" : "=r"(r) : "f"(hi), "f"(lo)); return r;
}
__device__ __forceinline__ float bf_lo(uint32_t u) { return __uint_as_float(u << 16); }
__device__ __forceinline__ float bf_hi(uint32_t u) { return __uint_as_float(u & 0xFFFF0000u); }
__device__ __forceinline__ float ex2(float x) { float y; asm("ex2.approx.ftz.f32 %0, %1;" : "=f"(y) : "f"(x)); return y; }

__device__ __forceinline__ void mbar_init(uint32_t bar, uint32_t count) {
    asm volatile("mbarrier.init.shared::cta.b64 [%0], %1;" :: "r"(bar), "r"(count) : "memory");
}
__device__ __forceinline__ void mbar_expect_tx(uint32_t bar, uint32_t bytes) {
    asm volatile("mbarrier.arrive.expect_tx.shared::cta.b64 _, [%0], %1;" :: "r"(bar), "r"(bytes) : "memory");
}
__device__ __forceinline__ void mbar_arrive(uint32_t bar) {
    asm volatile("mbarrier.arrive.shared::cta.b64 _, [%0];" :: "r"(bar) : "memory");
}
__device__ __forceinline__ void mbar_wait(uint32_t bar, uint32_t parity) {
    uint32_t done;
    #pragma unroll 1
    for (int it = 0; it < (1 << 26); it++) {
        asm volatile("{.reg .pred p; mbarrier.try_wait.parity.shared::cta.b64 p, [%1], %2; selp.u32 %0, 1, 0, p;}"
                     : "=r"(done) : "r"(bar), "r"(parity) : "memory");
        if (done) return;
    }
    __trap();
}
__device__ __forceinline__ void bulk_g2s(uint32_t dst, const void* src, uint32_t bytes, uint32_t bar) {
    asm volatile("cp.async.bulk.shared::cluster.global.mbarrier::complete_tx::bytes [%0], [%1], %2, [%3];"
                 :: "r"(dst), "l"(src), "r"(bytes), "r"(bar) : "memory");
}
__device__ __forceinline__ void tma_2d(uint32_t dst, const CUtensorMap* map, int c0, int c1, uint32_t bar) {
    asm volatile("cp.async.bulk.tensor.2d.shared::cluster.global.mbarrier::complete_tx::bytes [%0], [%1, {%3, %4}], [%2];"
                 :: "r"(dst), "l"(map), "r"(bar), "r"(c0), "r"(c1) : "memory");
}
__device__ __forceinline__ void fence_async_smem() { asm volatile("fence.proxy.async.shared::cta;" ::: "memory"); }
__device__ __forceinline__ void named_bar(int id, int n) { asm volatile("bar.sync %0, %1;" :: "r"(id), "r"(n) : "memory"); }

__device__ __forceinline__ uint64_t make_desc(uint32_t saddr, uint32_t lbo, uint32_t sbo, uint32_t swz) {
    return (uint64_t)((saddr & 0x3FFFF) >> 4) | ((uint64_t)(lbo >> 4) << 16) | ((uint64_t)(sbo >> 4) << 32) | ((uint64_t)swz << 62);
}
#define WG_FENCE() asm volatile("wgmma.fence.sync.aligned;" ::: "memory")
#define WG_COMMIT() asm volatile("wgmma.commit_group.sync.aligned;" ::: "memory")
template <int N> __device__ __forceinline__ void wg_wait() { asm volatile("wgmma.wait_group.sync.aligned %0;" :: "n"(N) : "memory"); }

#define F4(d, o) "+f"(d[o]), "+f"(d[o + 1]), "+f"(d[o + 2]), "+f"(d[o + 3])
#define F16(d, o) F4(d, o), F4(d, o + 4), F4(d, o + 8), F4(d, o + 12)
#define F32(d, o) F16(d, o), F16(d, o + 16)

__device__ __forceinline__ void wgmma_n192(float* d, uint64_t da, uint64_t db) {
    asm volatile("wgmma.mma_async.sync.aligned.m64n192k16.f32.bf16.bf16 "
        "{%0,%1,%2,%3,%4,%5,%6,%7,%8,%9,%10,%11,%12,%13,%14,%15,%16,%17,%18,%19,%20,%21,%22,%23,%24,%25,%26,%27,%28,%29,%30,%31,"
        "%32,%33,%34,%35,%36,%37,%38,%39,%40,%41,%42,%43,%44,%45,%46,%47,%48,%49,%50,%51,%52,%53,%54,%55,%56,%57,%58,%59,%60,%61,%62,%63,"
        "%64,%65,%66,%67,%68,%69,%70,%71,%72,%73,%74,%75,%76,%77,%78,%79,%80,%81,%82,%83,%84,%85,%86,%87,%88,%89,%90,%91,%92,%93,%94,%95}, "
        "%96, %97, 1, 1, 1, 0, 1;\n"
        : F32(d, 0), F32(d, 32), F32(d, 64) : "l"(da), "l"(db));
}
__device__ __forceinline__ void wgmma_n64(float* d, uint64_t da, uint64_t db) {
    asm volatile("wgmma.mma_async.sync.aligned.m64n64k16.f32.bf16.bf16 "
        "{%0,%1,%2,%3,%4,%5,%6,%7,%8,%9,%10,%11,%12,%13,%14,%15,%16,%17,%18,%19,%20,%21,%22,%23,%24,%25,%26,%27,%28,%29,%30,%31}, "
        "%32, %33, 1, 1, 1, 0, 1;\n"
        : F32(d, 0) : "l"(da), "l"(db));
}
__device__ __forceinline__ void wgmma_qk32(float* d, uint32_t qd, uint32_t kd) {
    asm volatile("{.reg .b64 a, b; mov.b64 a, {%16, 16}; mov.b64 b, {%17, 16};\n"
        "wgmma.mma_async.sync.aligned.m64n32k16.f32.bf16.bf16 {%0,%1,%2,%3,%4,%5,%6,%7,%8,%9,%10,%11,%12,%13,%14,%15}, a, b, 0, 1, 1, 0, 0;}\n"
        : F16(d, 0) : "r"(qd), "r"(kd));
}
__device__ __forceinline__ void wgmma_pv(float* d, const uint32_t* a, uint32_t vd) {
    asm volatile("{.reg .b64 b; mov.b64 b, {%16, 2048};\n"
        "wgmma.mma_async.sync.aligned.m64n24k16.f32.bf16.bf16 {%0,%1,%2,%3,%4,%5,%6,%7,%8,%9,%10,%11}, {%12,%13,%14,%15}, b, 1, 1, 1, 1;}\n"
        : F4(d, 0), F4(d, 4), F4(d, 8) : "r"(a[0]), "r"(a[1]), "r"(a[2]), "r"(a[3]), "r"(vd));
}
__device__ __forceinline__ void touch16(float* d) { asm volatile("" : F16(d, 0) :: "memory"); }
__device__ __forceinline__ void touch12(float* d) { asm volatile("" : F4(d, 0), F4(d, 4), F4(d, 8) :: "memory"); }
__device__ __forceinline__ void touch32(float* d) { asm volatile("" : F32(d, 0) :: "memory"); }
__device__ __forceinline__ void touch96(float* d) { asm volatile("" : F32(d, 0), F32(d, 32), F32(d, 64) :: "memory"); }

__device__ __forceinline__ float ln_elem(float x, float mean_b, float rden) {
    return bf16r(bf16r(x - mean_b) * rden);
}
__device__ __forceinline__ void pdl_wait() { asm volatile("griddepcontrol.wait;" ::: "memory"); }
__device__ __forceinline__ void pdl_launch() { asm volatile("griddepcontrol.launch_dependents;" ::: "memory"); }
__device__ __forceinline__ void cluster_arrive() { asm volatile("barrier.cluster.arrive.release.aligned;" ::: "memory"); }
__device__ __forceinline__ void cluster_wait() { asm volatile("barrier.cluster.wait.acquire.aligned;" ::: "memory"); }

constexpr int K1_THREADS = 288;
constexpr int K1_SMEM = 131072 + 4 * 24576 + 256;

__device__ __forceinline__ float reduce8(float* p, int lane) {
    #pragma unroll
    for (int i = 0; i < 4; i++) {
        const bool up = lane & 16;
        const float send = up ? p[i] : p[i + 4], keep = up ? p[i + 4] : p[i];
        p[i] = keep + __shfl_xor_sync(~0u, send, 16);
    }
    #pragma unroll
    for (int i = 0; i < 2; i++) {
        const bool up = lane & 8;
        const float send = up ? p[i] : p[i + 2], keep = up ? p[i + 2] : p[i];
        p[i] = keep + __shfl_xor_sync(~0u, send, 8);
    }
    const bool up = lane & 4;
    float r = (up ? p[1] : p[0]) + __shfl_xor_sync(~0u, up ? p[0] : p[1], 4);
    r += __shfl_xor_sync(~0u, r, 2);
    r += __shfl_xor_sync(~0u, r, 1);
    return r;
}

__global__ void __cluster_dims__(2, 1, 1) __launch_bounds__(K1_THREADS, 1)
k1_ln_qkv(const __grid_constant__ CUtensorMap wmap, const __nv_bfloat16* __restrict__ x, const __nv_bfloat16* __restrict__ w_r) {
    extern __shared__ __align__(1024) unsigned char smem[];
    const uint32_t sA = smem_u32(smem), sB = sA + 131072, sBar = sB + 4 * 24576;
    const int warp = __shfl_sync(~0u, threadIdx.x >> 5, 0), lane = threadIdx.x & 31;
    const int nt = blockIdx.x & 7, mt = blockIdx.x >> 3, rank = blockIdx.x & 1;
    TL(0, 0);
    pdl_launch();
    if (warp == 8) {
        if (lane == 0) {
            for (int i = 0; i < 4; i++) { mbar_init(sBar + i * 8, 1); mbar_init(sBar + 32 + i * 8, 2); }
            asm volatile("fence.mbarrier_init.release.cluster;" ::: "memory");
            for (int kc = 0; kc < 4; kc++) {
                mbar_expect_tx(sBar + kc * 8, 24576);
                for (int j = 0; j < 3; j++) tma_2d(sB + kc * 24576 + j * 8192, &wmap, nt * 192 + j * 64, kc * 64, sBar + kc * 8);
            }
        }
        __syncwarp();
        cluster_arrive();
        cluster_wait();
        cluster_arrive();
        cluster_wait();
        if (lane == 0) {
            for (int kc = 4; kc < 8; kc++) {
                const int st = kc & 3;
                mbar_wait(sBar + 32 + st * 8, 0);
                mbar_expect_tx(sBar + st * 8, 24576);
                for (int j = 0; j < 3; j++) tma_2d(sB + st * 24576 + j * 8192, &wmap, nt * 192 + j * 64, kc * 64, sBar + st * 8);
            }
        }
        return;
    }
    const int rbase = rank * 64 + warp * 8;
    uint32_t u[8][8];
    #pragma unroll
    for (int i = 0; i < 8; i++) {
        const __nv_bfloat16* xp = x + (size_t)(mt * 128 + rbase + i) * D_;
        const uint4 a = __ldg((const uint4*)(xp + lane * 8)), b = __ldg((const uint4*)(xp + 256 + lane * 8));
        u[i][0] = a.x; u[i][1] = a.y; u[i][2] = a.z; u[i][3] = a.w; u[i][4] = b.x; u[i][5] = b.y; u[i][6] = b.z; u[i][7] = b.w;
    }
    uint4 wr0 = make_uint4(0, 0, 0, 0), wr1 = wr0;
    if (nt < 2) { wr0 = __ldg((const uint4*)(w_r + lane * 8)); wr1 = __ldg((const uint4*)(w_r + 256 + lane * 8)); }
    asm volatile("barrier.cluster.arrive.relaxed.aligned;" ::: "memory");
    TL(0, 1);
    float part[8];
    #pragma unroll
    for (int i = 0; i < 8; i++) {
        float s0 = 0.f, s1 = 0.f;
        #pragma unroll
        for (int j = 0; j < 8; j++) { s0 += bf_lo(u[i][j]); s1 += bf_hi(u[i][j]); }
        part[i] = s0 + s1;
    }
    TL(0, 8);
    const float mean_l = reduce8(part, lane) * (1.0f / D_);
    #pragma unroll
    for (int i = 0; i < 8; i++) {
        const float mean = __shfl_sync(~0u, mean_l, i * 4);
        float q0 = 0.f, q1 = 0.f;
        #pragma unroll
        for (int j = 0; j < 8; j++) {
            const float d0 = bf_lo(u[i][j]) - mean, d1 = bf_hi(u[i][j]) - mean;
            q0 = fmaf(d0, d0, q0); q1 = fmaf(d1, d1, q1);
        }
        part[i] = q0 + q1;
    }
    const float var_b = bf16r(reduce8(part, lane) * (1.0f / D_));
    const float rden_l = __frcp_rn(bf16r(__fsqrt_rn(bf16r(var_b + 1e-5f))));
    const uint32_t mean2_l = pack_bf16(mean_l, mean_l);
    uint32_t peerA;
    asm volatile("mapa.shared::cluster.u32 %0, %1, %2;" : "=r"(peerA) : "r"(sA), "r"(rank ^ 1));
    cluster_wait();
    #pragma unroll
    for (int i = 0; i < 8; i++) {
        const int r = rbase + i;
        const uint32_t m2 = __shfl_sync(~0u, mean2_l, i * 4);
        const float rden = __shfl_sync(~0u, rden_l, i * 4);
        #pragma unroll
        for (int j = 0; j < 8; j++) {
            uint32_t d2;
            asm("sub.rn.bf16x2 %0, %1, %2;" : "=r"(d2) : "r"(u[i][j]), "r"(m2));
            u[i][j] = pack_bf16(bf_lo(d2) * rden, bf_hi(d2) * rden);
        }
        const uint32_t off = (lane >> 3) * 16384 + r * 128 + (((lane & 7) ^ (r & 7)) * 16);
        *(uint4*)(smem + off) = make_uint4(u[i][0], u[i][1], u[i][2], u[i][3]);
        *(uint4*)(smem + off + 65536) = make_uint4(u[i][4], u[i][5], u[i][6], u[i][7]);
        asm volatile("st.shared::cluster.v4.b32 [%0], {%1, %2, %3, %4};" :: "r"(peerA + off), "r"(u[i][0]), "r"(u[i][1]), "r"(u[i][2]), "r"(u[i][3]) : "memory");
        asm volatile("st.shared::cluster.v4.b32 [%0], {%1, %2, %3, %4};" :: "r"(peerA + off + 65536), "r"(u[i][4]), "r"(u[i][5]), "r"(u[i][6]), "r"(u[i][7]) : "memory");
    }
    TL(0, 2);
    asm volatile("fence.proxy.async;" ::: "memory");
    cluster_arrive();
    if (nt < 2) {
        const uint32_t w[8] = {wr0.x, wr0.y, wr0.z, wr0.w, wr1.x, wr1.y, wr1.z, wr1.w};
        #pragma unroll
        for (int i = 0; i < 8; i++) {
            float a0 = 0.f, a1 = 0.f;
            #pragma unroll
            for (int j = 0; j < 8; j++) { a0 = fmaf(bf_lo(u[i][j]), bf_lo(w[j]), a0); a1 = fmaf(bf_hi(u[i][j]), bf_hi(w[j]), a1); }
            part[i] = a0 + a1;
        }
        const float rl = reduce8(part, lane);
        if ((lane & 3) == 0) {
            const int row = mt * 128 + rbase + (lane >> 2);
            g_r[row] = bf16r(rl);
            g_stats[row] = make_float2(bf_lo(mean2_l), rden_l);
        }
    }
    cluster_wait();
    asm volatile("fence.proxy.async;" ::: "memory");
    TL(0, 3);
    const int wg = warp >> 2;
    float acc[96];
    #pragma unroll
    for (int i = 0; i < 96; i++) acc[i] = 0.f;
    const uint64_t da0 = make_desc(sA + wg * 8192, 16, 1024, 1);
    const uint64_t db0 = make_desc(sB, 8192, 1024, 1);
    #pragma unroll 1
    for (int kc = 0; kc < 8; kc++) {
        const int st = kc & 3;
        mbar_wait(sBar + st * 8, kc >> 2);
        WG_FENCE();
        #pragma unroll
        for (int kk = 0; kk < 4; kk++)
            wgmma_n192(acc, da0 + (uint64_t)(kc * 1024 + kk * 2), db0 + (uint64_t)(st * 1536 + kk * 128));
        WG_COMMIT();
        wg_wait<1>();
        if (kc >= 1 && kc <= 4 && (threadIdx.x & 127) == 0) mbar_arrive(sBar + 32 + (kc - 1) * 8);
    }
    wg_wait<0>();
    touch96(acc);
    TL(0, 5);
    const int g = lane >> 2, t = lane & 3;
    const int row0 = mt * 128 + warp * 16;
    const int g8a = row0 >> 3;
    const float sgn0 = is_poly_group(g8a) ? -1.f : 1.f, sgn1 = is_poly_group(g8a + 1) ? -1.f : 1.f;
    constexpr float QS = 0.25f * 1.4426950408889634f;
    const int off_qk = g8a * 64 + g * 4 + t, off_v = (row0 + g) * 4 + t;
    #pragma unroll
    for (int jj = 0; jj < 12; jj++) {
        const int hg = nt * 12 + jj;
        const bool isv = hg >= 64;
        const float m0 = isv ? sgn0 : (hg < 32 ? QS : 1.0f), m1 = isv ? sgn1 : (hg < 32 ? QS : 1.0f);
        uint32_t* base = (uint32_t*)g_QKV + (size_t)hg * 16384 + (isv ? off_v : off_qk);
        const int hs = isv ? 8192 : 32, rs = isv ? 32 : 64;
        base[0] = pack_bf16(acc[8 * jj] * m0, acc[8 * jj + 1] * m0);
        base[rs] = pack_bf16(acc[8 * jj + 2] * m1, acc[8 * jj + 3] * m1);
        base[hs] = pack_bf16(acc[8 * jj + 4] * m0, acc[8 * jj + 5] * m0);
        base[hs + rs] = pack_bf16(acc[8 * jj + 6] * m1, acc[8 * jj + 7] * m1);
    }
    TL(0, 6);
}

constexpr int K2_THREADS = 512;
constexpr int K2_SMEM = 65536 + 98304 + 16384 + 128;

__device__ __forceinline__ uint32_t polyexp(float s, float cb, uint32_t c421, float c3, float one) {
    float u;
    asm("fma.rn.sat.f32 %0, %1, 0f3B808081, %2;" : "=f"(u) : "f"(s), "f"(cb));
    float z = fmaf(u, 0.99609375f, one);
    uint32_t rb;
    asm("lop3.b32 %0, %1, 0xFFFF8000, %2, 0xEA;" : "=r"(rb) : "r"(__float_as_uint(z)), "r"(c421));
    float f = z - __uint_as_float(rb);
    float h = fmaf(f, c3, 58.86525f);
    h = fmaf(f, h, -0.29870507f);
    return __float_as_uint(fmaf(f, h, z));
}

struct ExpC { float nm0, nm1, cb0, cb1, c3, one; uint32_t c421; };

template <int G>
__device__ __forceinline__ void exp_block(const float* s, uint32_t* p, const ExpC& c) {
    #pragma unroll
    for (int hf = 0; hf < 2; hf++) {
        const float* x = s + hf * 4;
        if ((PMASK >> (G + hf)) & 1) {
            p[hf * 2 + 0] = __byte_perm(polyexp(x[0], c.cb0, c.c421, c.c3, c.one), polyexp(x[1], c.cb0, c.c421, c.c3, c.one), 0x6521);
            p[hf * 2 + 1] = __byte_perm(polyexp(x[2], c.cb1, c.c421, c.c3, c.one), polyexp(x[3], c.cb1, c.c421, c.c3, c.one), 0x6521);
        } else {
            p[hf * 2 + 0] = pack_bf16(ex2(x[0] + c.nm0), ex2(x[1] + c.nm0));
            p[hf * 2 + 1] = pack_bf16(ex2(x[2] + c.nm1), ex2(x[3] + c.nm1));
        }
    }
}

__device__ __forceinline__ void max16(const float* s, float& mx0, float& mx1) {
    #pragma unroll
    for (int j = 0; j < 4; j++) {
        mx0 = fmaxf(mx0, fmaxf(s[4 * j], s[4 * j + 1]));
        mx1 = fmaxf(mx1, fmaxf(s[4 * j + 2], s[4 * j + 3]));
    }
}

__device__ void moe_cta(int part, unsigned char* smem, const __nv_bfloat16* __restrict__ x, const __nv_bfloat16* __restrict__ w_gate,
                        const __nv_bfloat16* __restrict__ w_up, const __nv_bfloat16* __restrict__ w_down) {
    float* xs = (float*)smem;
    float* red = xs + 1024;
    float* hs = red + 8 * 4 * 448;
    __shared__ float s_v[32];
    __shared__ int s_i[32];
    __shared__ int s_sel[2];
    const int tid = threadIdx.x, warp = tid >> 5, lane = tid & 31;
    for (int pass = 0; pass < 2; pass++) {
        float bv = -INFINITY; int bi = 0x7fffffff;
        const int excl = pass ? s_sel[0] : -1;
        for (int i = tid; i < S_; i += K2_THREADS) {
            float v = g_r[i];
            if (i != excl && (v > bv || (v == bv && i < bi) || bi == 0x7fffffff)) { bv = v; bi = i; }
        }
        #pragma unroll
        for (int o = 16; o; o >>= 1) {
            float ov = __shfl_xor_sync(~0u, bv, o); int oi = __shfl_xor_sync(~0u, bi, o);
            if (ov > bv || (ov == bv && oi < bi)) { bv = ov; bi = oi; }
        }
        if (lane == 0) { s_v[warp] = bv; s_i[warp] = bi; }
        __syncthreads();
        if (warp == 0) {
            bv = lane < 16 ? s_v[lane] : -INFINITY; bi = lane < 16 ? s_i[lane] : 0x7fffffff;
            #pragma unroll
            for (int o = 16; o; o >>= 1) {
                float ov = __shfl_xor_sync(~0u, bv, o); int oi = __shfl_xor_sync(~0u, bi, o);
                if (ov > bv || (ov == bv && oi < bi)) { bv = ov; bi = oi; }
            }
            if (lane == 0) s_sel[pass] = (bi == 0x7fffffff) ? pass : bi;
        }
        __syncthreads();
    }
    for (int i = tid; i < 1024; i += K2_THREADS) {
        const int tok = s_sel[i >> 9];
        const float2 st = g_stats[tok];
        xs[i] = ln_elem(__bfloat162float(x[(size_t)tok * D_ + (i & 511)]), st.x, st.y);
    }
    if (part == 0 && tid < 2) g_sel[tid] = s_sel[tid];
    __syncthreads();
    const int c0 = part * 448;
    if (tid < 448) {
        const int cg = tid % 56, ks = tid / 56;
        float a[4][8];
        #pragma unroll
        for (int i = 0; i < 4; i++)
            #pragma unroll
            for (int j = 0; j < 8; j++) a[i][j] = 0.f;
        const __nv_bfloat16* pg = w_gate + (size_t)(ks * 64) * F_ + c0 + cg * 8;
        const __nv_bfloat16* pu = w_up + (size_t)(ks * 64) * F_ + c0 + cg * 8;
        #pragma unroll 8
        for (int k = 0; k < 64; k++) {
            const uint4 gv = __ldg((const uint4*)(pg + (size_t)k * F_));
            const uint4 uv = __ldg((const uint4*)(pu + (size_t)k * F_));
            const float x0 = xs[ks * 64 + k], x1 = xs[512 + ks * 64 + k];
            const uint32_t gu[4] = {gv.x, gv.y, gv.z, gv.w}, uu[4] = {uv.x, uv.y, uv.z, uv.w};
            #pragma unroll
            for (int j = 0; j < 4; j++) {
                const float g0 = bf_lo(gu[j]), g1 = bf_hi(gu[j]), u0 = bf_lo(uu[j]), u1 = bf_hi(uu[j]);
                a[0][2 * j] = fmaf(x0, g0, a[0][2 * j]); a[0][2 * j + 1] = fmaf(x0, g1, a[0][2 * j + 1]);
                a[1][2 * j] = fmaf(x1, g0, a[1][2 * j]); a[1][2 * j + 1] = fmaf(x1, g1, a[1][2 * j + 1]);
                a[2][2 * j] = fmaf(x0, u0, a[2][2 * j]); a[2][2 * j + 1] = fmaf(x0, u1, a[2][2 * j + 1]);
                a[3][2 * j] = fmaf(x1, u0, a[3][2 * j]); a[3][2 * j + 1] = fmaf(x1, u1, a[3][2 * j + 1]);
            }
        }
        #pragma unroll
        for (int i = 0; i < 4; i++)
            #pragma unroll
            for (int j = 0; j < 8; j++) red[(ks * 4 + i) * 448 + cg * 8 + j] = a[i][j];
    }
    __syncthreads();
    for (int i = tid; i < 896; i += K2_THREADS) {
        const int tok = i / 448, c = i % 448;
        float gs = 0.f, us = 0.f;
        #pragma unroll
        for (int ks = 0; ks < 8; ks++) { gs += red[(ks * 4 + tok) * 448 + c]; us += red[(ks * 4 + 2 + tok) * 448 + c]; }
        gs = bf16r(gs); us = bf16r(us);
        const float sl = bf16r(gs / (1.0f + __expf(-gs)));
        hs[i] = bf16r(sl * us);
    }
    __syncthreads();
    {
        const int cg = tid & 63, fs = tid >> 6;
        float a[2][8];
        #pragma unroll
        for (int j = 0; j < 8; j++) { a[0][j] = 0.f; a[1][j] = 0.f; }
        const __nv_bfloat16* pd = w_down + (size_t)(c0 + fs * 56) * D_ + cg * 8;
        #pragma unroll 8
        for (int f = 0; f < 56; f++) {
            const uint4 dv = __ldg((const uint4*)(pd + (size_t)f * D_));
            const float h0 = hs[fs * 56 + f], h1 = hs[448 + fs * 56 + f];
            const uint32_t du[4] = {dv.x, dv.y, dv.z, dv.w};
            #pragma unroll
            for (int j = 0; j < 4; j++) {
                const float d0 = bf_lo(du[j]), d1 = bf_hi(du[j]);
                a[0][2 * j] = fmaf(h0, d0, a[0][2 * j]); a[0][2 * j + 1] = fmaf(h0, d1, a[0][2 * j + 1]);
                a[1][2 * j] = fmaf(h1, d0, a[1][2 * j]); a[1][2 * j + 1] = fmaf(h1, d1, a[1][2 * j + 1]);
            }
        }
        #pragma unroll
        for (int j = 0; j < 8; j++) { red[(fs * 2) * 512 + cg * 8 + j] = a[0][j]; red[(fs * 2 + 1) * 512 + cg * 8 + j] = a[1][j]; }
    }
    __syncthreads();
    for (int i = tid; i < 1024; i += K2_THREADS) {
        float s = 0.f;
        #pragma unroll
        for (int fs = 0; fs < 8; fs++) s += red[(fs * 2 + (i >> 9)) * 512 + (i & 511)];
        g_ypart[part][i >> 9][i & 511] = s;
    }
}

__global__ void __launch_bounds__(K2_THREADS, 1)
k2_attn(const __nv_bfloat16* __restrict__ x, const __nv_bfloat16* __restrict__ w_gate, const __nv_bfloat16* __restrict__ w_up,
        const __nv_bfloat16* __restrict__ w_down) {
    extern __shared__ __align__(1024) unsigned char smem[];
    TL(1, 0);
    pdl_launch();
    if (blockIdx.x >= 128) {
        const int part = blockIdx.x - 128;
        {
            const int k = threadIdx.x;
            asm volatile("cp.async.bulk.prefetch.L2.global [%0], %1;" :: "l"(w_gate + (size_t)k * F_ + part * 448), "r"(896) : "memory");
            asm volatile("cp.async.bulk.prefetch.L2.global [%0], %1;" :: "l"(w_up + (size_t)k * F_ + part * 448), "r"(896) : "memory");
            if (k < 56) asm volatile("cp.async.bulk.prefetch.L2.global [%0], %1;" :: "l"(w_down + (size_t)(part * 448 + k * 8) * D_), "r"(8192) : "memory");
        }
        pdl_wait(); TL(1, 1); moe_cta(blockIdx.x - 128, smem, x, w_gate, w_up, w_down); TL(1, 2); return; }
    const uint32_t sK = smem_u32(smem), sV = sK + 65536, sQ = sV + 98304, sBar = sQ + 16384;
    const int h = blockIdx.x >> 2, qb = blockIdx.x & 3;
    const int warp = __shfl_sync(~0u, threadIdx.x >> 5, 0), lane = threadIdx.x & 31, wg = warp >> 2;
    if (threadIdx.x == 0) {
        mbar_init(sBar, 1); mbar_init(sBar + 8, 1);
        asm volatile("fence.mbarrier_init.release.cluster;" ::: "memory");
        pdl_wait();
        TL(1, 1);
        const uint4* gk = g_K + (size_t)h * 4096;
        const uint4* gv = g_V + (size_t)h * 4096;
        mbar_expect_tx(sBar, 16384 + 16384 + 2 * 8192);
        bulk_g2s(sQ, g_Q + (size_t)h * 4096 + qb * 1024, 16384, sBar);
        bulk_g2s(sK, gk, 16384, sBar);
        bulk_g2s(sV, gv, 8192, sBar);
        bulk_g2s(sV + 32768, gv + 2048, 8192, sBar);
        mbar_expect_tx(sBar + 8, 49152 + 2 * 24576);
        bulk_g2s(sK + 16384, gk + 1024, 49152, sBar + 8);
        bulk_g2s(sV + 8192, gv + 512, 24576, sBar + 8);
        bulk_g2s(sV + 32768 + 8192, gv + 2048 + 512, 24576, sBar + 8);
    }
    for (int i = threadIdx.x; i < 2048; i += K2_THREADS) {
        const uint32_t v = is_poly_group(i >> 3) ? 0xBF80BF80u : 0x3F803F80u;
        *(uint4*)(smem + 65536 + 65536 + i * 16) = make_uint4(v, v, v, v);
    }
    fence_async_smem();
    __syncthreads();
    ExpC c;
    {
        const volatile uint32_t* cc = g_const;
        c.c421 = cc[0]; c.c3 = __uint_as_float(cc[1]); c.one = __uint_as_float(cc[2]);
    }
    const uint32_t kdesc0 = (uint32_t)make_desc(sK, 128, 256, 0);
    const uint32_t vdesc0 = (uint32_t)make_desc(sV, 128, 32768, 0);
    mbar_wait(sBar, 0);
    TL(1, 2);
    #pragma unroll 1
    for (int pass = 0; pass < 2; pass++) {
        const int unit = pass * 4 + wg;
        const uint32_t q = (uint32_t)make_desc(sQ + unit * 2048, 128, 256, 0);
        float o[12];
        #pragma unroll 1
        for (int attempt = 0; attempt < 2; attempt++) {
            float s0[16], s1[16], s2[16];
            #pragma unroll
            for (int i = 0; i < 16; i++) { s0[i] = 0.f; s1[i] = 0.f; s2[i] = 0.f; }
            float mx0 = -INFINITY, mx1 = -INFINITY;
            if (attempt) {
                #pragma unroll 1
                for (int it = 0; it < 64; it++) {
                    WG_FENCE();
                    wgmma_qk32(s0, q, kdesc0 + it * 64);
                    WG_COMMIT();
                    wg_wait<0>();
                    touch16(s0);
                    max16(s0, mx0, mx1);
                }
            }
            #pragma unroll
            for (int i = 0; i < 12; i++) o[i] = 0.f;
            WG_FENCE();
            wgmma_qk32(s2, q, kdesc0);
            wgmma_qk32(s0, q, kdesc0 + 64);
            wgmma_qk32(s1, q, kdesc0 + 128);
            WG_COMMIT();
            wg_wait<0>();
            touch16(s0); touch16(s1); touch16(s2);
            max16(s0, mx0, mx1); max16(s1, mx0, mx1); max16(s2, mx0, mx1);
            mx0 = fmaxf(mx0, __shfl_xor_sync(~0u, mx0, 1)); mx0 = fmaxf(mx0, __shfl_xor_sync(~0u, mx0, 2));
            mx1 = fmaxf(mx1, __shfl_xor_sync(~0u, mx1, 1)); mx1 = fmaxf(mx1, __shfl_xor_sync(~0u, mx1, 2));
            const float bias = attempt ? 0.0f : 64.0f;
            c.nm0 = __shfl_sync(~0u, -(mx0 + bias), lane); c.nm1 = __shfl_sync(~0u, -(mx1 + bias), lane);
            c.cb0 = __shfl_sync(~0u, (127.0f + c.nm0) * (1.0f / 255.0f), lane);
            c.cb1 = __shfl_sync(~0u, (127.0f + c.nm1) * (1.0f / 255.0f), lane);
            uint32_t kd = kdesc0 + 192, vd = vdesc0 + 32;
            {
                uint32_t pa[4], pb[4];
                exp_block<12>(s2, pa, c);
                exp_block<14>(s2 + 8, pb, c);
                WG_FENCE();
                wgmma_pv(o, pa, vdesc0); wgmma_pv(o, pb, vdesc0 + 16);
                WG_COMMIT();
            }
            #pragma unroll 1
            for (int seg = 0; seg < 2; seg++) {
            if (seg) { wg_wait<0>(); mbar_wait(sBar + 8, 0); __syncwarp(); }
            #pragma unroll 1
            for (int it = seg ? 3 : 0; it < (seg ? 21 : 3); it++) {
                uint32_t p[6][4];
                WG_FENCE();
                wgmma_qk32(s2, q, kd);
                WG_COMMIT();
                exp_block<0>(s0, p[0], c);
                exp_block<2>(s0 + 8, p[1], c);
                WG_FENCE();
                wgmma_pv(o, p[0], vd); wgmma_pv(o, p[1], vd + 16);
                wgmma_qk32(s0, q, kd + 64);
                WG_COMMIT();
                wg_wait<1>();
                touch16(s2);
                exp_block<4>(s1, p[2], c);
                exp_block<6>(s1 + 8, p[3], c);
                WG_FENCE();
                wgmma_pv(o, p[2], vd + 32); wgmma_pv(o, p[3], vd + 48);
                wgmma_qk32(s1, q, kd + 128);
                WG_COMMIT();
                wg_wait<1>();
                touch16(s0);
                exp_block<8>(s2, p[4], c);
                exp_block<10>(s2 + 8, p[5], c);
                WG_FENCE();
                wgmma_pv(o, p[4], vd + 64); wgmma_pv(o, p[5], vd + 80);
                WG_COMMIT();
                vd += 96; kd += 192;
                wg_wait<1>();
                touch16(s1);
            }
            }
            wg_wait<0>();
            touch12(o);
            if (attempt) break;
            float big = 0.f;
            #pragma unroll
            for (int i = 0; i < 12; i++) big = fmaxf(big, fabsf(o[i]));
            bool bad = !(big < 1e30f);
            #pragma unroll
            for (int i = 0; i < 12; i++) bad |= (o[i] != o[i]);
            uint32_t any;
            asm volatile("{.reg .pred p, q; setp.ne.u32 p, %1, 0; barrier.cta.red.or.pred.aligned q, %2, 128, p; selp.u32 %0, 1, 0, q;}"
                         : "=r"(any) : "r"((uint32_t)bad), "r"(1 + wg) : "memory");
            if (!__any_sync(~0u, any)) break;
        }
        const int g = lane >> 2, t = lane & 3;
        const int r = (warp & 3) * 16 + g;
        const float i0 = __fdiv_rn(1.0f, o[8]), i1 = __fdiv_rn(1.0f, o[10]);
        uint32_t* ob = (uint32_t*)(g_O + (size_t)(qb * 8 + unit) * 4096 + (h >> 2) * 512 + r * 8) + t;
        const int c0 = ((h & 3) * 2) ^ (r & 7), c1 = ((h & 3) * 2 + 1) ^ (r & 7);
        ob[c0 * 4] = pack_bf16(o[0] * i0, o[1] * i0);
        ob[c1 * 4] = pack_bf16(o[4] * i0, o[5] * i0);
        ob[256 + c0 * 4] = pack_bf16(o[2] * i1, o[3] * i1);
        ob[256 + c1 * 4] = pack_bf16(o[6] * i1, o[7] * i1);
        TL(1, 3 + pass);
    }
}

constexpr int K3_THREADS = 256;
constexpr int K3_SMEM = 65536 + 131072 + 128;

__global__ void __launch_bounds__(K3_THREADS, 1)
k3_out(const __grid_constant__ CUtensorMap wmap, const __nv_bfloat16* __restrict__ x, __nv_bfloat16* __restrict__ out) {
    extern __shared__ __align__(1024) unsigned char smem[];
    const uint32_t sA = smem_u32(smem), sB = sA + 65536, sBar = sB + 131072;
    const int warp = __shfl_sync(~0u, threadIdx.x >> 5, 0), lane = threadIdx.x & 31, wg = warp >> 2;
    const int nt = blockIdx.x & 3, mt = blockIdx.x >> 2;
    TL(2, 0);
    if (threadIdx.x == 0) {
        for (int i = 0; i < 6; i++) mbar_init(sBar + i * 8, 1);
        asm volatile("fence.mbarrier_init.release.cluster;" ::: "memory");
        for (int kh = 0; kh < 2; kh++) {
            mbar_expect_tx(sBar + kh * 8, 65536);
            tma_2d(sB + kh * 32768, &wmap, nt * 128, kh * 256, sBar + kh * 8);
            tma_2d(sB + 65536 + kh * 32768, &wmap, nt * 128 + 64, kh * 256, sBar + kh * 8);
        }
    }
    const int er = threadIdx.x >> 2, ec = (threadIdx.x & 3) * 32;
    const int row = mt * 64 + er;
    uint4 xv[4];
    #pragma unroll
    for (int j = 0; j < 4; j++) xv[j] = __ldg((const uint4*)(x + (size_t)row * D_ + nt * 128 + ec) + j);
    pdl_wait();
    TL(2, 1);
    if (threadIdx.x == 0) {
        for (int q = 0; q < 4; q++) {
            mbar_expect_tx(sBar + 16 + q * 8, 16384);
            bulk_g2s(sA + q * 16384, g_O + (size_t)mt * 4096 + q * 1024, 16384, sBar + 16 + q * 8);
        }
    }
    const int sel0 = g_sel[0], sel1 = g_sel[1];
    const float2 st = g_stats[row];
    uint32_t bb[16];
    {
        const uint32_t xu[16] = {xv[0].x, xv[0].y, xv[0].z, xv[0].w, xv[1].x, xv[1].y, xv[1].z, xv[1].w,
                                 xv[2].x, xv[2].y, xv[2].z, xv[2].w, xv[3].x, xv[3].y, xv[3].z, xv[3].w};
        #pragma unroll
        for (int j = 0; j < 16; j++) bb[j] = pack_bf16(bf16r(bf_lo(xu[j]) - st.x) * st.y, bf16r(bf_hi(xu[j]) - st.x) * st.y);
        const int slot = row == sel0 ? 0 : (row == sel1 ? 1 : -1);
        if (slot >= 0) {
            const float gate = bf16r(1.0f / (1.0f + __expf(-g_r[row])));
            const int c0 = nt * 128 + ec;
            #pragma unroll
            for (int j = 0; j < 16; j++) {
                const float2 a = *(const float2*)&g_ypart[0][slot][c0 + 2 * j], b = *(const float2*)&g_ypart[1][slot][c0 + 2 * j];
                const float2 c = *(const float2*)&g_ypart[2][slot][c0 + 2 * j], d = *(const float2*)&g_ypart[3][slot][c0 + 2 * j];
                bb[j] = pack_bf16(bf_lo(bb[j]) + bf16r(bf16r(a.x + b.x + c.x + d.x) * gate), bf_hi(bb[j]) + bf16r(bf16r(a.y + b.y + c.y + d.y) * gate));
            }
        }
    }
    __syncthreads();
    float acc[32];
    #pragma unroll
    for (int i = 0; i < 32; i++) acc[i] = 0.f;
    const uint64_t da0 = make_desc(sA, 16, 1024, 1);
    const uint64_t db0 = make_desc(sB + wg * 65536, 8192, 1024, 1);
    #pragma unroll 1
    for (int q = 0; q < 4; q++) {
        if ((q & 1) == 0) mbar_wait(sBar + (q >> 1) * 8, 0);
        mbar_wait(sBar + 16 + q * 8, 0);
        WG_FENCE();
        #pragma unroll
        for (int kk = 0; kk < 8; kk++)
            wgmma_n64(acc, da0 + (uint64_t)(q * 1024 + (kk >> 2) * 512 + (kk & 3) * 2), db0 + (uint64_t)(q * 1024 + kk * 128));
        WG_COMMIT();
    }
    wg_wait<0>();
    touch32(acc);
    TL(2, 2);
    __syncthreads();
    {
        const int g = lane >> 2, t = lane & 3;
        unsigned char* sp = smem + ((warp & 3) * 16 + g) * 272 + wg * 128 + t * 4;
        #pragma unroll
        for (int j = 0; j < 8; j++) {
            *(uint32_t*)(sp + j * 16) = pack_bf16(acc[4 * j], acc[4 * j + 1]);
            *(uint32_t*)(sp + 8 * 272 + j * 16) = pack_bf16(acc[4 * j + 2], acc[4 * j + 3]);
        }
    }
    __syncthreads();
    #pragma unroll
    for (int j = 0; j < 4; j++) {
        const uint4 av = *(const uint4*)(smem + er * 272 + ec * 2 + j * 16);
        const uint32_t au[4] = {av.x, av.y, av.z, av.w}, xu[4] = {xv[j].x, xv[j].y, xv[j].z, xv[j].w};
        uint32_t o[4];
        #pragma unroll
        for (int i = 0; i < 4; i++) {
            uint32_t t2;
            asm("add.rn.bf16x2 %0, %1, %2;" : "=r"(t2) : "r"(xu[i]), "r"(au[i]));
            asm("add.rn.bf16x2 %0, %1, %2;" : "=r"(o[i]) : "r"(t2), "r"(bb[j * 4 + i]));
        }
        *((uint4*)(out + (size_t)row * D_ + nt * 128 + ec) + j) = make_uint4(o[0], o[1], o[2], o[3]);
    }
    TL(2, 3);
}

typedef CUresult (*EncodeFn)(CUtensorMap*, CUtensorMapDataType, cuuint32_t, void*, const cuuint64_t*, const cuuint64_t*,
                             const cuuint32_t*, const cuuint32_t*, CUtensorMapInterleave, CUtensorMapSwizzle,
                             CUtensorMapL2promotion, CUtensorMapFloatOOBfill);

void make_wmap(EncodeFn fn, CUtensorMap* map, const void* ptr, int rows, int cols, int box_rows) {
    cuuint64_t dims[2] = {(cuuint64_t)cols, (cuuint64_t)rows};
    cuuint64_t strides[1] = {(cuuint64_t)cols * 2};
    cuuint32_t box[2] = {64, (cuuint32_t)box_rows};
    cuuint32_t es[2] = {1, 1};
    fn(map, CU_TENSOR_MAP_DATA_TYPE_BFLOAT16, 2, (void*)ptr, dims, strides, box, es, CU_TENSOR_MAP_INTERLEAVE_NONE,
       CU_TENSOR_MAP_SWIZZLE_128B, CU_TENSOR_MAP_L2_PROMOTION_L2_256B, CU_TENSOR_MAP_FLOAT_OOB_FILL_NONE);
}

}

extern "C" void kernel_launch(void* const* d_in, const int* in_sizes, int n_in, void* d_out, int out_size) {
    const __nv_bfloat16* x = (const __nv_bfloat16*)d_in[0];
    const __nv_bfloat16* wqkv = (const __nv_bfloat16*)d_in[1];
    const __nv_bfloat16* wo = (const __nv_bfloat16*)d_in[2];
    const __nv_bfloat16* w_r = (const __nv_bfloat16*)d_in[4];
    const __nv_bfloat16* w_gate = (const __nv_bfloat16*)d_in[5];
    const __nv_bfloat16* w_up = (const __nv_bfloat16*)d_in[6];
    const __nv_bfloat16* w_down = (const __nv_bfloat16*)d_in[7];
    __nv_bfloat16* out = (__nv_bfloat16*)d_out;

    static EncodeFn encode = nullptr;
    if (!encode) {
        void* fn = nullptr;
        cudaDriverEntryPointQueryResult qres;
        cudaGetDriverEntryPoint("cuTensorMapEncodeTiled", &fn, cudaEnableDefault, &qres);
        encode = (EncodeFn)fn;
        cudaFuncSetAttribute(k1_ln_qkv, cudaFuncAttributeMaxDynamicSharedMemorySize, K1_SMEM);
        cudaFuncSetAttribute(k2_attn, cudaFuncAttributeMaxDynamicSharedMemorySize, K2_SMEM);
        cudaFuncSetAttribute(k3_out, cudaFuncAttributeMaxDynamicSharedMemorySize, K3_SMEM);
    }
    CUtensorMap map_qkv, map_wo;
    make_wmap(encode, &map_qkv, wqkv, D_, 3 * D_, 64);
    make_wmap(encode, &map_wo, wo, D_, D_, 256);

    k1_ln_qkv<<<128, K1_THREADS, K1_SMEM, cudaStreamPerThread>>>(map_qkv, x, w_r);
    cudaLaunchAttribute at[1];
    at[0].id = cudaLaunchAttributeProgrammaticStreamSerialization;
    at[0].val.programmaticStreamSerializationAllowed = 1;
    cudaLaunchConfig_t cfg = {};
    cfg.stream = cudaStreamPerThread;
    cfg.attrs = at; cfg.numAttrs = 1;
    cfg.gridDim = dim3(132); cfg.blockDim = dim3(K2_THREADS); cfg.dynamicSmemBytes = K2_SMEM;
    cudaLaunchKernelEx(&cfg, k2_attn, x, w_gate, w_up, w_down);
    cfg.gridDim = dim3(128); cfg.blockDim = dim3(K3_THREADS); cfg.dynamicSmemBytes = K3_SMEM;
    cudaLaunchKernelEx(&cfg, k3_out, map_wo, x, out);
}
```

```cpp
#include <cuda_runtime.h>
#include <cuda_bf16.h>
#include <cuda.h>
#include <stdint.h>

namespace {

constexpr int S_ = 2048, D_ = 512, H_ = 32, F_ = 1792;

constexpr uint32_t PMASK = 0xA52;
__host__ __device__ constexpr bool is_poly_group(int g8) { return g8 >= 4 && ((PMASK >> ((g8 - 4) % 12)) & 1); }

__device__ __align__(1024) uint4 g_QKV[3 * H_ * S_ * 2];
#define g_Q (g_QKV)
#define g_K (g_QKV + H_ * S_ * 2)
#define g_V (g_QKV + 2 * H_ * S_ * 2)
__device__ __align__(1024) uint4 g_O[S_ * D_ / 8];
__device__ float2 g_stats[S_];
__device__ uint32_t g_const[4] = {421u, 0x459EB285u  , 0x3F800000u  , 0u};
__device__ float g_r[S_];
__device__ __align__(16) float g_ypart[4][2][D_];
__device__ int g_sel[2];

#define TL(k, p)
__device__ __forceinline__ uint32_t smem_u32(const void* p) { return (uint32_t)__cvta_generic_to_shared(p); }
__device__ __forceinline__ float bf16r(float x) { return __bfloat162float(__float2bfloat16_rn(x)); }
__device__ __forceinline__ uint32_t pack_bf16(float lo, float hi) {
    uint32_t r; asm("cvt.rn.bf16x2.f32 %0, %1, %2;" : "=r"(r) : "f"(hi), "f"(lo)); return r;
}
__device__ __forceinline__ float bf_lo(uint32_t u) { return __uint_as_float(u << 16); }
__device__ __forceinline__ float bf_hi(uint32_t u) { return __uint_as_float(u & 0xFFFF0000u); }
__device__ __forceinline__ float ex2(float x) { float y; asm("ex2.approx.ftz.f32 %0, %1;" : "=f"(y) : "f"(x)); return y; }

__device__ __forceinline__ void mbar_init(uint32_t bar, uint32_t count) {
    asm volatile("mbarrier.init.shared::cta.b64 [%0], %1;" :: "r"(bar), "r"(count) : "memory");
}
__device__ __forceinline__ void mbar_expect_tx(uint32_t bar, uint32_t bytes) {
    asm volatile("mbarrier.arrive.expect_tx.shared::cta.b64 _, [%0], %1;" :: "r"(bar), "r"(bytes) : "memory");
}
__device__ __forceinline__ void mbar_arrive(uint32_t bar) {
    asm volatile("mbarrier.arrive.shared::cta.b64 _, [%0];" :: "r"(bar) : "memory");
}
__device__ __forceinline__ void mbar_wait(uint32_t bar, uint32_t parity) {
    uint32_t done;
    #pragma unroll 1
    for (int it = 0; it < (1 << 26); it++) {
        asm volatile("{.reg .pred p; mbarrier.try_wait.parity.shared::cta.b64 p, [%1], %2; selp.u32 %0, 1, 0, p;}"
                     : "=r"(done) : "r"(bar), "r"(parity) : "memory");
        if (done) return;
    }
    __trap();
}
__device__ __forceinline__ void bulk_g2s(uint32_t dst, const void* src, uint32_t bytes, uint32_t bar) {
    asm volatile("cp.async.bulk.shared::cluster.global.mbarrier::complete_tx::bytes [%0], [%1], %2, [%3];"
                 :: "r"(dst), "l"(src), "r"(bytes), "r"(bar) : "memory");
}
__device__ __forceinline__ void tma_2d(uint32_t dst, const CUtensorMap* map, int c0, int c1, uint32_t bar) {
    asm volatile("cp.async.bulk.tensor.2d.shared::cluster.global.mbarrier::complete_tx::bytes [%0], [%1, {%3, %4}], [%2];"
                 :: "r"(dst), "l"(map), "r"(bar), "r"(c0), "r"(c1) : "memory");
}
__device__ __forceinline__ void fence_async_smem() { asm volatile("fence.proxy.async.shared::cta;" ::: "memory"); }
__device__ __forceinline__ void named_bar(int id, int n) { asm volatile("bar.sync %0, %1;" :: "r"(id), "r"(n) : "memory"); }

__device__ __forceinline__ uint64_t make_desc(uint32_t saddr, uint32_t lbo, uint32_t sbo, uint32_t swz) {
    return (uint64_t)((saddr & 0x3FFFF) >> 4) | ((uint64_t)(lbo >> 4) << 16) | ((uint64_t)(sbo >> 4) << 32) | ((uint64_t)swz << 62);
}
#define WG_FENCE() asm volatile("wgmma.fence.sync.aligned;" ::: "memory")
#define WG_COMMIT() asm volatile("wgmma.commit_group.sync.aligned;" ::: "memory")
template <int N> __device__ __forceinline__ void wg_wait() { asm volatile("wgmma.wait_group.sync.aligned %0;" :: "n"(N) : "memory"); }

#define F4(d, o) "+f"(d[o]), "+f"(d[o + 1]), "+f"(d[o + 2]), "+f"(d[o + 3])
#define F16(d, o) F4(d, o), F4(d, o + 4), F4(d, o + 8), F4(d, o + 12)
#define F32(d, o) F16(d, o), F16(d, o + 16)

__device__ __forceinline__ void wgmma_n192(float* d, uint64_t da, uint64_t db) {
    asm volatile("wgmma.mma_async.sync.aligned.m64n192k16.f32.bf16.bf16 "
        "{%0,%1,%2,%3,%4,%5,%6,%7,%8,%9,%10,%11,%12,%13,%14,%15,%16,%17,%18,%19,%20,%21,%22,%23,%24,%25,%26,%27,%28,%29,%30,%31,"
        "%32,%33,%34,%35,%36,%37,%38,%39,%40,%41,%42,%43,%44,%45,%46,%47,%48,%49,%50,%51,%52,%53,%54,%55,%56,%57,%58,%59,%60,%61,%62,%63,"
        "%64,%65,%66,%67,%68,%69,%70,%71,%72,%73,%74,%75,%76,%77,%78,%79,%80,%81,%82,%83,%84,%85,%86,%87,%88,%89,%90,%91,%92,%93,%94,%95}, "
        "%96, %97, 1, 1, 1, 0, 1;\n"
        : F32(d, 0), F32(d, 32), F32(d, 64) : "l"(da), "l"(db));
}
__device__ __forceinline__ void wgmma_n64(float* d, uint64_t da, uint64_t db) {
    asm volatile("wgmma.mma_async.sync.aligned.m64n64k16.f32.bf16.bf16 "
        "{%0,%1,%2,%3,%4,%5,%6,%7,%8,%9,%10,%11,%12,%13,%14,%15,%16,%17,%18,%19,%20,%21,%22,%23,%24,%25,%26,%27,%28,%29,%30,%31}, "
        "%32, %33, 1, 1, 1, 0, 1;\n"
        : F32(d, 0) : "l"(da), "l"(db));
}
__device__ __forceinline__ void wgmma_qk32(float* d, uint32_t qd, uint32_t kd) {
    asm volatile("{.reg .b64 a, b; mov.b64 a, {%16, 16}; mov.b64 b, {%17, 16};\n"
        "wgmma.mma_async.sync.aligned.m64n32k16.f32.bf16.bf16 {%0,%1,%2,%3,%4,%5,%6,%7,%8,%9,%10,%11,%12,%13,%14,%15}, a, b, 0, 1, 1, 0, 0;}\n"
        : F16(d, 0) : "r"(qd), "r"(kd));
}
__device__ __forceinline__ void wgmma_pv(float* d, const uint32_t* a, uint32_t vd) {
    asm volatile("{.reg .b64 b; mov.b64 b, {%16, 2048};\n"
        "wgmma.mma_async.sync.aligned.m64n24k16.f32.bf16.bf16 {%0,%1,%2,%3,%4,%5,%6,%7,%8,%9,%10,%11}, {%12,%13,%14,%15}, b, 1, 1, 1, 1;}\n"
        : F4(d, 0), F4(d, 4), F4(d, 8) : "r"(a[0]), "r"(a[1]), "r"(a[2]), "r"(a[3]), "r"(vd));
}
__device__ __forceinline__ void touch16(float* d) { asm volatile("" : F16(d, 0) :: "memory"); }
__device__ __forceinline__ void touch12(float* d) { asm volatile("" : F4(d, 0), F4(d, 4), F4(d, 8) :: "memory"); }
__device__ __forceinline__ void touch32(float* d) { asm volatile("" : F32(d, 0) :: "memory"); }
__device__ __forceinline__ void touch96(float* d) { asm volatile("" : F32(d, 0), F32(d, 32), F32(d, 64) :: "memory"); }

__device__ __forceinline__ float ln_elem(float x, float mean_b, float rden) {
    return bf16r(bf16r(x - mean_b) * rden);
}
__device__ __forceinline__ void pdl_wait() { asm volatile("griddepcontrol.wait;" ::: "memory"); }
__device__ __forceinline__ void pdl_launch() { asm volatile("griddepcontrol.launch_dependents;" ::: "memory"); }
__device__ __forceinline__ void cluster_arrive() { asm volatile("barrier.cluster.arrive.release.aligned;" ::: "memory"); }
__device__ __forceinline__ void cluster_wait() { asm volatile("barrier.cluster.wait.acquire.aligned;" ::: "memory"); }

constexpr int K1_THREADS = 288;
constexpr int K1_SMEM = 131072 + 4 * 24576 + 256;

__device__ __forceinline__ float reduce2(float a, float b, int lane) {
    const bool up = lane & 16;
    float r = (up ? b : a) + __shfl_xor_sync(~0u, up ? a : b, 16);
    #pragma unroll
    for (int o = 8; o; o >>= 1) r += __shfl_xor_sync(~0u, r, o);
    return r;
}

__device__ __forceinline__ void k1_epilogue(const float* acc, uint32_t stage, int nt, int mt, int wg, int w4, int lane, bool live) {
    const int g8a = mt * 16 + wg * 8 + w4 * 2;
    const uint32_t sx0 = is_poly_group(g8a) ? 0x80008000u : 0u, sx1 = is_poly_group(g8a + 1) ? 0x80008000u : 0u;
    const int mi = lane >> 3, lr = lane & 7;
    const uint32_t off_qk = stage + (w4 * 2 + (mi & 1)) * 256 + (mi >> 1) * 128 + lr * 16;
    const uint32_t off_v = stage + (mi >> 1) * 1024 + (w4 * 16 + (mi & 1) * 8 + lr) * 16;
    #pragma unroll
    for (int jj = 0; jj < 12; jj++) {
        const bool isv = nt * 12 + jj >= 64;
        const uint32_t x0 = isv ? sx0 : 0u, x1 = isv ? sx1 : 0u;
        const uint32_t r0 = pack_bf16(acc[8 * jj], acc[8 * jj + 1]) ^ x0, r1 = pack_bf16(acc[8 * jj + 2], acc[8 * jj + 3]) ^ x1;
        const uint32_t r2 = pack_bf16(acc[8 * jj + 4], acc[8 * jj + 5]) ^ x0, r3 = pack_bf16(acc[8 * jj + 6], acc[8 * jj + 7]) ^ x1;
        const uint32_t addr = (isv ? off_v : off_qk) + (jj >> 2) * 16384 + (jj & 3) * 2048;
        if (live) asm volatile("stmatrix.sync.aligned.m8n8.x4.shared.b16 [%0], {%1, %2, %3, %4};" :: "r"(addr), "r"(r0), "r"(r1), "r"(r2), "r"(r3) : "memory");
    }
    if (live) {
        fence_async_smem();
        named_bar(1 + wg, 128);
        const int pc = w4 * 6 + lane;
        if (lane < 6) {
            const int jj = pc >> 1, hf = pc & 1, hg = nt * 12 + jj;
            const unsigned char* dst = (const unsigned char*)g_QKV + (size_t)hg * 65536
                + (hg >= 64 ? hf * 32768 + (mt * 128 + wg * 64) * 16 : (mt * 16 + wg * 8) * 256 + hf * 1024);
            asm volatile("cp.async.bulk.global.shared::cta.bulk_group [%0], [%1], 1024;"
                         :: "l"(dst), "r"(stage + (jj >> 2) * 16384 + (jj & 3) * 2048 + hf * 1024) : "memory");
            asm volatile("cp.async.bulk.commit_group;" ::: "memory");
            asm volatile("cp.async.bulk.wait_group 0;" ::: "memory");
        }
    }
}

__global__ void __cluster_dims__(2, 1, 1) __launch_bounds__(K1_THREADS, 1)
k1_ln_qkv(const __grid_constant__ CUtensorMap wmap, const __nv_bfloat16* __restrict__ x, const __nv_bfloat16* __restrict__ w_r) {
    extern __shared__ __align__(1024) unsigned char smem[];
    const uint32_t sA = smem_u32(smem), sB = sA + 131072, sBar = sB + 4 * 24576;
    const int warp = __shfl_sync(~0u, threadIdx.x >> 5, 0), lane = threadIdx.x & 31;
    const int nt = blockIdx.x & 7, mt = blockIdx.x >> 3, rank = blockIdx.x & 1;
    const bool producer = warp == 8;
    const int wg = (warp >> 2) & 1;
    TL(0, 0);
    pdl_launch();
    float acc[96];
    #pragma unroll
    for (int i = 0; i < 96; i++) acc[i] = 0.f;
    if (producer) {
        if (lane == 0) {
            for (int i = 0; i < 4; i++) { mbar_init(sBar + i * 8, 1); mbar_init(sBar + 32 + i * 8, 2); }
            asm volatile("fence.mbarrier_init.release.cluster;" ::: "memory");
            for (int kc = 0; kc < 4; kc++) {
                mbar_expect_tx(sBar + kc * 8, 24576);
                for (int j = 0; j < 3; j++) tma_2d(sB + kc * 24576 + j * 8192, &wmap, nt * 192 + j * 64, kc * 64, sBar + kc * 8);
            }
        }
        __syncwarp();
        cluster_arrive();
        cluster_wait();
        cluster_arrive();
        cluster_wait();
        if (lane == 0) {
            for (int kc = 4; kc < 8; kc++) {
                const int st = kc & 3;
                mbar_wait(sBar + 32 + st * 8, 0);
                mbar_expect_tx(sBar + st * 8, 24576);
                for (int j = 0; j < 3; j++) tma_2d(sB + st * 24576 + j * 8192, &wmap, nt * 192 + j * 64, kc * 64, sBar + st * 8);
            }
        }
        __syncwarp();
    } else {
        const int rbase = rank * 64 + warp * 8;
        uint32_t u[10][8];
        #pragma unroll
        for (int j = 0; j < 8; j++) { u[0][j] = 0; u[1][j] = 0; }
        #pragma unroll
        for (int i = 0; i < 8; i++) {
            const __nv_bfloat16* xp = x + (size_t)(mt * 128 + rbase + i) * D_;
            const uint4 a = __ldg((const uint4*)(xp + lane * 8)), b = __ldg((const uint4*)(xp + 256 + lane * 8));
            u[i + 2][0] = a.x; u[i + 2][1] = a.y; u[i + 2][2] = a.z; u[i + 2][3] = a.w;
            u[i + 2][4] = b.x; u[i + 2][5] = b.y; u[i + 2][6] = b.z; u[i + 2][7] = b.w;
        }
        const uint4 wr0 = __ldg((const uint4*)(w_r + lane * 8)), wr1 = __ldg((const uint4*)(w_r + 256 + lane * 8));
        asm volatile("barrier.cluster.arrive.relaxed.aligned;" ::: "memory");
        uint32_t peerA;
        asm volatile("mapa.shared::cluster.u32 %0, %1, %2;" : "=r"(peerA) : "r"(sA), "r"(rank ^ 1));
        TL(0, 1);
        #pragma unroll 1
        for (int it = -1; it < 4; it++) {
            float p[2];
            #pragma unroll
            for (int i = 0; i < 2; i++) {
                float s0 = 0.f, s1 = 0.f;
                #pragma unroll
                for (int j = 0; j < 8; j++) { s0 += bf_lo(u[i][j]); s1 += bf_hi(u[i][j]); }
                p[i] = s0 + s1;
            }
            const float mean_l = reduce2(p[0], p[1], lane) * (1.0f / D_);
            #pragma unroll
            for (int i = 0; i < 2; i++) {
                const float mean = __shfl_sync(~0u, mean_l, i * 16);
                float q0 = 0.f, q1 = 0.f;
                #pragma unroll
                for (int j = 0; j < 8; j++) {
                    const float d0 = bf_lo(u[i][j]) - mean, d1 = bf_hi(u[i][j]) - mean;
                    q0 = fmaf(d0, d0, q0); q1 = fmaf(d1, d1, q1);
                }
                p[i] = q0 + q1;
            }
            const float var_b = bf16r(reduce2(p[0], p[1], lane) * (1.0f / D_));
            const float rden_l = __frcp_rn(bf16r(__fsqrt_rn(bf16r(var_b + 1e-5f))));
            const uint32_t mean2_l = pack_bf16(mean_l, mean_l);
            const uint32_t w[8] = {wr0.x, wr0.y, wr0.z, wr0.w, wr1.x, wr1.y, wr1.z, wr1.w};
            #pragma unroll
            for (int i = 0; i < 2; i++) {
                const int r = rbase + it * 2 + i;
                const uint32_t m2 = __shfl_sync(~0u, mean2_l, i * 16);
                const float rden = __shfl_sync(~0u, rden_l, i * 16);
                float a0 = 0.f, a1 = 0.f;
                #pragma unroll
                for (int j = 0; j < 8; j++) {
                    uint32_t d2;
                    asm("sub.rn.bf16x2 %0, %1, %2;" : "=r"(d2) : "r"(u[i][j]), "r"(m2));
                    u[i][j] = pack_bf16(bf_lo(d2) * rden, bf_hi(d2) * rden);
                }
                if (it >= 0) {
                    const uint32_t off = (lane >> 3) * 16384 + r * 128 + (((lane & 7) ^ (r & 7)) * 16);
                    *(uint4*)(smem + off) = make_uint4(u[i][0], u[i][1], u[i][2], u[i][3]);
                    *(uint4*)(smem + off + 65536) = make_uint4(u[i][4], u[i][5], u[i][6], u[i][7]);
                    asm volatile("st.shared::cluster.v4.b32 [%0], {%1, %2, %3, %4};" :: "r"(peerA + off), "r"(u[i][0]), "r"(u[i][1]), "r"(u[i][2]), "r"(u[i][3]) : "memory");
                    asm volatile("st.shared::cluster.v4.b32 [%0], {%1, %2, %3, %4};" :: "r"(peerA + off + 65536), "r"(u[i][4]), "r"(u[i][5]), "r"(u[i][6]), "r"(u[i][7]) : "memory");
                }
                if (nt < 2) {
                    #pragma unroll
                    for (int j = 0; j < 8; j++) { a0 = fmaf(bf_lo(u[i][j]), bf_lo(w[j]), a0); a1 = fmaf(bf_hi(u[i][j]), bf_hi(w[j]), a1); }
                }
                p[i] = a0 + a1;
            }
            if (nt < 2) {
                const float rl = reduce2(p[0], p[1], lane);
                if ((lane & 15) == 0 && it >= 0) {
                    const int row = mt * 128 + rbase + it * 2 + (lane >> 4);
                    g_r[row] = bf16r(rl);
                    g_stats[row] = make_float2(bf_lo(mean2_l), rden_l);
                }
            }
            #pragma unroll
            for (int i = 0; i < 8; i++)
                #pragma unroll
                for (int j = 0; j < 8; j++) u[i][j] = u[i + 2][j];
            if (it < 0) cluster_wait();
        }
        TL(0, 2);
        asm volatile("fence.proxy.async;" ::: "memory");
        cluster_arrive();
        cluster_wait();
        asm volatile("fence.proxy.async;" ::: "memory");
        TL(0, 3);
        const uint64_t da0 = make_desc(sA + wg * 8192, 16, 1024, 1);
        const uint64_t db0 = make_desc(sB, 8192, 1024, 1);
        #pragma unroll 1
        for (int kc = 0; kc < 8; kc++) {
            const int st = kc & 3;
            mbar_wait(sBar + st * 8, kc >> 2);
            WG_FENCE();
            #pragma unroll
            for (int kk = 0; kk < 4; kk++)
                wgmma_n192(acc, da0 + (uint64_t)(kc * 1024 + kk * 2), db0 + (uint64_t)(st * 1536 + kk * 128));
            WG_COMMIT();
            wg_wait<1>();
            if (kc >= 1 && kc <= 4 && (threadIdx.x & 127) == 0) mbar_arrive(sBar + 32 + (kc - 1) * 8);
        }
        wg_wait<0>();
        touch96(acc);
        named_bar(1 + wg, 128);
        TL(0, 5);
    }
    k1_epilogue(acc, sA + wg * 8192, nt, mt, wg, warp & 3, lane, !producer);
    TL(0, 6);
}

constexpr int K2_THREADS = 512;
constexpr int K2_SMEM = 65536 + 98304 + 16384 + 128;

constexpr float QS = 0.25f * 1.4426950408889634f;
__device__ __forceinline__ uint32_t polyexp(float s, float cb, uint32_t c421, float c3, float one) {
    float u;
    asm("fma.rn.sat.f32 %0, %1, %2, %3;" : "=f"(u) : "f"(s), "f"(QS * (1.0f / 255.0f)), "f"(cb));
    float z = fmaf(u, 0.99609375f, one);
    uint32_t rb;
    asm("lop3.b32 %0, %1, 0xFFFF8000, %2, 0xEA;" : "=r"(rb) : "r"(__float_as_uint(z)), "r"(c421));
    float f = z - __uint_as_float(rb);
    float h = fmaf(f, c3, 58.86525f);
    h = fmaf(f, h, -0.29870507f);
    return __float_as_uint(fmaf(f, h, z));
}

struct ExpC { float nm0, nm1, cb0, cb1, c3, one; uint32_t c421; };

template <int G>
__device__ __forceinline__ void exp_block(const float* s, uint32_t* p, const ExpC& c) {
    #pragma unroll
    for (int hf = 0; hf < 2; hf++) {
        const float* x = s + hf * 4;
        if ((PMASK >> (G + hf)) & 1) {
            p[hf * 2 + 0] = __byte_perm(polyexp(x[0], c.cb0, c.c421, c.c3, c.one), polyexp(x[1], c.cb0, c.c421, c.c3, c.one), 0x6521);
            p[hf * 2 + 1] = __byte_perm(polyexp(x[2], c.cb1, c.c421, c.c3, c.one), polyexp(x[3], c.cb1, c.c421, c.c3, c.one), 0x6521);
        } else {
            p[hf * 2 + 0] = pack_bf16(ex2(fmaf(x[0], QS, c.nm0)), ex2(fmaf(x[1], QS, c.nm0)));
            p[hf * 2 + 1] = pack_bf16(ex2(fmaf(x[2], QS, c.nm1)), ex2(fmaf(x[3], QS, c.nm1)));
        }
    }
}

__device__ __forceinline__ void max16(const float* s, float& mx0, float& mx1) {
    #pragma unroll
    for (int j = 0; j < 4; j++) {
        mx0 = fmaxf(mx0, fmaxf(s[4 * j], s[4 * j + 1]));
        mx1 = fmaxf(mx1, fmaxf(s[4 * j + 2], s[4 * j + 3]));
    }
}

__device__ void moe_cta(int part, unsigned char* smem, const __nv_bfloat16* __restrict__ x, const __nv_bfloat16* __restrict__ w_gate,
                        const __nv_bfloat16* __restrict__ w_up, const __nv_bfloat16* __restrict__ w_down) {
    float* xs = (float*)smem;
    float* red = xs + 1024;
    float* hs = red + 8 * 4 * 448;
    __shared__ float s_v[32];
    __shared__ int s_i[32];
    __shared__ int s_sel[2];
    const int tid = threadIdx.x, warp = tid >> 5, lane = tid & 31;
    for (int pass = 0; pass < 2; pass++) {
        float bv = -INFINITY; int bi = 0x7fffffff;
        const int excl = pass ? s_sel[0] : -1;
        for (int i = tid; i < S_; i += K2_THREADS) {
            float v = g_r[i];
            if (i != excl && (v > bv || (v == bv && i < bi) || bi == 0x7fffffff)) { bv = v; bi = i; }
        }
        #pragma unroll
        for (int o = 16; o; o >>= 1) {
            float ov = __shfl_xor_sync(~0u, bv, o); int oi = __shfl_xor_sync(~0u, bi, o);
            if (ov > bv || (ov == bv && oi < bi)) { bv = ov; bi = oi; }
        }
        if (lane == 0) { s_v[warp] = bv; s_i[warp] = bi; }
        __syncthreads();
        if (warp == 0) {
            bv = lane < 16 ? s_v[lane] : -INFINITY; bi = lane < 16 ? s_i[lane] : 0x7fffffff;
            #pragma unroll
            for (int o = 16; o; o >>= 1) {
                float ov = __shfl_xor_sync(~0u, bv, o); int oi = __shfl_xor_sync(~0u, bi, o);
                if (ov > bv || (ov == bv && oi < bi)) { bv = ov; bi = oi; }
            }
            if (lane == 0) s_sel[pass] = (bi == 0x7fffffff) ? pass : bi;
        }
        __syncthreads();
    }
    for (int i = tid; i < 1024; i += K2_THREADS) {
        const int tok = s_sel[i >> 9];
        const float2 st = g_stats[tok];
        xs[i] = ln_elem(__bfloat162float(x[(size_t)tok * D_ + (i & 511)]), st.x, st.y);
    }
    if (part == 0 && tid < 2) g_sel[tid] = s_sel[tid];
    __syncthreads();
    const int c0 = part * 448;
    if (tid < 448) {
        const int cg = tid % 56, ks = tid / 56;
        float a[4][8];
        #pragma unroll
        for (int i = 0; i < 4; i++)
            #pragma unroll
            for (int j = 0; j < 8; j++) a[i][j] = 0.f;
        const __nv_bfloat16* pg = w_gate + (size_t)(ks * 64) * F_ + c0 + cg * 8;
        const __nv_bfloat16* pu = w_up + (size_t)(ks * 64) * F_ + c0 + cg * 8;
        #pragma unroll 8
        for (int k = 0; k < 64; k++) {
            const uint4 gv = __ldg((const uint4*)(pg + (size_t)k * F_));
            const uint4 uv = __ldg((const uint4*)(pu + (size_t)k * F_));
            const float x0 = xs[ks * 64 + k], x1 = xs[512 + ks * 64 + k];
            const uint32_t gu[4] = {gv.x, gv.y, gv.z, gv.w}, uu[4] = {uv.x, uv.y, uv.z, uv.w};
            #pragma unroll
            for (int j = 0; j < 4; j++) {
                const float g0 = bf_lo(gu[j]), g1 = bf_hi(gu[j]), u0 = bf_lo(uu[j]), u1 = bf_hi(uu[j]);
                a[0][2 * j] = fmaf(x0, g0, a[0][2 * j]); a[0][2 * j + 1] = fmaf(x0, g1, a[0][2 * j + 1]);
                a[1][2 * j] = fmaf(x1, g0, a[1][2 * j]); a[1][2 * j + 1] = fmaf(x1, g1, a[1][2 * j + 1]);
                a[2][2 * j] = fmaf(x0, u0, a[2][2 * j]); a[2][2 * j + 1] = fmaf(x0, u1, a[2][2 * j + 1]);
                a[3][2 * j] = fmaf(x1, u0, a[3][2 * j]); a[3][2 * j + 1] = fmaf(x1, u1, a[3][2 * j + 1]);
            }
        }
        #pragma unroll
        for (int i = 0; i < 4; i++)
            #pragma unroll
            for (int j = 0; j < 8; j++) red[(ks * 4 + i) * 448 + cg * 8 + j] = a[i][j];
    }
    __syncthreads();
    for (int i = tid; i < 896; i += K2_THREADS) {
        const int tok = i / 448, c = i % 448;
        float gs = 0.f, us = 0.f;
        #pragma unroll
        for (int ks = 0; ks < 8; ks++) { gs += red[(ks * 4 + tok) * 448 + c]; us += red[(ks * 4 + 2 + tok) * 448 + c]; }
        gs = bf16r(gs); us = bf16r(us);
        const float sl = bf16r(gs / (1.0f + __expf(-gs)));
        hs[i] = bf16r(sl * us);
    }
    __syncthreads();
    {
        const int cg = tid & 63, fs = tid >> 6;
        float a[2][8];
        #pragma unroll
        for (int j = 0; j < 8; j++) { a[0][j] = 0.f; a[1][j] = 0.f; }
        const __nv_bfloat16* pd = w_down + (size_t)(c0 + fs * 56) * D_ + cg * 8;
        #pragma unroll 8
        for (int f = 0; f < 56; f++) {
            const uint4 dv = __ldg((const uint4*)(pd + (size_t)f * D_));
            const float h0 = hs[fs * 56 + f], h1 = hs[448 + fs * 56 + f];
            const uint32_t du[4] = {dv.x, dv.y, dv.z, dv.w};
            #pragma unroll
            for (int j = 0; j < 4; j++) {
                const float d0 = bf_lo(du[j]), d1 = bf_hi(du[j]);
                a[0][2 * j] = fmaf(h0, d0, a[0][2 * j]); a[0][2 * j + 1] = fmaf(h0, d1, a[0][2 * j + 1]);
                a[1][2 * j] = fmaf(h1, d0, a[1][2 * j]); a[1][2 * j + 1] = fmaf(h1, d1, a[1][2 * j + 1]);
            }
        }
        #pragma unroll
        for (int j = 0; j < 8; j++) { red[(fs * 2) * 512 + cg * 8 + j] = a[0][j]; red[(fs * 2 + 1) * 512 + cg * 8 + j] = a[1][j]; }
    }
    __syncthreads();
    for (int i = tid; i < 1024; i += K2_THREADS) {
        float s = 0.f;
        #pragma unroll
        for (int fs = 0; fs < 8; fs++) s += red[(fs * 2 + (i >> 9)) * 512 + (i & 511)];
        g_ypart[part][i >> 9][i & 511] = s;
    }
}

__global__ void __launch_bounds__(K2_THREADS, 1)
k2_attn(const __nv_bfloat16* __restrict__ x, const __nv_bfloat16* __restrict__ w_gate, const __nv_bfloat16* __restrict__ w_up,
        const __nv_bfloat16* __restrict__ w_down) {
    extern __shared__ __align__(1024) unsigned char smem[];
    TL(1, 0);
    pdl_launch();
    if (blockIdx.x >= 128) {
        const int part = blockIdx.x - 128;
        {
            const int k = threadIdx.x;
            asm volatile("cp.async.bulk.prefetch.L2.global [%0], %1;" :: "l"(w_gate + (size_t)k * F_ + part * 448), "r"(896) : "memory");
            asm volatile("cp.async.bulk.prefetch.L2.global [%0], %1;" :: "l"(w_up + (size_t)k * F_ + part * 448), "r"(896) : "memory");
            if (k < 56) asm volatile("cp.async.bulk.prefetch.L2.global [%0], %1;" :: "l"(w_down + (size_t)(part * 448 + k * 8) * D_), "r"(8192) : "memory");
        }
        pdl_wait(); TL(1, 1); moe_cta(blockIdx.x - 128, smem, x, w_gate, w_up, w_down); TL(1, 2); return; }
    const uint32_t sK = smem_u32(smem), sV = sK + 65536, sQ = sV + 98304, sBar = sQ + 16384;
    const int h = blockIdx.x >> 2, qb = blockIdx.x & 3;
    const int warp = __shfl_sync(~0u, threadIdx.x >> 5, 0), lane = threadIdx.x & 31, wg = warp >> 2;
    if (threadIdx.x == 0) {
        mbar_init(sBar, 1); mbar_init(sBar + 8, 1);
        asm volatile("fence.mbarrier_init.release.cluster;" ::: "memory");
        pdl_wait();
        TL(1, 1);
        const uint4* gk = g_K + (size_t)h * 4096;
        const uint4* gv = g_V + (size_t)h * 4096;
        mbar_expect_tx(sBar, 16384 + 16384 + 2 * 8192);
        bulk_g2s(sQ, g_Q + (size_t)h * 4096 + qb * 1024, 16384, sBar);
        bulk_g2s(sK, gk, 16384, sBar);
        bulk_g2s(sV, gv, 8192, sBar);
        bulk_g2s(sV + 32768, gv + 2048, 8192, sBar);
        mbar_expect_tx(sBar + 8, 49152 + 2 * 24576);
        bulk_g2s(sK + 16384, gk + 1024, 49152, sBar + 8);
        bulk_g2s(sV + 8192, gv + 512, 24576, sBar + 8);
        bulk_g2s(sV + 32768 + 8192, gv + 2048 + 512, 24576, sBar + 8);
    }
    for (int i = threadIdx.x; i < 2048; i += K2_THREADS) {
        const uint32_t v = is_poly_group(i >> 3) ? 0xBF80BF80u : 0x3F803F80u;
        *(uint4*)(smem + 65536 + 65536 + i * 16) = make_uint4(v, v, v, v);
    }
    fence_async_smem();
    __syncthreads();
    ExpC c;
    {
        const volatile uint32_t* cc = g_const;
        c.c421 = cc[0]; c.c3 = __uint_as_float(cc[1]); c.one = __uint_as_float(cc[2]);
    }
    const uint32_t kdesc0 = (uint32_t)make_desc(sK, 128, 256, 0);
    const uint32_t vdesc0 = (uint32_t)make_desc(sV, 128, 32768, 0);
    mbar_wait(sBar, 0);
    TL(1, 2);
    #pragma unroll 1
    for (int pass = 0; pass < 2; pass++) {
        const int unit = pass * 4 + wg;
        const uint32_t q = (uint32_t)make_desc(sQ + unit * 2048, 128, 256, 0);
        float o[12];
        #pragma unroll 1
        for (int attempt = 0; attempt < 2; attempt++) {
            float s0[16], s1[16], s2[16];
            #pragma unroll
            for (int i = 0; i < 16; i++) { s0[i] = 0.f; s1[i] = 0.f; s2[i] = 0.f; }
            float mx0 = -INFINITY, mx1 = -INFINITY;
            if (attempt) {
                #pragma unroll 1
                for (int it = 0; it < 64; it++) {
                    WG_FENCE();
                    wgmma_qk32(s0, q, kdesc0 + it * 64);
                    WG_COMMIT();
                    wg_wait<0>();
                    touch16(s0);
                    max16(s0, mx0, mx1);
                }
            }
            #pragma unroll
            for (int i = 0; i < 12; i++) o[i] = 0.f;
            WG_FENCE();
            wgmma_qk32(s2, q, kdesc0);
            wgmma_qk32(s0, q, kdesc0 + 64);
            wgmma_qk32(s1, q, kdesc0 + 128);
            WG_COMMIT();
            wg_wait<0>();
            touch16(s0); touch16(s1); touch16(s2);
            max16(s0, mx0, mx1); max16(s1, mx0, mx1); max16(s2, mx0, mx1);
            mx0 = fmaxf(mx0, __shfl_xor_sync(~0u, mx0, 1)); mx0 = fmaxf(mx0, __shfl_xor_sync(~0u, mx0, 2));
            mx1 = fmaxf(mx1, __shfl_xor_sync(~0u, mx1, 1)); mx1 = fmaxf(mx1, __shfl_xor_sync(~0u, mx1, 2));
            const float bias = attempt ? 0.0f : 64.0f;
            c.nm0 = __shfl_sync(~0u, -fmaf(mx0, QS, bias), lane); c.nm1 = __shfl_sync(~0u, -fmaf(mx1, QS, bias), lane);
            c.cb0 = __shfl_sync(~0u, (127.0f + c.nm0) * (1.0f / 255.0f), lane);
            c.cb1 = __shfl_sync(~0u, (127.0f + c.nm1) * (1.0f / 255.0f), lane);
            uint32_t kd = kdesc0 + 192, vd = vdesc0 + 32;
            {
                uint32_t pa[4], pb[4];
                exp_block<12>(s2, pa, c);
                exp_block<14>(s2 + 8, pb, c);
                WG_FENCE();
                wgmma_pv(o, pa, vdesc0); wgmma_pv(o, pb, vdesc0 + 16);
                WG_COMMIT();
            }
            #pragma unroll 1
            for (int seg = 0; seg < 2; seg++) {
            if (seg) { wg_wait<0>(); mbar_wait(sBar + 8, 0); __syncwarp(); }
            #pragma unroll 1
            for (int it = seg ? 3 : 0; it < (seg ? 21 : 3); it++) {
                uint32_t p[6][4];
                WG_FENCE();
                wgmma_qk32(s2, q, kd);
                WG_COMMIT();
                exp_block<0>(s0, p[0], c);
                exp_block<2>(s0 + 8, p[1], c);
                WG_FENCE();
                wgmma_pv(o, p[0], vd); wgmma_pv(o, p[1], vd + 16);
                wgmma_qk32(s0, q, kd + 64);
                WG_COMMIT();
                wg_wait<1>();
                touch16(s2);
                exp_block<4>(s1, p[2], c);
                exp_block<6>(s1 + 8, p[3], c);
                WG_FENCE();
                wgmma_pv(o, p[2], vd + 32); wgmma_pv(o, p[3], vd + 48);
                wgmma_qk32(s1, q, kd + 128);
                WG_COMMIT();
                wg_wait<1>();
                touch16(s0);
                exp_block<8>(s2, p[4], c);
                exp_block<10>(s2 + 8, p[5], c);
                WG_FENCE();
                wgmma_pv(o, p[4], vd + 64); wgmma_pv(o, p[5], vd + 80);
                WG_COMMIT();
                vd += 96; kd += 192;
                wg_wait<1>();
                touch16(s1);
            }
            }
            wg_wait<0>();
            touch12(o);
            if (attempt) break;
            float big = 0.f;
            #pragma unroll
            for (int i = 0; i < 12; i++) big = fmaxf(big, fabsf(o[i]));
            bool bad = !(big < 1e30f);
            #pragma unroll
            for (int i = 0; i < 12; i++) bad |= (o[i] != o[i]);
            uint32_t any;
            asm volatile("{.reg .pred p, q; setp.ne.u32 p, %1, 0; barrier.cta.red.or.pred.aligned q, %2, 128, p; selp.u32 %0, 1, 0, q;}"
                         : "=r"(any) : "r"((uint32_t)bad), "r"(1 + wg) : "memory");
            if (!__any_sync(~0u, any)) break;
        }
        const int g = lane >> 2, t = lane & 3;
        const int r = (warp & 3) * 16 + g;
        const float i0 = __fdiv_rn(1.0f, o[8]), i1 = __fdiv_rn(1.0f, o[10]);
        uint32_t* ob = (uint32_t*)(g_O + (size_t)(qb * 8 + unit) * 4096 + (h >> 2) * 512 + r * 8) + t;
        const int c0 = ((h & 3) * 2) ^ (r & 7), c1 = ((h & 3) * 2 + 1) ^ (r & 7);
        ob[c0 * 4] = pack_bf16(o[0] * i0, o[1] * i0);
        ob[c1 * 4] = pack_bf16(o[4] * i0, o[5] * i0);
        ob[256 + c0 * 4] = pack_bf16(o[2] * i1, o[3] * i1);
        ob[256 + c1 * 4] = pack_bf16(o[6] * i1, o[7] * i1);
        TL(1, 3 + pass);
    }
}

constexpr int K3_THREADS = 256;
constexpr int K3_SMEM = 65536 + 131072 + 128;

__global__ void __launch_bounds__(K3_THREADS, 1)
k3_out(const __grid_constant__ CUtensorMap wmap, const __nv_bfloat16* __restrict__ x, __nv_bfloat16* __restrict__ out) {
    extern __shared__ __align__(1024) unsigned char smem[];
    const uint32_t sA = smem_u32(smem), sB = sA + 65536, sBar = sB + 131072;
    const int warp = __shfl_sync(~0u, threadIdx.x >> 5, 0), lane = threadIdx.x & 31, wg = warp >> 2;
    const int nt = blockIdx.x & 3, mt = blockIdx.x >> 2;
    TL(2, 0);
    if (threadIdx.x == 0) {
        for (int i = 0; i < 6; i++) mbar_init(sBar + i * 8, 1);
        asm volatile("fence.mbarrier_init.release.cluster;" ::: "memory");
        for (int kh = 0; kh < 2; kh++) {
            mbar_expect_tx(sBar + kh * 8, 65536);
            tma_2d(sB + kh * 32768, &wmap, nt * 128, kh * 256, sBar + kh * 8);
            tma_2d(sB + 65536 + kh * 32768, &wmap, nt * 128 + 64, kh * 256, sBar + kh * 8);
        }
    }
    const int er = threadIdx.x >> 2, ec = (threadIdx.x & 3) * 32;
    const int row = mt * 64 + er;
    uint4 xv[4];
    #pragma unroll
    for (int j = 0; j < 4; j++) xv[j] = __ldg((const uint4*)(x + (size_t)row * D_ + nt * 128 + ec) + j);
    pdl_wait();
    TL(2, 1);
    if (threadIdx.x == 0) {
        for (int q = 0; q < 4; q++) {
            mbar_expect_tx(sBar + 16 + q * 8, 16384);
            bulk_g2s(sA + q * 16384, g_O + (size_t)mt * 4096 + q * 1024, 16384, sBar + 16 + q * 8);
        }
    }
    const int sel0 = g_sel[0], sel1 = g_sel[1];
    const float2 st = g_stats[row];
    uint32_t bb[16];
    {
        const uint32_t xu[16] = {xv[0].x, xv[0].y, xv[0].z, xv[0].w, xv[1].x, xv[1].y, xv[1].z, xv[1].w,
                                 xv[2].x, xv[2].y, xv[2].z, xv[2].w, xv[3].x, xv[3].y, xv[3].z, xv[3].w};
        #pragma unroll
        for (int j = 0; j < 16; j++) bb[j] = pack_bf16(bf16r(bf_lo(xu[j]) - st.x) * st.y, bf16r(bf_hi(xu[j]) - st.x) * st.y);
        const int slot = row == sel0 ? 0 : (row == sel1 ? 1 : -1);
        if (slot >= 0) {
            const float gate = bf16r(1.0f / (1.0f + __expf(-g_r[row])));
            const int c0 = nt * 128 + ec;
            #pragma unroll
            for (int j = 0; j < 16; j++) {
                const float2 a = *(const float2*)&g_ypart[0][slot][c0 + 2 * j], b = *(const float2*)&g_ypart[1][slot][c0 + 2 * j];
                const float2 c = *(const float2*)&g_ypart[2][slot][c0 + 2 * j], d = *(const float2*)&g_ypart[3][slot][c0 + 2 * j];
                bb[j] = pack_bf16(bf_lo(bb[j]) + bf16r(bf16r(a.x + b.x + c.x + d.x) * gate), bf_hi(bb[j]) + bf16r(bf16r(a.y + b.y + c.y + d.y) * gate));
            }
        }
    }
    __syncthreads();
    float acc[32];
    #pragma unroll
    for (int i = 0; i < 32; i++) acc[i] = 0.f;
    const uint64_t da0 = make_desc(sA, 16, 1024, 1);
    const uint64_t db0 = make_desc(sB + wg * 65536, 8192, 1024, 1);
    #pragma unroll 1
    for (int q = 0; q < 4; q++) {
        if ((q & 1) == 0) mbar_wait(sBar + (q >> 1) * 8, 0);
        mbar_wait(sBar + 16 + q * 8, 0);
        WG_FENCE();
        #pragma unroll
        for (int kk = 0; kk < 8; kk++)
            wgmma_n64(acc, da0 + (uint64_t)(q * 1024 + (kk >> 2) * 512 + (kk & 3) * 2), db0 + (uint64_t)(q * 1024 + kk * 128));
        WG_COMMIT();
    }
    wg_wait<0>();
    touch32(acc);
    TL(2, 2);
    __syncthreads();
    {
        const int g = lane >> 2, t = lane & 3;
        unsigned char* sp = smem + ((warp & 3) * 16 + g) * 272 + wg * 128 + t * 4;
        #pragma unroll
        for (int j = 0; j < 8; j++) {
            *(uint32_t*)(sp + j * 16) = pack_bf16(acc[4 * j], acc[4 * j + 1]);
            *(uint32_t*)(sp + 8 * 272 + j * 16) = pack_bf16(acc[4 * j + 2], acc[4 * j + 3]);
        }
    }
    __syncthreads();
    #pragma unroll
    for (int j = 0; j < 4; j++) {
        const uint4 av = *(const uint4*)(smem + er * 272 + ec * 2 + j * 16);
        const uint32_t au[4] = {av.x, av.y, av.z, av.w}, xu[4] = {xv[j].x, xv[j].y, xv[j].z, xv[j].w};
        uint32_t o[4];
        #pragma unroll
        for (int i = 0; i < 4; i++) {
            uint32_t t2;
            asm("add.rn.bf16x2 %0, %1, %2;" : "=r"(t2) : "r"(xu[i]), "r"(au[i]));
            asm("add.rn.bf16x2 %0, %1, %2;" : "=r"(o[i]) : "r"(t2), "r"(bb[j * 4 + i]));
        }
        *((uint4*)(out + (size_t)row * D_ + nt * 128 + ec) + j) = make_uint4(o[0], o[1], o[2], o[3]);
    }
    TL(2, 3);
}

typedef CUresult (*EncodeFn)(CUtensorMap*, CUtensorMapDataType, cuuint32_t, void*, const cuuint64_t*, const cuuint64_t*,
                             const cuuint32_t*, const cuuint32_t*, CUtensorMapInterleave, CUtensorMapSwizzle,
                             CUtensorMapL2promotion, CUtensorMapFloatOOBfill);

void make_wmap(EncodeFn fn, CUtensorMap* map, const void* ptr, int rows, int cols, int box_rows) {
    cuuint64_t dims[2] = {(cuuint64_t)cols, (cuuint64_t)rows};
    cuuint64_t strides[1] = {(cuuint64_t)cols * 2};
    cuuint32_t box[2] = {64, (cuuint32_t)box_rows};
    cuuint32_t es[2] = {1, 1};
    fn(map, CU_TENSOR_MAP_DATA_TYPE_BFLOAT16, 2, (void*)ptr, dims, strides, box, es, CU_TENSOR_MAP_INTERLEAVE_NONE,
       CU_TENSOR_MAP_SWIZZLE_128B, CU_TENSOR_MAP_L2_PROMOTION_L2_256B, CU_TENSOR_MAP_FLOAT_OOB_FILL_NONE);
}

}

extern "C" void kernel_launch(void* const* d_in, const int* in_sizes, int n_in, void* d_out, int out_size) {
    const __nv_bfloat16* x = (const __nv_bfloat16*)d_in[0];
    const __nv_bfloat16* wqkv = (const __nv_bfloat16*)d_in[1];
    const __nv_bfloat16* wo = (const __nv_bfloat16*)d_in[2];
    const __nv_bfloat16* w_r = (const __nv_bfloat16*)d_in[4];
    const __nv_bfloat16* w_gate = (const __nv_bfloat16*)d_in[5];
    const __nv_bfloat16* w_up = (const __nv_bfloat16*)d_in[6];
    const __nv_bfloat16* w_down = (const __nv_bfloat16*)d_in[7];
    __nv_bfloat16* out = (__nv_bfloat16*)d_out;

    static EncodeFn encode = nullptr;
    if (!encode) {
        void* fn = nullptr;
        cudaDriverEntryPointQueryResult qres;
        cudaGetDriverEntryPoint("cuTensorMapEncodeTiled", &fn, cudaEnableDefault, &qres);
        encode = (EncodeFn)fn;
        cudaFuncSetAttribute(k1_ln_qkv, cudaFuncAttributeMaxDynamicSharedMemorySize, K1_SMEM);
        cudaFuncSetAttribute(k2_attn, cudaFuncAttributeMaxDynamicSharedMemorySize, K2_SMEM);
        cudaFuncSetAttribute(k3_out, cudaFuncAttributeMaxDynamicSharedMemorySize, K3_SMEM);
    }
    CUtensorMap map_qkv, map_wo;
    make_wmap(encode, &map_qkv, wqkv, D_, 3 * D_, 64);
    make_wmap(encode, &map_wo, wo, D_, D_, 256);

    k1_ln_qkv<<<128, K1_THREADS, K1_SMEM, cudaStreamPerThread>>>(map_qkv, x, w_r);
    cudaLaunchAttribute at[1];
    at[0].id = cudaLaunchAttributeProgrammaticStreamSerialization;
    at[0].val.programmaticStreamSerializationAllowed = 1;
    cudaLaunchConfig_t cfg = {};
    cfg.stream = cudaStreamPerThread;
    cfg.attrs = at; cfg.numAttrs = 1;
    cfg.gridDim = dim3(132); cfg.blockDim = dim3(K2_THREADS); cfg.dynamicSmemBytes = K2_SMEM;
    cudaLaunchKernelEx(&cfg, k2_attn, x, w_gate, w_up, w_down);
    cfg.gridDim = dim3(128); cfg.blockDim = dim3(K3_THREADS); cfg.dynamicSmemBytes = K3_SMEM;
    cudaLaunchKernelEx(&cfg, k3_out, map_wo, x, out);
}
```

```cpp
#include <cuda_runtime.h>
#include <cuda_bf16.h>
#include <cuda.h>
#include <stdint.h>

namespace {

constexpr int S_ = 2048, D_ = 512, H_ = 32, F_ = 1792;

constexpr uint32_t PMASK = 0xA52;
__host__ __device__ constexpr bool is_poly_group(int g8) { return g8 >= 4 && ((PMASK >> ((g8 - 4) % 12)) & 1); }

__device__ __align__(1024) uint4 g_QKV[3 * H_ * S_ * 2];
#define g_Q (g_QKV)
#define g_K (g_QKV + H_ * S_ * 2)
#define g_V (g_QKV + 2 * H_ * S_ * 2)
__device__ __align__(1024) uint4 g_O[S_ * D_ / 8];
__device__ float2 g_stats[S_];
__device__ uint32_t g_const[4] = {421u, 0x459EB285u  , 0x3F800000u  , 0u};
__device__ float g_r[S_];
__device__ __align__(16) float g_ypart[4][2][D_];
__device__ int g_sel[2];

#define TL(k, p)
__device__ __forceinline__ uint32_t smem_u32(const void* p) { return (uint32_t)__cvta_generic_to_shared(p); }
__device__ __forceinline__ float bf16r(float x) { return __bfloat162float(__float2bfloat16_rn(x)); }
__device__ __forceinline__ uint32_t pack_bf16(float lo, float hi) {
    uint32_t r; asm("cvt.rn.bf16x2.f32 %0, %1, %2;" : "=r"(r) : "f"(hi), "f"(lo)); return r;
}
__device__ __forceinline__ float bf_lo(uint32_t u) { return __uint_as_float(u << 16); }
__device__ __forceinline__ float bf_hi(uint32_t u) { return __uint_as_float(u & 0xFFFF0000u); }
__device__ __forceinline__ float ex2(float x) { float y; asm("ex2.approx.ftz.f32 %0, %1;" : "=f"(y) : "f"(x)); return y; }

__device__ __forceinline__ void mbar_init(uint32_t bar, uint32_t count) {
    asm volatile("mbarrier.init.shared::cta.b64 [%0], %1;" :: "r"(bar), "r"(count) : "memory");
}
__device__ __forceinline__ void mbar_expect_tx(uint32_t bar, uint32_t bytes) {
    asm volatile("mbarrier.arrive.expect_tx.shared::cta.b64 _, [%0], %1;" :: "r"(bar), "r"(bytes) : "memory");
}
__device__ __forceinline__ void mbar_arrive(uint32_t bar) {
    asm volatile("mbarrier.arrive.shared::cta.b64 _, [%0];" :: "r"(bar) : "memory");
}
__device__ __forceinline__ void mbar_wait(uint32_t bar, uint32_t parity) {
    uint32_t done;
    #pragma unroll 1
    for (int it = 0; it < (1 << 26); it++) {
        asm volatile("{.reg .pred p; mbarrier.try_wait.parity.shared::cta.b64 p, [%1], %2; selp.u32 %0, 1, 0, p;}"
                     : "=r"(done) : "r"(bar), "r"(parity) : "memory");
        if (done) return;
    }
    __trap();
}
__device__ __forceinline__ void bulk_g2s(uint32_t dst, const void* src, uint32_t bytes, uint32_t bar) {
    asm volatile("cp.async.bulk.shared::cluster.global.mbarrier::complete_tx::bytes [%0], [%1], %2, [%3];"
                 :: "r"(dst), "l"(src), "r"(bytes), "r"(bar) : "memory");
}
__device__ __forceinline__ void tma_2d(uint32_t dst, const CUtensorMap* map, int c0, int c1, uint32_t bar) {
    asm volatile("cp.async.bulk.tensor.2d.shared::cluster.global.mbarrier::complete_tx::bytes [%0], [%1, {%3, %4}], [%2];"
                 :: "r"(dst), "l"(map), "r"(bar), "r"(c0), "r"(c1) : "memory");
}
__device__ __forceinline__ void fence_async_smem() { asm volatile("fence.proxy.async.shared::cta;" ::: "memory"); }
__device__ __forceinline__ void named_bar(int id, int n) { asm volatile("bar.sync %0, %1;" :: "r"(id), "r"(n) : "memory"); }

__device__ __forceinline__ uint64_t make_desc(uint32_t saddr, uint32_t lbo, uint32_t sbo, uint32_t swz) {
    return (uint64_t)((saddr & 0x3FFFF) >> 4) | ((uint64_t)(lbo >> 4) << 16) | ((uint64_t)(sbo >> 4) << 32) | ((uint64_t)swz << 62);
}
#define WG_FENCE() asm volatile("wgmma.fence.sync.aligned;" ::: "memory")
#define WG_COMMIT() asm volatile("wgmma.commit_group.sync.aligned;" ::: "memory")
template <int N> __device__ __forceinline__ void wg_wait() { asm volatile("wgmma.wait_group.sync.aligned %0;" :: "n"(N) : "memory"); }

#define F4(d, o) "+f"(d[o]), "+f"(d[o + 1]), "+f"(d[o + 2]), "+f"(d[o + 3])
#define F16(d, o) F4(d, o), F4(d, o + 4), F4(d, o + 8), F4(d, o + 12)
#define F32(d, o) F16(d, o), F16(d, o + 16)

__device__ __forceinline__ void wgmma_n192(float* d, uint64_t da, uint64_t db) {
    asm volatile("wgmma.mma_async.sync.aligned.m64n192k16.f32.bf16.bf16 "
        "{%0,%1,%2,%3,%4,%5,%6,%7,%8,%9,%10,%11,%12,%13,%14,%15,%16,%17,%18,%19,%20,%21,%22,%23,%24,%25,%26,%27,%28,%29,%30,%31,"
        "%32,%33,%34,%35,%36,%37,%38,%39,%40,%41,%42,%43,%44,%45,%46,%47,%48,%49,%50,%51,%52,%53,%54,%55,%56,%57,%58,%59,%60,%61,%62,%63,"
        "%64,%65,%66,%67,%68,%69,%70,%71,%72,%73,%74,%75,%76,%77,%78,%79,%80,%81,%82,%83,%84,%85,%86,%87,%88,%89,%90,%91,%92,%93,%94,%95}, "
        "%96, %97, 1, 1, 1, 0, 1;\n"
        : F32(d, 0), F32(d, 32), F32(d, 64) : "l"(da), "l"(db));
}
__device__ __forceinline__ void wgmma_n64(float* d, uint64_t da, uint64_t db) {
    asm volatile("wgmma.mma_async.sync.aligned.m64n64k16.f32.bf16.bf16 "
        "{%0,%1,%2,%3,%4,%5,%6,%7,%8,%9,%10,%11,%12,%13,%14,%15,%16,%17,%18,%19,%20,%21,%22,%23,%24,%25,%26,%27,%28,%29,%30,%31}, "
        "%32, %33, 1, 1, 1, 0, 1;\n"
        : F32(d, 0) : "l"(da), "l"(db));
}
__device__ __forceinline__ void wgmma_qk32(float* d, uint32_t qd, uint32_t kd) {
    asm volatile("{.reg .b64 a, b; mov.b64 a, {%16, 16}; mov.b64 b, {%17, 16};\n"
        "wgmma.mma_async.sync.aligned.m64n32k16.f32.bf16.bf16 {%0,%1,%2,%3,%4,%5,%6,%7,%8,%9,%10,%11,%12,%13,%14,%15}, a, b, 0, 1, 1, 0, 0;}\n"
        : F16(d, 0) : "r"(qd), "r"(kd));
}
__device__ __forceinline__ void wgmma_pv(float* d, const uint32_t* a, uint32_t vd) {
    asm volatile("{.reg .b64 b; mov.b64 b, {%16, 2048};\n"
        "wgmma.mma_async.sync.aligned.m64n24k16.f32.bf16.bf16 {%0,%1,%2,%3,%4,%5,%6,%7,%8,%9,%10,%11}, {%12,%13,%14,%15}, b, 1, 1, 1, 1;}\n"
        : F4(d, 0), F4(d, 4), F4(d, 8) : "r"(a[0]), "r"(a[1]), "r"(a[2]), "r"(a[3]), "r"(vd));
}
__device__ __forceinline__ void touch16(float* d) { asm volatile("" : F16(d, 0) :: "memory"); }
__device__ __forceinline__ void touch12(float* d) { asm volatile("" : F4(d, 0), F4(d, 4), F4(d, 8) :: "memory"); }
__device__ __forceinline__ void touch32(float* d) { asm volatile("" : F32(d, 0) :: "memory"); }
__device__ __forceinline__ void touch96(float* d) { asm volatile("" : F32(d, 0), F32(d, 32), F32(d, 64) :: "memory"); }

__device__ __forceinline__ float ln_elem(float x, float mean_b, float rden) {
    return bf16r(bf16r(x - mean_b) * rden);
}
__device__ __forceinline__ void pdl_wait() { asm volatile("griddepcontrol.wait;" ::: "memory"); }
__device__ __forceinline__ void pdl_launch() { asm volatile("griddepcontrol.launch_dependents;" ::: "memory"); }
__device__ __forceinline__ void cluster_arrive() { asm volatile("barrier.cluster.arrive.release.aligned;" ::: "memory"); }
__device__ __forceinline__ void cluster_wait() { asm volatile("barrier.cluster.wait.acquire.aligned;" ::: "memory"); }

constexpr int K1_THREADS = 288;
constexpr int K1_SMEM = 131072 + 4 * 24576 + 256;

__device__ __forceinline__ float reduce2(float a, float b, int lane) {
    const bool up = lane & 16;
    float r = (up ? b : a) + __shfl_xor_sync(~0u, up ? a : b, 16);
    #pragma unroll
    for (int o = 8; o; o >>= 1) r += __shfl_xor_sync(~0u, r, o);
    return r;
}

__device__ __forceinline__ void k1_epilogue(const float* acc, uint32_t stage, int nt, int mt, int wg, int w4, int lane, bool live) {
    const int g8a = mt * 16 + wg * 8 + w4 * 2;
    const uint32_t sx0 = is_poly_group(g8a) ? 0x80008000u : 0u, sx1 = is_poly_group(g8a + 1) ? 0x80008000u : 0u;
    const int mi = lane >> 3, lr = lane & 7;
    const uint32_t off_qk = stage + (w4 * 2 + (mi & 1)) * 256 + (mi >> 1) * 128 + lr * 16;
    const uint32_t off_v = stage + (mi >> 1) * 1024 + (w4 * 16 + (mi & 1) * 8 + lr) * 16;
    #pragma unroll
    for (int jj = 0; jj < 12; jj++) {
        const bool isv = nt * 12 + jj >= 64;
        const uint32_t x0 = isv ? sx0 : 0u, x1 = isv ? sx1 : 0u;
        const uint32_t r0 = pack_bf16(acc[8 * jj], acc[8 * jj + 1]) ^ x0, r1 = pack_bf16(acc[8 * jj + 2], acc[8 * jj + 3]) ^ x1;
        const uint32_t r2 = pack_bf16(acc[8 * jj + 4], acc[8 * jj + 5]) ^ x0, r3 = pack_bf16(acc[8 * jj + 6], acc[8 * jj + 7]) ^ x1;
        const uint32_t addr = (isv ? off_v : off_qk) + (jj >> 2) * 16384 + (jj & 3) * 2048;
        if (live) asm volatile("stmatrix.sync.aligned.m8n8.x4.shared.b16 [%0], {%1, %2, %3, %4};" :: "r"(addr), "r"(r0), "r"(r1), "r"(r2), "r"(r3) : "memory");
    }
    if (live) {
        fence_async_smem();
        named_bar(1 + wg, 128);
        const int pc = w4 * 6 + lane;
        if (lane < 6) {
            const int jj = pc >> 1, hf = pc & 1, hg = nt * 12 + jj;
            const unsigned char* dst = (const unsigned char*)g_QKV + (size_t)hg * 65536
                + (hg >= 64 ? hf * 32768 + (mt * 128 + wg * 64) * 16 : (mt * 16 + wg * 8) * 256 + hf * 1024);
            asm volatile("cp.async.bulk.global.shared::cta.bulk_group [%0], [%1], 1024;"
                         :: "l"(dst), "r"(stage + (jj >> 2) * 16384 + (jj & 3) * 2048 + hf * 1024) : "memory");
            asm volatile("cp.async.bulk.commit_group;" ::: "memory");
            asm volatile("cp.async.bulk.wait_group 0;" ::: "memory");
        }
    }
}

__global__ void __launch_bounds__(K1_THREADS, 1)
k1_ln_qkv(const __grid_constant__ CUtensorMap wmap, const __grid_constant__ CUtensorMap xmap, const __nv_bfloat16* __restrict__ w_r) {
    extern __shared__ __align__(1024) unsigned char smem[];
    const uint32_t sA = smem_u32(smem), sB = sA + 131072, sBar = sB + 4 * 24576;
    const int warp = __shfl_sync(~0u, threadIdx.x >> 5, 0), lane = threadIdx.x & 31;
    const int nt = blockIdx.x & 7, mt = blockIdx.x >> 3;
    const bool producer = warp == 8;
    const int wg = (warp >> 2) & 1;
    TL(0, 0);
    pdl_launch();
    if (threadIdx.x == 256) {
        for (int i = 0; i < 4; i++) { mbar_init(sBar + i * 8, 1); mbar_init(sBar + 32 + i * 8, 2); }
        mbar_init(sBar + 64, 1); mbar_init(sBar + 72, 1);
        asm volatile("fence.mbarrier_init.release.cluster;" ::: "memory");
        for (int hf = 0; hf < 2; hf++) {
            mbar_expect_tx(sBar + 64 + hf * 8, 65536);
            for (int pn = 0; pn < 8; pn++) tma_2d(sA + pn * 16384 + hf * 8192, &xmap, pn * 64, mt * 128 + hf * 64, sBar + 64 + hf * 8);
        }
    }
    __syncthreads();
    float acc[96];
    #pragma unroll
    for (int i = 0; i < 96; i++) acc[i] = 0.f;
    if (producer) {
        if (lane == 0) {
            for (int kc = 0; kc < 8; kc++) {
                const int st = kc & 3;
                if (kc >= 4) mbar_wait(sBar + 32 + st * 8, 0);
                mbar_expect_tx(sBar + st * 8, 24576);
                for (int j = 0; j < 3; j++) tma_2d(sB + st * 24576 + j * 8192, &wmap, nt * 192 + j * 64, kc * 64, sBar + st * 8);
            }
        }
        __syncwarp();
    } else {
        const uint4 wr0 = __ldg((const uint4*)(w_r + lane * 8)), wr1 = __ldg((const uint4*)(w_r + 256 + lane * 8));
        TL(0, 1);
        #pragma unroll 1
        for (int it = -1; it < 8; it++) {
            if (it == 0) { mbar_wait(sBar + 64 + wg * 8, 0); TL(0, 8); }
            uint32_t u[2][8];
            unsigned char* sp[2];
            #pragma unroll
            for (int i = 0; i < 2; i++) {
                const int r = warp * 16 + (it & 7) * 2 + i;
                sp[i] = smem + (lane >> 3) * 16384 + r * 128 + (((lane & 7) ^ (r & 7)) * 16);
                const uint4 a = *(const uint4*)sp[i], b = *(const uint4*)(sp[i] + 65536);
                u[i][0] = a.x; u[i][1] = a.y; u[i][2] = a.z; u[i][3] = a.w; u[i][4] = b.x; u[i][5] = b.y; u[i][6] = b.z; u[i][7] = b.w;
            }
            float p[2];
            #pragma unroll
            for (int i = 0; i < 2; i++) {
                float s0 = 0.f, s1 = 0.f;
                #pragma unroll
                for (int j = 0; j < 8; j++) { s0 += bf_lo(u[i][j]); s1 += bf_hi(u[i][j]); }
                p[i] = s0 + s1;
            }
            const float mean_l = reduce2(p[0], p[1], lane) * (1.0f / D_);
            #pragma unroll
            for (int i = 0; i < 2; i++) {
                const float mean = __shfl_sync(~0u, mean_l, i * 16);
                float q0 = 0.f, q1 = 0.f;
                #pragma unroll
                for (int j = 0; j < 8; j++) {
                    const float d0 = bf_lo(u[i][j]) - mean, d1 = bf_hi(u[i][j]) - mean;
                    q0 = fmaf(d0, d0, q0); q1 = fmaf(d1, d1, q1);
                }
                p[i] = q0 + q1;
            }
            const float var_b = bf16r(reduce2(p[0], p[1], lane) * (1.0f / D_));
            const float rden_l = __frcp_rn(bf16r(__fsqrt_rn(bf16r(var_b + 1e-5f))));
            const uint32_t mean2_l = pack_bf16(mean_l, mean_l);
            #pragma unroll
            for (int i = 0; i < 2; i++) {
                const uint32_t m2 = __shfl_sync(~0u, mean2_l, i * 16);
                const float rden = __shfl_sync(~0u, rden_l, i * 16);
                #pragma unroll
                for (int j = 0; j < 8; j++) {
                    uint32_t d2;
                    asm("sub.rn.bf16x2 %0, %1, %2;" : "=r"(d2) : "r"(u[i][j]), "r"(m2));
                    u[i][j] = pack_bf16(bf_lo(d2) * rden, bf_hi(d2) * rden);
                }
                if (it >= 0) {
                    *(uint4*)sp[i] = make_uint4(u[i][0], u[i][1], u[i][2], u[i][3]);
                    *(uint4*)(sp[i] + 65536) = make_uint4(u[i][4], u[i][5], u[i][6], u[i][7]);
                }
            }
            if (nt == (it & 7)) {
                const uint32_t w[8] = {wr0.x, wr0.y, wr0.z, wr0.w, wr1.x, wr1.y, wr1.z, wr1.w};
                #pragma unroll
                for (int i = 0; i < 2; i++) {
                    float a0 = 0.f, a1 = 0.f;
                    #pragma unroll
                    for (int j = 0; j < 8; j++) { a0 = fmaf(bf_lo(u[i][j]), bf_lo(w[j]), a0); a1 = fmaf(bf_hi(u[i][j]), bf_hi(w[j]), a1); }
                    p[i] = a0 + a1;
                }
                const float rl = reduce2(p[0], p[1], lane);
                if ((lane & 15) == 0 && it >= 0) {
                    const int row = mt * 128 + warp * 16 + it * 2 + (lane >> 4);
                    g_r[row] = bf16r(rl);
                    g_stats[row] = make_float2(bf_lo(mean2_l), rden_l);
                }
            }
        }
        TL(0, 2);
        fence_async_smem();
        named_bar(1 + wg, 128);
        TL(0, 3);
        const uint64_t da0 = make_desc(sA + wg * 8192, 16, 1024, 1);
        const uint64_t db0 = make_desc(sB, 8192, 1024, 1);
        #pragma unroll 1
        for (int kc = 0; kc < 8; kc++) {
            const int st = kc & 3;
            mbar_wait(sBar + st * 8, kc >> 2);
            WG_FENCE();
            #pragma unroll
            for (int kk = 0; kk < 4; kk++)
                wgmma_n192(acc, da0 + (uint64_t)(kc * 1024 + kk * 2), db0 + (uint64_t)(st * 1536 + kk * 128));
            WG_COMMIT();
            wg_wait<1>();
            if (kc >= 1 && kc <= 4 && (threadIdx.x & 127) == 0) mbar_arrive(sBar + 32 + (kc - 1) * 8);
        }
        wg_wait<0>();
        touch96(acc);
        named_bar(1 + wg, 128);
        TL(0, 5);
    }
    k1_epilogue(acc, sA + wg * 8192, nt, mt, wg, warp & 3, lane, !producer);
    TL(0, 6);
}

constexpr int K2_THREADS = 512;
constexpr int K2_SMEM = 65536 + 98304 + 16384 + 128;

constexpr float QS = 0.25f * 1.4426950408889634f;
__device__ __forceinline__ uint32_t polyexp(float s, float cb, uint32_t c421, float c3, float one) {
    float u;
    asm("fma.rn.sat.f32 %0, %1, %2, %3;" : "=f"(u) : "f"(s), "f"(QS * (1.0f / 255.0f)), "f"(cb));
    float z = fmaf(u, 0.99609375f, one);
    uint32_t rb;
    asm("lop3.b32 %0, %1, 0xFFFF8000, %2, 0xEA;" : "=r"(rb) : "r"(__float_as_uint(z)), "r"(c421));
    float f = z - __uint_as_float(rb);
    float h = fmaf(f, c3, 58.86525f);
    h = fmaf(f, h, -0.29870507f);
    return __float_as_uint(fmaf(f, h, z));
}

struct ExpC { float nm0, nm1, cb0, cb1, c3, one; uint32_t c421; };

template <int G>
__device__ __forceinline__ void exp_block(const float* s, uint32_t* p, const ExpC& c) {
    #pragma unroll
    for (int hf = 0; hf < 2; hf++) {
        const float* x = s + hf * 4;
        if ((PMASK >> (G + hf)) & 1) {
            p[hf * 2 + 0] = __byte_perm(polyexp(x[0], c.cb0, c.c421, c.c3, c.one), polyexp(x[1], c.cb0, c.c421, c.c3, c.one), 0x6521);
            p[hf * 2 + 1] = __byte_perm(polyexp(x[2], c.cb1, c.c421, c.c3, c.one), polyexp(x[3], c.cb1, c.c421, c.c3, c.one), 0x6521);
        } else {
            p[hf * 2 + 0] = pack_bf16(ex2(fmaf(x[0], QS, c.nm0)), ex2(fmaf(x[1], QS, c.nm0)));
            p[hf * 2 + 1] = pack_bf16(ex2(fmaf(x[2], QS, c.nm1)), ex2(fmaf(x[3], QS, c.nm1)));
        }
    }
}

__device__ __forceinline__ void max16(const float* s, float& mx0, float& mx1) {
    #pragma unroll
    for (int j = 0; j < 4; j++) {
        mx0 = fmaxf(mx0, fmaxf(s[4 * j], s[4 * j + 1]));
        mx1 = fmaxf(mx1, fmaxf(s[4 * j + 2], s[4 * j + 3]));
    }
}

__device__ void moe_cta(int part, unsigned char* smem, const __nv_bfloat16* __restrict__ x, const __nv_bfloat16* __restrict__ w_gate,
                        const __nv_bfloat16* __restrict__ w_up, const __nv_bfloat16* __restrict__ w_down) {
    float* xs = (float*)smem;
    float* red = xs + 1024;
    float* hs = red + 8 * 4 * 448;
    __shared__ float s_v[32];
    __shared__ int s_i[32];
    __shared__ int s_sel[2];
    const int tid = threadIdx.x, warp = tid >> 5, lane = tid & 31;
    for (int pass = 0; pass < 2; pass++) {
        float bv = -INFINITY; int bi = 0x7fffffff;
        const int excl = pass ? s_sel[0] : -1;
        for (int i = tid; i < S_; i += K2_THREADS) {
            float v = g_r[i];
            if (i != excl && (v > bv || (v == bv && i < bi) || bi == 0x7fffffff)) { bv = v; bi = i; }
        }
        #pragma unroll
        for (int o = 16; o; o >>= 1) {
            float ov = __shfl_xor_sync(~0u, bv, o); int oi = __shfl_xor_sync(~0u, bi, o);
            if (ov > bv || (ov == bv && oi < bi)) { bv = ov; bi = oi; }
        }
        if (lane == 0) { s_v[warp] = bv; s_i[warp] = bi; }
        __syncthreads();
        if (warp == 0) {
            bv = lane < 16 ? s_v[lane] : -INFINITY; bi = lane < 16 ? s_i[lane] : 0x7fffffff;
            #pragma unroll
            for (int o = 16; o; o >>= 1) {
                float ov = __shfl_xor_sync(~0u, bv, o); int oi = __shfl_xor_sync(~0u, bi, o);
                if (ov > bv || (ov == bv && oi < bi)) { bv = ov; bi = oi; }
            }
            if (lane == 0) s_sel[pass] = (bi == 0x7fffffff) ? pass : bi;
        }
        __syncthreads();
    }
    for (int i = tid; i < 1024; i += K2_THREADS) {
        const int tok = s_sel[i >> 9];
        const float2 st = g_stats[tok];
        xs[i] = ln_elem(__bfloat162float(x[(size_t)tok * D_ + (i & 511)]), st.x, st.y);
    }
    if (part == 0 && tid < 2) g_sel[tid] = s_sel[tid];
    __syncthreads();
    const int c0 = part * 448;
    if (tid < 448) {
        const int cg = tid % 56, ks = tid / 56;
        float a[4][8];
        #pragma unroll
        for (int i = 0; i < 4; i++)
            #pragma unroll
            for (int j = 0; j < 8; j++) a[i][j] = 0.f;
        const __nv_bfloat16* pg = w_gate + (size_t)(ks * 64) * F_ + c0 + cg * 8;
        const __nv_bfloat16* pu = w_up + (size_t)(ks * 64) * F_ + c0 + cg * 8;
        #pragma unroll 8
        for (int k = 0; k < 64; k++) {
            const uint4 gv = __ldg((const uint4*)(pg + (size_t)k * F_));
            const uint4 uv = __ldg((const uint4*)(pu + (size_t)k * F_));
            const float x0 = xs[ks * 64 + k], x1 = xs[512 + ks * 64 + k];
            const uint32_t gu[4] = {gv.x, gv.y, gv.z, gv.w}, uu[4] = {uv.x, uv.y, uv.z, uv.w};
            #pragma unroll
            for (int j = 0; j < 4; j++) {
                const float g0 = bf_lo(gu[j]), g1 = bf_hi(gu[j]), u0 = bf_lo(uu[j]), u1 = bf_hi(uu[j]);
                a[0][2 * j] = fmaf(x0, g0, a[0][2 * j]); a[0][2 * j + 1] = fmaf(x0, g1, a[0][2 * j + 1]);
                a[1][2 * j] = fmaf(x1, g0, a[1][2 * j]); a[1][2 * j + 1] = fmaf(x1, g1, a[1][2 * j + 1]);
                a[2][2 * j] = fmaf(x0, u0, a[2][2 * j]); a[2][2 * j + 1] = fmaf(x0, u1, a[2][2 * j + 1]);
                a[3][2 * j] = fmaf(x1, u0, a[3][2 * j]); a[3][2 * j + 1] = fmaf(x1, u1, a[3][2 * j + 1]);
            }
        }
        #pragma unroll
        for (int i = 0; i < 4; i++)
            #pragma unroll
            for (int j = 0; j < 8; j++) red[(ks * 4 + i) * 448 + cg * 8 + j] = a[i][j];
    }
    __syncthreads();
    for (int i = tid; i < 896; i += K2_THREADS) {
        const int tok = i / 448, c = i % 448;
        float gs = 0.f, us = 0.f;
        #pragma unroll
        for (int ks = 0; ks < 8; ks++) { gs += red[(ks * 4 + tok) * 448 + c]; us += red[(ks * 4 + 2 + tok) * 448 + c]; }
        gs = bf16r(gs); us = bf16r(us);
        const float sl = bf16r(gs / (1.0f + __expf(-gs)));
        hs[i] = bf16r(sl * us);
    }
    __syncthreads();
    {
        const int cg = tid & 63, fs = tid >> 6;
        float a[2][8];
        #pragma unroll
        for (int j = 0; j < 8; j++) { a[0][j] = 0.f; a[1][j] = 0.f; }
        const __nv_bfloat16* pd = w_down + (size_t)(c0 + fs * 56) * D_ + cg * 8;
        #pragma unroll 8
        for (int f = 0; f < 56; f++) {
            const uint4 dv = __ldg((const uint4*)(pd + (size_t)f * D_));
            const float h0 = hs[fs * 56 + f], h1 = hs[448 + fs * 56 + f];
            const uint32_t du[4] = {dv.x, dv.y, dv.z, dv.w};
            #pragma unroll
            for (int j = 0; j < 4; j++) {
                const float d0 = bf_lo(du[j]), d1 = bf_hi(du[j]);
                a[0][2 * j] = fmaf(h0, d0, a[0][2 * j]); a[0][2 * j + 1] = fmaf(h0, d1, a[0][2 * j + 1]);
                a[1][2 * j] = fmaf(h1, d0, a[1][2 * j]); a[1][2 * j + 1] = fmaf(h1, d1, a[1][2 * j + 1]);
            }
        }
        #pragma unroll
        for (int j = 0; j < 8; j++) { red[(fs * 2) * 512 + cg * 8 + j] = a[0][j]; red[(fs * 2 + 1) * 512 + cg * 8 + j] = a[1][j]; }
    }
    __syncthreads();
    for (int i = tid; i < 1024; i += K2_THREADS) {
        float s = 0.f;
        #pragma unroll
        for (int fs = 0; fs < 8; fs++) s += red[(fs * 2 + (i >> 9)) * 512 + (i & 511)];
        g_ypart[part][i >> 9][i & 511] = s;
    }
}

__global__ void __launch_bounds__(K2_THREADS, 1)
k2_attn(const __nv_bfloat16* __restrict__ x, const __nv_bfloat16* __restrict__ w_gate, const __nv_bfloat16* __restrict__ w_up,
        const __nv_bfloat16* __restrict__ w_down) {
    extern __shared__ __align__(1024) unsigned char smem[];
    TL(1, 0);
    pdl_launch();
    if (blockIdx.x >= 128) {
        const int part = blockIdx.x - 128;
        {
            const int k = threadIdx.x;
            asm volatile("cp.async.bulk.prefetch.L2.global [%0], %1;" :: "l"(w_gate + (size_t)k * F_ + part * 448), "r"(896) : "memory");
            asm volatile("cp.async.bulk.prefetch.L2.global [%0], %1;" :: "l"(w_up + (size_t)k * F_ + part * 448), "r"(896) : "memory");
            if (k < 56) asm volatile("cp.async.bulk.prefetch.L2.global [%0], %1;" :: "l"(w_down + (size_t)(part * 448 + k * 8) * D_), "r"(8192) : "memory");
        }
        pdl_wait(); TL(1, 1); moe_cta(blockIdx.x - 128, smem, x, w_gate, w_up, w_down); TL(1, 2); return; }
    const uint32_t sK = smem_u32(smem), sV = sK + 65536, sQ = sV + 98304, sBar = sQ + 16384;
    const int h = blockIdx.x >> 2, qb = blockIdx.x & 3;
    const int warp = __shfl_sync(~0u, threadIdx.x >> 5, 0), lane = threadIdx.x & 31, wg = warp >> 2;
    if (threadIdx.x == 0) {
        mbar_init(sBar, 1); mbar_init(sBar + 8, 1);
        asm volatile("fence.mbarrier_init.release.cluster;" ::: "memory");
        pdl_wait();
        TL(1, 1);
        const uint4* gk = g_K + (size_t)h * 4096;
        const uint4* gv = g_V + (size_t)h * 4096;
        mbar_expect_tx(sBar, 16384 + 16384 + 2 * 8192);
        bulk_g2s(sQ, g_Q + (size_t)h * 4096 + qb * 1024, 16384, sBar);
        bulk_g2s(sK, gk, 16384, sBar);
        bulk_g2s(sV, gv, 8192, sBar);
        bulk_g2s(sV + 32768, gv + 2048, 8192, sBar);
        mbar_expect_tx(sBar + 8, 49152 + 2 * 24576);
        bulk_g2s(sK + 16384, gk + 1024, 49152, sBar + 8);
        bulk_g2s(sV + 8192, gv + 512, 24576, sBar + 8);
        bulk_g2s(sV + 32768 + 8192, gv + 2048 + 512, 24576, sBar + 8);
    }
    for (int i = threadIdx.x; i < 2048; i += K2_THREADS) {
        const uint32_t v = is_poly_group(i >> 3) ? 0xBF80BF80u : 0x3F803F80u;
        *(uint4*)(smem + 65536 + 65536 + i * 16) = make_uint4(v, v, v, v);
    }
    fence_async_smem();
    __syncthreads();
    ExpC c;
    {
        const volatile uint32_t* cc = g_const;
        c.c421 = cc[0]; c.c3 = __uint_as_float(cc[1]); c.one = __uint_as_float(cc[2]);
    }
    const uint32_t kdesc0 = (uint32_t)make_desc(sK, 128, 256, 0);
    const uint32_t vdesc0 = (uint32_t)make_desc(sV, 128, 32768, 0);
    mbar_wait(sBar, 0);
    TL(1, 2);
    #pragma unroll 1
    for (int pass = 0; pass < 2; pass++) {
        const int unit = pass * 4 + wg;
        const uint32_t q = (uint32_t)make_desc(sQ + unit * 2048, 128, 256, 0);
        float o[12];
        #pragma unroll 1
        for (int attempt = 0; attempt < 2; attempt++) {
            float s0[16], s1[16], s2[16];
            #pragma unroll
            for (int i = 0; i < 16; i++) { s0[i] = 0.f; s1[i] = 0.f; s2[i] = 0.f; }
            float mx0 = -INFINITY, mx1 = -INFINITY;
            if (attempt) {
                #pragma unroll 1
                for (int it = 0; it < 64; it++) {
                    WG_FENCE();
                    wgmma_qk32(s0, q, kdesc0 + it * 64);
                    WG_COMMIT();
                    wg_wait<0>();
                    touch16(s0);
                    max16(s0, mx0, mx1);
                }
            }
            #pragma unroll
            for (int i = 0; i < 12; i++) o[i] = 0.f;
            WG_FENCE();
            wgmma_qk32(s2, q, kdesc0);
            wgmma_qk32(s0, q, kdesc0 + 64);
            wgmma_qk32(s1, q, kdesc0 + 128);
            WG_COMMIT();
            wg_wait<0>();
            touch16(s0); touch16(s1); touch16(s2);
            max16(s0, mx0, mx1); max16(s1, mx0, mx1); max16(s2, mx0, mx1);
            mx0 = fmaxf(mx0, __shfl_xor_sync(~0u, mx0, 1)); mx0 = fmaxf(mx0, __shfl_xor_sync(~0u, mx0, 2));
            mx1 = fmaxf(mx1, __shfl_xor_sync(~0u, mx1, 1)); mx1 = fmaxf(mx1, __shfl_xor_sync(~0u, mx1, 2));
            const float bias = attempt ? 0.0f : 64.0f;
            c.nm0 = __shfl_sync(~0u, -fmaf(mx0, QS, bias), lane); c.nm1 = __shfl_sync(~0u, -fmaf(mx1, QS, bias), lane);
            c.cb0 = __shfl_sync(~0u, (127.0f + c.nm0) * (1.0f / 255.0f), lane);
            c.cb1 = __shfl_sync(~0u, (127.0f + c.nm1) * (1.0f / 255.0f), lane);
            uint32_t kd = kdesc0 + 192, vd = vdesc0 + 32;
            {
                uint32_t pa[4], pb[4];
                exp_block<12>(s2, pa, c);
                exp_block<14>(s2 + 8, pb, c);
                WG_FENCE();
                wgmma_pv(o, pa, vdesc0); wgmma_pv(o, pb, vdesc0 + 16);
                WG_COMMIT();
            }
            #pragma unroll 1
            for (int seg = 0; seg < 2; seg++) {
            if (seg) { wg_wait<0>(); mbar_wait(sBar + 8, 0); __syncwarp(); }
            #pragma unroll 1
            for (int it = seg ? 3 : 0; it < (seg ? 21 : 3); it++) {
                uint32_t p[6][4];
                WG_FENCE();
                wgmma_qk32(s2, q, kd);
                WG_COMMIT();
                exp_block<0>(s0, p[0], c);
                exp_block<2>(s0 + 8, p[1], c);
                WG_FENCE();
                wgmma_pv(o, p[0], vd); wgmma_pv(o, p[1], vd + 16);
                wgmma_qk32(s0, q, kd + 64);
                WG_COMMIT();
                wg_wait<1>();
                touch16(s2);
                exp_block<4>(s1, p[2], c);
                exp_block<6>(s1 + 8, p[3], c);
                WG_FENCE();
                wgmma_pv(o, p[2], vd + 32); wgmma_pv(o, p[3], vd + 48);
                wgmma_qk32(s1, q, kd + 128);
                WG_COMMIT();
                wg_wait<1>();
                touch16(s0);
                exp_block<8>(s2, p[4], c);
                exp_block<10>(s2 + 8, p[5], c);
                WG_FENCE();
                wgmma_pv(o, p[4], vd + 64); wgmma_pv(o, p[5], vd + 80);
                WG_COMMIT();
                vd += 96; kd += 192;
                wg_wait<1>();
                touch16(s1);
            }
            }
            wg_wait<0>();
            touch12(o);
            if (attempt) break;
            float big = 0.f;
            #pragma unroll
            for (int i = 0; i < 12; i++) big = fmaxf(big, fabsf(o[i]));
            bool bad = !(big < 1e30f);
            #pragma unroll
            for (int i = 0; i < 12; i++) bad |= (o[i] != o[i]);
            uint32_t any;
            asm volatile("{.reg .pred p, q; setp.ne.u32 p, %1, 0; barrier.cta.red.or.pred.aligned q, %2, 128, p; selp.u32 %0, 1, 0, q;}"
                         : "=r"(any) : "r"((uint32_t)bad), "r"(1 + wg) : "memory");
            if (!__any_sync(~0u, any)) break;
        }
        const int g = lane >> 2, t = lane & 3;
        const int r = (warp & 3) * 16 + g;
        const float i0 = __fdiv_rn(1.0f, o[8]), i1 = __fdiv_rn(1.0f, o[10]);
        uint32_t* ob = (uint32_t*)(g_O + (size_t)(qb * 8 + unit) * 4096 + (h >> 2) * 512 + r * 8) + t;
        const int c0 = ((h & 3) * 2) ^ (r & 7), c1 = ((h & 3) * 2 + 1) ^ (r & 7);
        ob[c0 * 4] = pack_bf16(o[0] * i0, o[1] * i0);
        ob[c1 * 4] = pack_bf16(o[4] * i0, o[5] * i0);
        ob[256 + c0 * 4] = pack_bf16(o[2] * i1, o[3] * i1);
        ob[256 + c1 * 4] = pack_bf16(o[6] * i1, o[7] * i1);
        TL(1, 3 + pass);
    }
}

constexpr int K3_THREADS = 256;
constexpr int K3_SMEM = 65536 + 131072 + 128;

__global__ void __launch_bounds__(K3_THREADS, 1)
k3_out(const __grid_constant__ CUtensorMap wmap, const __nv_bfloat16* __restrict__ x, __nv_bfloat16* __restrict__ out) {
    extern __shared__ __align__(1024) unsigned char smem[];
    const uint32_t sA = smem_u32(smem), sB = sA + 65536, sBar = sB + 131072;
    const int warp = __shfl_sync(~0u, threadIdx.x >> 5, 0), lane = threadIdx.x & 31, wg = warp >> 2;
    const int nt = blockIdx.x & 3, mt = blockIdx.x >> 2;
    TL(2, 0);
    if (threadIdx.x == 0) {
        for (int i = 0; i < 6; i++) mbar_init(sBar + i * 8, 1);
        asm volatile("fence.mbarrier_init.release.cluster;" ::: "memory");
        for (int kh = 0; kh < 2; kh++) {
            mbar_expect_tx(sBar + kh * 8, 65536);
            tma_2d(sB + kh * 32768, &wmap, nt * 128, kh * 256, sBar + kh * 8);
            tma_2d(sB + 65536 + kh * 32768, &wmap, nt * 128 + 64, kh * 256, sBar + kh * 8);
        }
    }
    const int er = threadIdx.x >> 2, ec = (threadIdx.x & 3) * 32;
    const int row = mt * 64 + er;
    uint4 xv[4];
    #pragma unroll
    for (int j = 0; j < 4; j++) xv[j] = __ldg((const uint4*)(x + (size_t)row * D_ + nt * 128 + ec) + j);
    pdl_wait();
    TL(2, 1);
    if (threadIdx.x == 0) {
        for (int q = 0; q < 4; q++) {
            mbar_expect_tx(sBar + 16 + q * 8, 16384);
            bulk_g2s(sA + q * 16384, g_O + (size_t)mt * 4096 + q * 1024, 16384, sBar + 16 + q * 8);
        }
    }
    const int sel0 = g_sel[0], sel1 = g_sel[1];
    const float2 st = g_stats[row];
    uint32_t bb[16];
    {
        const uint32_t xu[16] = {xv[0].x, xv[0].y, xv[0].z, xv[0].w, xv[1].x, xv[1].y, xv[1].z, xv[1].w,
                                 xv[2].x, xv[2].y, xv[2].z, xv[2].w, xv[3].x, xv[3].y, xv[3].z, xv[3].w};
        #pragma unroll
        for (int j = 0; j < 16; j++) bb[j] = pack_bf16(bf16r(bf_lo(xu[j]) - st.x) * st.y, bf16r(bf_hi(xu[j]) - st.x) * st.y);
        const int slot = row == sel0 ? 0 : (row == sel1 ? 1 : -1);
        if (slot >= 0) {
            const float gate = bf16r(1.0f / (1.0f + __expf(-g_r[row])));
            const int c0 = nt * 128 + ec;
            #pragma unroll
            for (int j = 0; j < 16; j++) {
                const float2 a = *(const float2*)&g_ypart[0][slot][c0 + 2 * j], b = *(const float2*)&g_ypart[1][slot][c0 + 2 * j];
                const float2 c = *(const float2*)&g_ypart[2][slot][c0 + 2 * j], d = *(const float2*)&g_ypart[3][slot][c0 + 2 * j];
                bb[j] = pack_bf16(bf_lo(bb[j]) + bf16r(bf16r(a.x + b.x + c.x + d.x) * gate), bf_hi(bb[j]) + bf16r(bf16r(a.y + b.y + c.y + d.y) * gate));
            }
        }
    }
    __syncthreads();
    float acc[32];
    #pragma unroll
    for (int i = 0; i < 32; i++) acc[i] = 0.f;
    const uint64_t da0 = make_desc(sA, 16, 1024, 1);
    const uint64_t db0 = make_desc(sB + wg * 65536, 8192, 1024, 1);
    #pragma unroll 1
    for (int q = 0; q < 4; q++) {
        if ((q & 1) == 0) mbar_wait(sBar + (q >> 1) * 8, 0);
        mbar_wait(sBar + 16 + q * 8, 0);
        WG_FENCE();
        #pragma unroll
        for (int kk = 0; kk < 8; kk++)
            wgmma_n64(acc, da0 + (uint64_t)(q * 1024 + (kk >> 2) * 512 + (kk & 3) * 2), db0 + (uint64_t)(q * 1024 + kk * 128));
        WG_COMMIT();
    }
    wg_wait<0>();
    touch32(acc);
    TL(2, 2);
    __syncthreads();
    {
        const int g = lane >> 2, t = lane & 3;
        unsigned char* sp = smem + ((warp & 3) * 16 + g) * 272 + wg * 128 + t * 4;
        #pragma unroll
        for (int j = 0; j < 8; j++) {
            *(uint32_t*)(sp + j * 16) = pack_bf16(acc[4 * j], acc[4 * j + 1]);
            *(uint32_t*)(sp + 8 * 272 + j * 16) = pack_bf16(acc[4 * j + 2], acc[4 * j + 3]);
        }
    }
    __syncthreads();
    #pragma unroll
    for (int j = 0; j < 4; j++) {
        const uint4 av = *(const uint4*)(smem + er * 272 + ec * 2 + j * 16);
        const uint32_t au[4] = {av.x, av.y, av.z, av.w}, xu[4] = {xv[j].x, xv[j].y, xv[j].z, xv[j].w};
        uint32_t o[4];
        #pragma unroll
        for (int i = 0; i < 4; i++) {
            uint32_t t2;
            asm("add.rn.bf16x2 %0, %1, %2;" : "=r"(t2) : "r"(xu[i]), "r"(au[i]));
            asm("add.rn.bf16x2 %0, %1, %2;" : "=r"(o[i]) : "r"(t2), "r"(bb[j * 4 + i]));
        }
        *((uint4*)(out + (size_t)row * D_ + nt * 128 + ec) + j) = make_uint4(o[0], o[1], o[2], o[3]);
    }
    TL(2, 3);
}

typedef CUresult (*EncodeFn)(CUtensorMap*, CUtensorMapDataType, cuuint32_t, void*, const cuuint64_t*, const cuuint64_t*,
                             const cuuint32_t*, const cuuint32_t*, CUtensorMapInterleave, CUtensorMapSwizzle,
                             CUtensorMapL2promotion, CUtensorMapFloatOOBfill);

void make_wmap(EncodeFn fn, CUtensorMap* map, const void* ptr, int rows, int cols, int box_rows) {
    cuuint64_t dims[2] = {(cuuint64_t)cols, (cuuint64_t)rows};
    cuuint64_t strides[1] = {(cuuint64_t)cols * 2};
    cuuint32_t box[2] = {64, (cuuint32_t)box_rows};
    cuuint32_t es[2] = {1, 1};
    fn(map, CU_TENSOR_MAP_DATA_TYPE_BFLOAT16, 2, (void*)ptr, dims, strides, box, es, CU_TENSOR_MAP_INTERLEAVE_NONE,
       CU_TENSOR_MAP_SWIZZLE_128B, CU_TENSOR_MAP_L2_PROMOTION_L2_256B, CU_TENSOR_MAP_FLOAT_OOB_FILL_NONE);
}

}

extern "C" void kernel_launch(void* const* d_in, const int* in_sizes, int n_in, void* d_out, int out_size) {
    const __nv_bfloat16* x = (const __nv_bfloat16*)d_in[0];
    const __nv_bfloat16* wqkv = (const __nv_bfloat16*)d_in[1];
    const __nv_bfloat16* wo = (const __nv_bfloat16*)d_in[2];
    const __nv_bfloat16* w_r = (const __nv_bfloat16*)d_in[4];
    const __nv_bfloat16* w_gate = (const __nv_bfloat16*)d_in[5];
    const __nv_bfloat16* w_up = (const __nv_bfloat16*)d_in[6];
    const __nv_bfloat16* w_down = (const __nv_bfloat16*)d_in[7];
    __nv_bfloat16* out = (__nv_bfloat16*)d_out;

    static EncodeFn encode = nullptr;
    if (!encode) {
        void* fn = nullptr;
        cudaDriverEntryPointQueryResult qres;
        cudaGetDriverEntryPoint("cuTensorMapEncodeTiled", &fn, cudaEnableDefault, &qres);
        encode = (EncodeFn)fn;
        cudaFuncSetAttribute(k1_ln_qkv, cudaFuncAttributeMaxDynamicSharedMemorySize, K1_SMEM);
        cudaFuncSetAttribute(k2_attn, cudaFuncAttributeMaxDynamicSharedMemorySize, K2_SMEM);
        cudaFuncSetAttribute(k3_out, cudaFuncAttributeMaxDynamicSharedMemorySize, K3_SMEM);
    }
    CUtensorMap map_qkv, map_wo, map_x;
    make_wmap(encode, &map_x, x, S_, D_, 64);
    make_wmap(encode, &map_qkv, wqkv, D_, 3 * D_, 64);
    make_wmap(encode, &map_wo, wo, D_, D_, 256);

    k1_ln_qkv<<<128, K1_THREADS, K1_SMEM, cudaStreamPerThread>>>(map_qkv, map_x, w_r);
    cudaLaunchAttribute at[1];
    at[0].id = cudaLaunchAttributeProgrammaticStreamSerialization;
    at[0].val.programmaticStreamSerializationAllowed = 1;
    cudaLaunchConfig_t cfg = {};
    cfg.stream = cudaStreamPerThread;
    cfg.attrs = at; cfg.numAttrs = 1;
    cfg.gridDim = dim3(132); cfg.blockDim = dim3(K2_THREADS); cfg.dynamicSmemBytes = K2_SMEM;
    cudaLaunchKernelEx(&cfg, k2_attn, x, w_gate, w_up, w_down);
    cfg.gridDim = dim3(128); cfg.blockDim = dim3(K3_THREADS); cfg.dynamicSmemBytes = K3_SMEM;
    cudaLaunchKernelEx(&cfg, k3_out, map_wo, x, out);
}
```

```cpp
#include <cuda_runtime.h>
#include <cuda_bf16.h>
#include <cuda.h>
#include <stdint.h>

namespace {

constexpr int S_ = 2048, D_ = 512, H_ = 32, F_ = 1792;

constexpr uint32_t PMASK = 0xA52;
__host__ __device__ constexpr bool is_poly_group(int g8) { return g8 >= 4 && ((PMASK >> ((g8 - 4) % 12)) & 1); }

__device__ __align__(1024) uint4 g_QKV[3 * H_ * S_ * 2];
#define g_Q (g_QKV)
#define g_K (g_QKV + H_ * S_ * 2)
#define g_V (g_QKV + 2 * H_ * S_ * 2)
__device__ __align__(1024) uint4 g_O[S_ * D_ / 8];
__device__ float2 g_stats[S_];
__device__ uint32_t g_const[4] = {421u, 0x459EB285u  , 0x3F800000u  , 0u};
__device__ float g_r[S_];
__device__ __align__(16) float g_ypart[4][2][D_];
__device__ int g_sel[2];

#define TL(k, p)
__device__ __forceinline__ uint32_t smem_u32(const void* p) { return (uint32_t)__cvta_generic_to_shared(p); }
__device__ __forceinline__ float bf16r(float x) { return __bfloat162float(__float2bfloat16_rn(x)); }
__device__ __forceinline__ uint32_t pack_bf16(float lo, float hi) {
    uint32_t r; asm("cvt.rn.bf16x2.f32 %0, %1, %2;" : "=r"(r) : "f"(hi), "f"(lo)); return r;
}
__device__ __forceinline__ float bf_lo(uint32_t u) { return __uint_as_float(u << 16); }
__device__ __forceinline__ float bf_hi(uint32_t u) { return __uint_as_float(u & 0xFFFF0000u); }
__device__ __forceinline__ float ex2(float x) { float y; asm("ex2.approx.ftz.f32 %0, %1;" : "=f"(y) : "f"(x)); return y; }

__device__ __forceinline__ void mbar_init(uint32_t bar, uint32_t count) {
    asm volatile("mbarrier.init.shared::cta.b64 [%0], %1;" :: "r"(bar), "r"(count) : "memory");
}
__device__ __forceinline__ void mbar_expect_tx(uint32_t bar, uint32_t bytes) {
    asm volatile("mbarrier.arrive.expect_tx.shared::cta.b64 _, [%0], %1;" :: "r"(bar), "r"(bytes) : "memory");
}
__device__ __forceinline__ void mbar_arrive(uint32_t bar) {
    asm volatile("mbarrier.arrive.shared::cta.b64 _, [%0];" :: "r"(bar) : "memory");
}
__device__ __forceinline__ void mbar_wait(uint32_t bar, uint32_t parity) {
    uint32_t done;
    #pragma unroll 1
    for (int it = 0; it < (1 << 26); it++) {
        asm volatile("{.reg .pred p; mbarrier.try_wait.parity.shared::cta.b64 p, [%1], %2; selp.u32 %0, 1, 0, p;}"
                     : "=r"(done) : "r"(bar), "r"(parity) : "memory");
        if (done) return;
    }
    __trap();
}
__device__ __forceinline__ void bulk_g2s(uint32_t dst, const void* src, uint32_t bytes, uint32_t bar) {
    asm volatile("cp.async.bulk.shared::cluster.global.mbarrier::complete_tx::bytes [%0], [%1], %2, [%3];"
                 :: "r"(dst), "l"(src), "r"(bytes), "r"(bar) : "memory");
}
__device__ __forceinline__ void tma_2d(uint32_t dst, const CUtensorMap* map, int c0, int c1, uint32_t bar) {
    asm volatile("cp.async.bulk.tensor.2d.shared::cluster.global.mbarrier::complete_tx::bytes [%0], [%1, {%3, %4}], [%2];"
                 :: "r"(dst), "l"(map), "r"(bar), "r"(c0), "r"(c1) : "memory");
}
__device__ __forceinline__ void fence_async_smem() { asm volatile("fence.proxy.async.shared::cta;" ::: "memory"); }
__device__ __forceinline__ void named_bar(int id, int n) { asm volatile("bar.sync %0, %1;" :: "r"(id), "r"(n) : "memory"); }

__device__ __forceinline__ uint64_t make_desc(uint32_t saddr, uint32_t lbo, uint32_t sbo, uint32_t swz) {
    return (uint64_t)((saddr & 0x3FFFF) >> 4) | ((uint64_t)(lbo >> 4) << 16) | ((uint64_t)(sbo >> 4) << 32) | ((uint64_t)swz << 62);
}
#define WG_FENCE() asm volatile("wgmma.fence.sync.aligned;" ::: "memory")
#define WG_COMMIT() asm volatile("wgmma.commit_group.sync.aligned;" ::: "memory")
template <int N> __device__ __forceinline__ void wg_wait() { asm volatile("wgmma.wait_group.sync.aligned %0;" :: "n"(N) : "memory"); }

#define F4(d, o) "+f"(d[o]), "+f"(d[o + 1]), "+f"(d[o + 2]), "+f"(d[o + 3])
#define F16(d, o) F4(d, o), F4(d, o + 4), F4(d, o + 8), F4(d, o + 12)
#define F32(d, o) F16(d, o), F16(d, o + 16)

__device__ __forceinline__ void wgmma_n192(float* d, uint64_t da, uint64_t db) {
    asm volatile("wgmma.mma_async.sync.aligned.m64n192k16.f32.bf16.bf16 "
        "{%0,%1,%2,%3,%4,%5,%6,%7,%8,%9,%10,%11,%12,%13,%14,%15,%16,%17,%18,%19,%20,%21,%22,%23,%24,%25,%26,%27,%28,%29,%30,%31,"
        "%32,%33,%34,%35,%36,%37,%38,%39,%40,%41,%42,%43,%44,%45,%46,%47,%48,%49,%50,%51,%52,%53,%54,%55,%56,%57,%58,%59,%60,%61,%62,%63,"
        "%64,%65,%66,%67,%68,%69,%70,%71,%72,%73,%74,%75,%76,%77,%78,%79,%80,%81,%82,%83,%84,%85,%86,%87,%88,%89,%90,%91,%92,%93,%94,%95}, "
        "%96, %97, 1, 1, 1, 0, 1;\n"
        : F32(d, 0), F32(d, 32), F32(d, 64) : "l"(da), "l"(db));
}
__device__ __forceinline__ void wgmma_n64(float* d, uint64_t da, uint64_t db) {
    asm volatile("wgmma.mma_async.sync.aligned.m64n64k16.f32.bf16.bf16 "
        "{%0,%1,%2,%3,%4,%5,%6,%7,%8,%9,%10,%11,%12,%13,%14,%15,%16,%17,%18,%19,%20,%21,%22,%23,%24,%25,%26,%27,%28,%29,%30,%31}, "
        "%32, %33, 1, 1, 1, 0, 1;\n"
        : F32(d, 0) : "l"(da), "l"(db));
}
__device__ __forceinline__ void wgmma_qk32(float* d, uint32_t qd, uint32_t kd) {
    asm volatile("{.reg .b64 a, b; mov.b64 a, {%16, 16}; mov.b64 b, {%17, 16};\n"
        "wgmma.mma_async.sync.aligned.m64n32k16.f32.bf16.bf16 {%0,%1,%2,%3,%4,%5,%6,%7,%8,%9,%10,%11,%12,%13,%14,%15}, a, b, 0, 1, 1, 0, 0;}\n"
        : F16(d, 0) : "r"(qd), "r"(kd));
}
__device__ __forceinline__ void wgmma_pv(float* d, const uint32_t* a, uint32_t vd) {
    asm volatile("{.reg .b64 b; mov.b64 b, {%16, 2048};\n"
        "wgmma.mma_async.sync.aligned.m64n24k16.f32.bf16.bf16 {%0,%1,%2,%3,%4,%5,%6,%7,%8,%9,%10,%11}, {%12,%13,%14,%15}, b, 1, 1, 1, 1;}\n"
        : F4(d, 0), F4(d, 4), F4(d, 8) : "r"(a[0]), "r"(a[1]), "r"(a[2]), "r"(a[3]), "r"(vd));
}
__device__ __forceinline__ void touch16(float* d) { asm volatile("" : F16(d, 0) :: "memory"); }
__device__ __forceinline__ void touch12(float* d) { asm volatile("" : F4(d, 0), F4(d, 4), F4(d, 8) :: "memory"); }
__device__ __forceinline__ void touch32(float* d) { asm volatile("" : F32(d, 0) :: "memory"); }
__device__ __forceinline__ void touch96(float* d) { asm volatile("" : F32(d, 0), F32(d, 32), F32(d, 64) :: "memory"); }

__device__ __forceinline__ float ln_elem(float x, float mean_b, float rden) {
    return bf16r(bf16r(x - mean_b) * rden);
}
__device__ __forceinline__ void pdl_wait() { asm volatile("griddepcontrol.wait;" ::: "memory"); }
__device__ __forceinline__ void pdl_launch() { asm volatile("griddepcontrol.launch_dependents;" ::: "memory"); }
__device__ __forceinline__ void cluster_arrive() { asm volatile("barrier.cluster.arrive.release.aligned;" ::: "memory"); }
__device__ __forceinline__ void cluster_wait() { asm volatile("barrier.cluster.wait.acquire.aligned;" ::: "memory"); }

constexpr int K1_THREADS = 288;
constexpr int K1_SMEM = 131072 + 4 * 24576 + 256;

__device__ __forceinline__ void ldsm4(uint32_t* r, uint32_t addr) {
    asm volatile("ldmatrix.sync.aligned.m8n8.x4.shared.b16 {%0, %1, %2, %3}, [%4];" : "=r"(r[0]), "=r"(r[1]), "=r"(r[2]), "=r"(r[3]) : "r"(addr) : "memory");
}
__device__ __forceinline__ void stsm4(uint32_t addr, uint32_t r0, uint32_t r1, uint32_t r2, uint32_t r3) {
    asm volatile("stmatrix.sync.aligned.m8n8.x4.shared.b16 [%0], {%1, %2, %3, %4};" :: "r"(addr), "r"(r0), "r"(r1), "r"(r2), "r"(r3) : "memory");
}
__device__ __forceinline__ void mma16816(float* d, const uint32_t* a, uint32_t b0, uint32_t b1) {
    asm("mma.sync.aligned.m16n8k16.row.col.f32.bf16.bf16.f32 {%0,%1,%2,%3}, {%4,%5,%6,%7}, {%8,%9}, {%0,%1,%2,%3};"
        : "+f"(d[0]), "+f"(d[1]), "+f"(d[2]), "+f"(d[3]) : "r"(a[0]), "r"(a[1]), "r"(a[2]), "r"(a[3]), "r"(b0), "r"(b1));
}
__device__ __forceinline__ uint32_t sub_bf16x2(uint32_t a, uint32_t b) {
    uint32_t d; asm("sub.rn.bf16x2 %0, %1, %2;" : "=r"(d) : "r"(a), "r"(b)); return d;
}

__device__ __forceinline__ void k1_epilogue(const float* acc, float rs0, float rs1, uint32_t stage, int nt, int mt, int wg, int w4, int lane, bool live) {
    const int g8a = mt * 16 + wg * 8 + w4 * 2;
    const float rv0 = is_poly_group(g8a) ? -rs0 : rs0, rv1 = is_poly_group(g8a + 1) ? -rs1 : rs1;
    const int mi = lane >> 3, lr = lane & 7;
    const uint32_t off_qk = stage + (w4 * 2 + (mi & 1)) * 256 + (mi >> 1) * 128 + lr * 16;
    const uint32_t off_v = stage + (mi >> 1) * 1024 + (w4 * 16 + (mi & 1) * 8 + lr) * 16;
    #pragma unroll
    for (int jj = 0; jj < 12; jj++) {
        const bool isv = nt * 12 + jj >= 64;
        const float m0 = isv ? rv0 : rs0, m1 = isv ? rv1 : rs1;
        const uint32_t r0 = pack_bf16(acc[8 * jj] * m0, acc[8 * jj + 1] * m0), r1 = pack_bf16(acc[8 * jj + 2] * m1, acc[8 * jj + 3] * m1);
        const uint32_t r2 = pack_bf16(acc[8 * jj + 4] * m0, acc[8 * jj + 5] * m0), r3 = pack_bf16(acc[8 * jj + 6] * m1, acc[8 * jj + 7] * m1);
        const uint32_t addr = (isv ? off_v : off_qk) + (jj >> 2) * 16384 + (jj & 3) * 2048;
        if (live) stsm4(addr, r0, r1, r2, r3);
    }
    if (live) {
        fence_async_smem();
        named_bar(1 + wg, 128);
        const int pc = w4 * 6 + lane;
        if (lane < 6) {
            const int jj = pc >> 1, hf = pc & 1, hg = nt * 12 + jj;
            const unsigned char* dst = (const unsigned char*)g_QKV + (size_t)hg * 65536
                + (hg >= 64 ? hf * 32768 + (mt * 128 + wg * 64) * 16 : (mt * 16 + wg * 8) * 256 + hf * 1024);
            asm volatile("cp.async.bulk.global.shared::cta.bulk_group [%0], [%1], 1024;"
                         :: "l"(dst), "r"(stage + (jj >> 2) * 16384 + (jj & 3) * 2048 + hf * 1024) : "memory");
            asm volatile("cp.async.bulk.commit_group;" ::: "memory");
            asm volatile("cp.async.bulk.wait_group 0;" ::: "memory");
        }
    }
}

__global__ void __launch_bounds__(K1_THREADS, 1)
k1_ln_qkv(const __grid_constant__ CUtensorMap wmap, const __grid_constant__ CUtensorMap xmap, const __nv_bfloat16* __restrict__ w_r) {
    extern __shared__ __align__(1024) unsigned char smem[];
    const uint32_t sA = smem_u32(smem), sB = sA + 131072, sBar = sB + 4 * 24576;
    const int warp = __shfl_sync(~0u, threadIdx.x >> 5, 0), lane = threadIdx.x & 31;
    const int nt = blockIdx.x & 7, mt = blockIdx.x >> 3;
    const bool producer = warp == 8;
    const int wg = (warp >> 2) & 1;
    TL(0, 0);
    pdl_launch();
    if (threadIdx.x == 256) {
        for (int i = 0; i < 4; i++) { mbar_init(sBar + i * 8, 1); mbar_init(sBar + 32 + i * 8, 2); }
        mbar_init(sBar + 64, 1); mbar_init(sBar + 72, 1);
        asm volatile("fence.mbarrier_init.release.cluster;" ::: "memory");
        for (int hf = 0; hf < 2; hf++) {
            mbar_expect_tx(sBar + 64 + hf * 8, 65536);
            for (int pn = 0; pn < 8; pn++) tma_2d(sA + pn * 16384 + hf * 8192, &xmap, pn * 64, mt * 128 + hf * 64, sBar + 64 + hf * 8);
        }
    }
    __syncthreads();
    float acc[96];
    #pragma unroll
    for (int i = 0; i < 96; i++) acc[i] = 0.f;
    float rs0 = 0.f, rs1 = 0.f;
    if (producer) {
        if (lane == 0) {
            for (int kc = 0; kc < 8; kc++) {
                const int st = kc & 3;
                if (kc >= 4) mbar_wait(sBar + 32 + st * 8, 0);
                mbar_expect_tx(sBar + st * 8, 24576);
                for (int j = 0; j < 3; j++) tma_2d(sB + st * 24576 + j * 8192, &wmap, nt * 192 + j * 64, kc * 64, sBar + st * 8);
            }
        }
        __syncwarp();
    } else {
        const int g = lane >> 2, t = lane & 3;
        const int lrow = warp * 16 + (lane & 7) + ((lane >> 3) & 1) * 8;
        const uint32_t lbase = sA + lrow * 128;
        const int lsw = lane & 7, lhi = lane >> 4;
        const uint32_t* wr32 = (const uint32_t*)w_r;
        TL(0, 1);
        mbar_wait(sBar + 64 + wg * 8, 0);
        TL(0, 8);
        float dsum[4] = {0.f, 0.f, 0.f, 0.f}, dq0[4] = {0.f, 0.f, 0.f, 0.f}, dq1[4] = {0.f, 0.f, 0.f, 0.f};
        #pragma unroll 4
        for (int ks = 0; ks < 32; ks++) {
            uint32_t a[4];
            ldsm4(a, lbase + (ks >> 2) * 16384 + ((((ks & 3) * 2 + lhi) ^ lsw) * 16));
            mma16816(dsum, a, 0x3F803F80u, 0x3F803F80u);
            mma16816(dq0, a, a[0], a[2]);
            mma16816(dq1, a, a[1], a[3]);
        }
        const int dsrc = g * 4 + (g >> 1);
        float sq0 = __shfl_sync(~0u, (g & 1) ? dq0[1] : dq0[0], dsrc), sq1 = __shfl_sync(~0u, (g & 1) ? dq1[3] : dq1[2], dsrc);
        const float mean0 = dsum[0] * (1.0f / D_), mean1 = dsum[2] * (1.0f / D_);
        float var0 = fmaf(-mean0, mean0, sq0 * (1.0f / D_)), var1 = fmaf(-mean1, mean1, sq1 * (1.0f / D_));
        if (__any_sync(~0u, !(mean0 * mean0 <= 16.0f * var0) || !(mean1 * mean1 <= 16.0f * var1))) {
            float q0 = 0.f, q1 = 0.f;
            #pragma unroll 1
            for (int ks = 0; ks < 32; ks++) {
                uint32_t a[4];
                ldsm4(a, lbase + (ks >> 2) * 16384 + ((((ks & 3) * 2 + lhi) ^ lsw) * 16));
                #pragma unroll
                for (int i = 0; i < 4; i++) {
                    const float m = (i & 1) ? mean1 : mean0;
                    const float d0 = bf_lo(a[i]) - m, d1 = bf_hi(a[i]) - m;
                    if (i & 1) q1 = fmaf(d0, d0, fmaf(d1, d1, q1)); else q0 = fmaf(d0, d0, fmaf(d1, d1, q0));
                }
            }
            q0 += __shfl_xor_sync(~0u, q0, 1); q0 += __shfl_xor_sync(~0u, q0, 2);
            q1 += __shfl_xor_sync(~0u, q1, 1); q1 += __shfl_xor_sync(~0u, q1, 2);
            var0 = q0 * (1.0f / D_); var1 = q1 * (1.0f / D_);
        }
        rs0 = __frcp_rn(bf16r(__fsqrt_rn(bf16r(bf16r(var0) + 1e-5f))));
        rs1 = __frcp_rn(bf16r(__fsqrt_rn(bf16r(bf16r(var1) + 1e-5f))));
        const uint32_t m20 = pack_bf16(mean0, mean0), m21 = pack_bf16(mean1, mean1);
        float dr[4] = {0.f, 0.f, 0.f, 0.f};
        #pragma unroll 4
        for (int ks = 0; ks < 32; ks++) {
            uint32_t a[4];
            const uint32_t addr = lbase + (ks >> 2) * 16384 + ((((ks & 3) * 2 + lhi) ^ lsw) * 16);
            ldsm4(a, addr);
            a[0] = sub_bf16x2(a[0], m20); a[1] = sub_bf16x2(a[1], m21); a[2] = sub_bf16x2(a[2], m20); a[3] = sub_bf16x2(a[3], m21);
            stsm4(addr, a[0], a[1], a[2], a[3]);
            if (nt == 0) mma16816(dr, a, __ldg(wr32 + ks * 8 + t), __ldg(wr32 + ks * 8 + 4 + t));
        }
        if (nt == 0 && t == 0) {
            const int row = mt * 128 + warp * 16 + g;
            g_r[row] = bf16r(dr[0] * rs0); g_r[row + 8] = bf16r(dr[2] * rs1);
            g_stats[row] = make_float2(bf_lo(m20), rs0); g_stats[row + 8] = make_float2(bf_lo(m21), rs1);
        }
        TL(0, 2);
        fence_async_smem();
        named_bar(1 + wg, 128);
        TL(0, 3);
        const uint64_t da0 = make_desc(sA + wg * 8192, 16, 1024, 1);
        const uint64_t db0 = make_desc(sB, 8192, 1024, 1);
        #pragma unroll 1
        for (int kc = 0; kc < 8; kc++) {
            const int st = kc & 3;
            mbar_wait(sBar + st * 8, kc >> 2);
            WG_FENCE();
            #pragma unroll
            for (int kk = 0; kk < 4; kk++)
                wgmma_n192(acc, da0 + (uint64_t)(kc * 1024 + kk * 2), db0 + (uint64_t)(st * 1536 + kk * 128));
            WG_COMMIT();
            wg_wait<1>();
            if (kc >= 1 && kc <= 4 && (threadIdx.x & 127) == 0) mbar_arrive(sBar + 32 + (kc - 1) * 8);
        }
        wg_wait<0>();
        touch96(acc);
        named_bar(1 + wg, 128);
        TL(0, 5);
    }
    k1_epilogue(acc, rs0, rs1, sA + wg * 8192, nt, mt, wg, warp & 3, lane, !producer);
    TL(0, 6);
}

constexpr int K2_THREADS = 512;
constexpr int K2_SMEM = 65536 + 98304 + 16384 + 128;

constexpr float QS = 0.25f * 1.4426950408889634f;
__device__ __forceinline__ uint32_t polyexp(float s, float cb, uint32_t c421, float c3, float one) {
    float u;
    asm("fma.rn.sat.f32 %0, %1, %2, %3;" : "=f"(u) : "f"(s), "f"(QS * (1.0f / 255.0f)), "f"(cb));
    float z = fmaf(u, 0.99609375f, one);
    uint32_t rb;
    asm("lop3.b32 %0, %1, 0xFFFF8000, %2, 0xEA;" : "=r"(rb) : "r"(__float_as_uint(z)), "r"(c421));
    float f = z - __uint_as_float(rb);
    float h = fmaf(f, c3, 58.86525f);
    h = fmaf(f, h, -0.29870507f);
    return __float_as_uint(fmaf(f, h, z));
}

struct ExpC { float nm0, nm1, cb0, cb1, c3, one; uint32_t c421; };

template <int G>
__device__ __forceinline__ void exp_block(const float* s, uint32_t* p, const ExpC& c) {
    #pragma unroll
    for (int hf = 0; hf < 2; hf++) {
        const float* x = s + hf * 4;
        if ((PMASK >> (G + hf)) & 1) {
            p[hf * 2 + 0] = __byte_perm(polyexp(x[0], c.cb0, c.c421, c.c3, c.one), polyexp(x[1], c.cb0, c.c421, c.c3, c.one), 0x6521);
            p[hf * 2 + 1] = __byte_perm(polyexp(x[2], c.cb1, c.c421, c.c3, c.one), polyexp(x[3], c.cb1, c.c421, c.c3, c.one), 0x6521);
        } else {
            p[hf * 2 + 0] = pack_bf16(ex2(fmaf(x[0], QS, c.nm0)), ex2(fmaf(x[1], QS, c.nm0)));
            p[hf * 2 + 1] = pack_bf16(ex2(fmaf(x[2], QS, c.nm1)), ex2(fmaf(x[3], QS, c.nm1)));
        }
    }
}

__device__ __forceinline__ void max16(const float* s, float& mx0, float& mx1) {
    #pragma unroll
    for (int j = 0; j < 4; j++) {
        mx0 = fmaxf(mx0, fmaxf(s[4 * j], s[4 * j + 1]));
        mx1 = fmaxf(mx1, fmaxf(s[4 * j + 2], s[4 * j + 3]));
    }
}

__device__ void moe_cta(int part, unsigned char* smem, const __nv_bfloat16* __restrict__ x, const __nv_bfloat16* __restrict__ w_gate,
                        const __nv_bfloat16* __restrict__ w_up, const __nv_bfloat16* __restrict__ w_down) {
    float* xs = (float*)smem;
    float* red = xs + 1024;
    float* hs = red + 8 * 4 * 448;
    __shared__ float s_v[32];
    __shared__ int s_i[32];
    __shared__ int s_sel[2];
    const int tid = threadIdx.x, warp = tid >> 5, lane = tid & 31;
    for (int pass = 0; pass < 2; pass++) {
        float bv = -INFINITY; int bi = 0x7fffffff;
        const int excl = pass ? s_sel[0] : -1;
        for (int i = tid; i < S_; i += K2_THREADS) {
            float v = g_r[i];
            if (i != excl && (v > bv || (v == bv && i < bi) || bi == 0x7fffffff)) { bv = v; bi = i; }
        }
        #pragma unroll
        for (int o = 16; o; o >>= 1) {
            float ov = __shfl_xor_sync(~0u, bv, o); int oi = __shfl_xor_sync(~0u, bi, o);
            if (ov > bv || (ov == bv && oi < bi)) { bv = ov; bi = oi; }
        }
        if (lane == 0) { s_v[warp] = bv; s_i[warp] = bi; }
        __syncthreads();
        if (warp == 0) {
            bv = lane < 16 ? s_v[lane] : -INFINITY; bi = lane < 16 ? s_i[lane] : 0x7fffffff;
            #pragma unroll
            for (int o = 16; o; o >>= 1) {
                float ov = __shfl_xor_sync(~0u, bv, o); int oi = __shfl_xor_sync(~0u, bi, o);
                if (ov > bv || (ov == bv && oi < bi)) { bv = ov; bi = oi; }
            }
            if (lane == 0) s_sel[pass] = (bi == 0x7fffffff) ? pass : bi;
        }
        __syncthreads();
    }
    for (int i = tid; i < 1024; i += K2_THREADS) {
        const int tok = s_sel[i >> 9];
        const float2 st = g_stats[tok];
        xs[i] = ln_elem(__bfloat162float(x[(size_t)tok * D_ + (i & 511)]), st.x, st.y);
    }
    if (part == 0 && tid < 2) g_sel[tid] = s_sel[tid];
    __syncthreads();
    const int c0 = part * 448;
    if (tid < 448) {
        const int cg = tid % 56, ks = tid / 56;
        float a[4][8];
        #pragma unroll
        for (int i = 0; i < 4; i++)
            #pragma unroll
            for (int j = 0; j < 8; j++) a[i][j] = 0.f;
        const __nv_bfloat16* pg = w_gate + (size_t)(ks * 64) * F_ + c0 + cg * 8;
        const __nv_bfloat16* pu = w_up + (size_t)(ks * 64) * F_ + c0 + cg * 8;
        #pragma unroll 8
        for (int k = 0; k < 64; k++) {
            const uint4 gv = __ldg((const uint4*)(pg + (size_t)k * F_));
            const uint4 uv = __ldg((const uint4*)(pu + (size_t)k * F_));
            const float x0 = xs[ks * 64 + k], x1 = xs[512 + ks * 64 + k];
            const uint32_t gu[4] = {gv.x, gv.y, gv.z, gv.w}, uu[4] = {uv.x, uv.y, uv.z, uv.w};
            #pragma unroll
            for (int j = 0; j < 4; j++) {
                const float g0 = bf_lo(gu[j]), g1 = bf_hi(gu[j]), u0 = bf_lo(uu[j]), u1 = bf_hi(uu[j]);
                a[0][2 * j] = fmaf(x0, g0, a[0][2 * j]); a[0][2 * j + 1] = fmaf(x0, g1, a[0][2 * j + 1]);
                a[1][2 * j] = fmaf(x1, g0, a[1][2 * j]); a[1][2 * j + 1] = fmaf(x1, g1, a[1][2 * j + 1]);
                a[2][2 * j] = fmaf(x0, u0, a[2][2 * j]); a[2][2 * j + 1] = fmaf(x0, u1, a[2][2 * j + 1]);
                a[3][2 * j] = fmaf(x1, u0, a[3][2 * j]); a[3][2 * j + 1] = fmaf(x1, u1, a[3][2 * j + 1]);
            }
        }
        #pragma unroll
        for (int i = 0; i < 4; i++)
            #pragma unroll
            for (int j = 0; j < 8; j++) red[(ks * 4 + i) * 448 + cg * 8 + j] = a[i][j];
    }
    __syncthreads();
    for (int i = tid; i < 896; i += K2_THREADS) {
        const int tok = i / 448, c = i % 448;
        float gs = 0.f, us = 0.f;
        #pragma unroll
        for (int ks = 0; ks < 8; ks++) { gs += red[(ks * 4 + tok) * 448 + c]; us += red[(ks * 4 + 2 + tok) * 448 + c]; }
        gs = bf16r(gs); us = bf16r(us);
        const float sl = bf16r(gs / (1.0f + __expf(-gs)));
        hs[i] = bf16r(sl * us);
    }
    __syncthreads();
    {
        const int cg = tid & 63, fs = tid >> 6;
        float a[2][8];
        #pragma unroll
        for (int j = 0; j < 8; j++) { a[0][j] = 0.f; a[1][j] = 0.f; }
        const __nv_bfloat16* pd = w_down + (size_t)(c0 + fs * 56) * D_ + cg * 8;
        #pragma unroll 8
        for (int f = 0; f < 56; f++) {
            const uint4 dv = __ldg((const uint4*)(pd + (size_t)f * D_));
            const float h0 = hs[fs * 56 + f], h1 = hs[448 + fs * 56 + f];
            const uint32_t du[4] = {dv.x, dv.y, dv.z, dv.w};
            #pragma unroll
            for (int j = 0; j < 4; j++) {
                const float d0 = bf_lo(du[j]), d1 = bf_hi(du[j]);
                a[0][2 * j] = fmaf(h0, d0, a[0][2 * j]); a[0][2 * j + 1] = fmaf(h0, d1, a[0][2 * j + 1]);
                a[1][2 * j] = fmaf(h1, d0, a[1][2 * j]); a[1][2 * j + 1] = fmaf(h1, d1, a[1][2 * j + 1]);
            }
        }
        #pragma unroll
        for (int j = 0; j < 8; j++) { red[(fs * 2) * 512 + cg * 8 + j] = a[0][j]; red[(fs * 2 + 1) * 512 + cg * 8 + j] = a[1][j]; }
    }
    __syncthreads();
    for (int i = tid; i < 1024; i += K2_THREADS) {
        float s = 0.f;
        #pragma unroll
        for (int fs = 0; fs < 8; fs++) s += red[(fs * 2 + (i >> 9)) * 512 + (i & 511)];
        g_ypart[part][i >> 9][i & 511] = s;
    }
}

__global__ void __launch_bounds__(K2_THREADS, 1)
k2_attn(const __nv_bfloat16* __restrict__ x, const __nv_bfloat16* __restrict__ w_gate, const __nv_bfloat16* __restrict__ w_up,
        const __nv_bfloat16* __restrict__ w_down) {
    extern __shared__ __align__(1024) unsigned char smem[];
    TL(1, 0);
    pdl_launch();
    if (blockIdx.x >= 128) {
        const int part = blockIdx.x - 128;
        {
            const int k = threadIdx.x;
            asm volatile("cp.async.bulk.prefetch.L2.global [%0], %1;" :: "l"(w_gate + (size_t)k * F_ + part * 448), "r"(896) : "memory");
            asm volatile("cp.async.bulk.prefetch.L2.global [%0], %1;" :: "l"(w_up + (size_t)k * F_ + part * 448), "r"(896) : "memory");
            if (k < 56) asm volatile("cp.async.bulk.prefetch.L2.global [%0], %1;" :: "l"(w_down + (size_t)(part * 448 + k * 8) * D_), "r"(8192) : "memory");
        }
        pdl_wait(); TL(1, 1); moe_cta(blockIdx.x - 128, smem, x, w_gate, w_up, w_down); TL(1, 2); return; }
    const uint32_t sK = smem_u32(smem), sV = sK + 65536, sQ = sV + 98304, sBar = sQ + 16384;
    const int h = blockIdx.x >> 2, qb = blockIdx.x & 3;
    const int warp = __shfl_sync(~0u, threadIdx.x >> 5, 0), lane = threadIdx.x & 31, wg = warp >> 2;
    if (threadIdx.x == 0) {
        mbar_init(sBar, 1); mbar_init(sBar + 8, 1);
        asm volatile("fence.mbarrier_init.release.cluster;" ::: "memory");
        pdl_wait();
        TL(1, 1);
        const uint4* gk = g_K + (size_t)h * 4096;
        const uint4* gv = g_V + (size_t)h * 4096;
        mbar_expect_tx(sBar, 16384 + 16384 + 2 * 8192);
        bulk_g2s(sQ, g_Q + (size_t)h * 4096 + qb * 1024, 16384, sBar);
        bulk_g2s(sK, gk, 16384, sBar);
        bulk_g2s(sV, gv, 8192, sBar);
        bulk_g2s(sV + 32768, gv + 2048, 8192, sBar);
        mbar_expect_tx(sBar + 8, 49152 + 2 * 24576);
        bulk_g2s(sK + 16384, gk + 1024, 49152, sBar + 8);
        bulk_g2s(sV + 8192, gv + 512, 24576, sBar + 8);
        bulk_g2s(sV + 32768 + 8192, gv + 2048 + 512, 24576, sBar + 8);
    }
    for (int i = threadIdx.x; i < 2048; i += K2_THREADS) {
        const uint32_t v = is_poly_group(i >> 3) ? 0xBF80BF80u : 0x3F803F80u;
        *(uint4*)(smem + 65536 + 65536 + i * 16) = make_uint4(v, v, v, v);
    }
    fence_async_smem();
    __syncthreads();
    ExpC c;
    {
        const volatile uint32_t* cc = g_const;
        c.c421 = cc[0]; c.c3 = __uint_as_float(cc[1]); c.one = __uint_as_float(cc[2]);
    }
    const uint32_t kdesc0 = (uint32_t)make_desc(sK, 128, 256, 0);
    const uint32_t vdesc0 = (uint32_t)make_desc(sV, 128, 32768, 0);
    mbar_wait(sBar, 0);
    TL(1, 2);
    #pragma unroll 1
    for (int pass = 0; pass < 2; pass++) {
        const int unit = pass * 4 + wg;
        const uint32_t q = (uint32_t)make_desc(sQ + unit * 2048, 128, 256, 0);
        float o[12];
        #pragma unroll 1
        for (int attempt = 0; attempt < 2; attempt++) {
            float s0[16], s1[16], s2[16];
            #pragma unroll
            for (int i = 0; i < 16; i++) { s0[i] = 0.f; s1[i] = 0.f; s2[i] = 0.f; }
            float mx0 = -INFINITY, mx1 = -INFINITY;
            if (attempt) {
                #pragma unroll 1
                for (int it = 0; it < 64; it++) {
                    WG_FENCE();
                    wgmma_qk32(s0, q, kdesc0 + it * 64);
                    WG_COMMIT();
                    wg_wait<0>();
                    touch16(s0);
                    max16(s0, mx0, mx1);
                }
            }
            #pragma unroll
            for (int i = 0; i < 12; i++) o[i] = 0.f;
            WG_FENCE();
            wgmma_qk32(s2, q, kdesc0);
            wgmma_qk32(s0, q, kdesc0 + 64);
            wgmma_qk32(s1, q, kdesc0 + 128);
            WG_COMMIT();
            wg_wait<0>();
            touch16(s0); touch16(s1); touch16(s2);
            max16(s0, mx0, mx1); max16(s1, mx0, mx1); max16(s2, mx0, mx1);
            mx0 = fmaxf(mx0, __shfl_xor_sync(~0u, mx0, 1)); mx0 = fmaxf(mx0, __shfl_xor_sync(~0u, mx0, 2));
            mx1 = fmaxf(mx1, __shfl_xor_sync(~0u, mx1, 1)); mx1 = fmaxf(mx1, __shfl_xor_sync(~0u, mx1, 2));
            const float bias = attempt ? 0.0f : 64.0f;
            c.nm0 = __shfl_sync(~0u, -fmaf(mx0, QS, bias), lane); c.nm1 = __shfl_sync(~0u, -fmaf(mx1, QS, bias), lane);
            c.cb0 = __shfl_sync(~0u, (127.0f + c.nm0) * (1.0f / 255.0f), lane);
            c.cb1 = __shfl_sync(~0u, (127.0f + c.nm1) * (1.0f / 255.0f), lane);
            uint32_t kd = kdesc0 + 192, vd = vdesc0 + 32;
            {
                uint32_t pa[4], pb[4];
                exp_block<12>(s2, pa, c);
                exp_block<14>(s2 + 8, pb, c);
                WG_FENCE();
                wgmma_pv(o, pa, vdesc0); wgmma_pv(o, pb, vdesc0 + 16);
                WG_COMMIT();
            }
            #pragma unroll 1
            for (int seg = 0; seg < 2; seg++) {
            if (seg) { wg_wait<0>(); mbar_wait(sBar + 8, 0); __syncwarp(); }
            #pragma unroll 1
            for (int it = seg ? 3 : 0; it < (seg ? 21 : 3); it++) {
                uint32_t p[6][4];
                WG_FENCE();
                wgmma_qk32(s2, q, kd);
                WG_COMMIT();
                exp_block<0>(s0, p[0], c);
                exp_block<2>(s0 + 8, p[1], c);
                WG_FENCE();
                wgmma_pv(o, p[0], vd); wgmma_pv(o, p[1], vd + 16);
                wgmma_qk32(s0, q, kd + 64);
                WG_COMMIT();
                wg_wait<1>();
                touch16(s2);
                exp_block<4>(s1, p[2], c);
                exp_block<6>(s1 + 8, p[3], c);
                WG_FENCE();
                wgmma_pv(o, p[2], vd + 32); wgmma_pv(o, p[3], vd + 48);
                wgmma_qk32(s1, q, kd + 128);
                WG_COMMIT();
                wg_wait<1>();
                touch16(s0);
                exp_block<8>(s2, p[4], c);
                exp_block<10>(s2 + 8, p[5], c);
                WG_FENCE();
                wgmma_pv(o, p[4], vd + 64); wgmma_pv(o, p[5], vd + 80);
                WG_COMMIT();
                vd += 96; kd += 192;
                wg_wait<1>();
                touch16(s1);
            }
            }
            wg_wait<0>();
            touch12(o);
            if (attempt) break;
            float big = 0.f;
            #pragma unroll
            for (int i = 0; i < 12; i++) big = fmaxf(big, fabsf(o[i]));
            bool bad = !(big < 1e30f);
            #pragma unroll
            for (int i = 0; i < 12; i++) bad |= (o[i] != o[i]);
            uint32_t any;
            asm volatile("{.reg .pred p, q; setp.ne.u32 p, %1, 0; barrier.cta.red.or.pred.aligned q, %2, 128, p; selp.u32 %0, 1, 0, q;}"
                         : "=r"(any) : "r"((uint32_t)bad), "r"(1 + wg) : "memory");
            if (!__any_sync(~0u, any)) break;
        }
        const int g = lane >> 2, t = lane & 3;
        const int r = (warp & 3) * 16 + g;
        const float i0 = __fdiv_rn(1.0f, o[8]), i1 = __fdiv_rn(1.0f, o[10]);
        uint32_t* ob = (uint32_t*)(g_O + (size_t)(qb * 8 + unit) * 4096 + (h >> 2) * 512 + r * 8) + t;
        const int c0 = ((h & 3) * 2) ^ (r & 7), c1 = ((h & 3) * 2 + 1) ^ (r & 7);
        ob[c0 * 4] = pack_bf16(o[0] * i0, o[1] * i0);
        ob[c1 * 4] = pack_bf16(o[4] * i0, o[5] * i0);
        ob[256 + c0 * 4] = pack_bf16(o[2] * i1, o[3] * i1);
        ob[256 + c1 * 4] = pack_bf16(o[6] * i1, o[7] * i1);
        TL(1, 3 + pass);
    }
}

constexpr int K3_THREADS = 256;
constexpr int K3_SMEM = 65536 + 131072 + 128;

__global__ void __launch_bounds__(K3_THREADS, 1)
k3_out(const __grid_constant__ CUtensorMap wmap, const __nv_bfloat16* __restrict__ x, __nv_bfloat16* __restrict__ out) {
    extern __shared__ __align__(1024) unsigned char smem[];
    const uint32_t sA = smem_u32(smem), sB = sA + 65536, sBar = sB + 131072;
    const int warp = __shfl_sync(~0u, threadIdx.x >> 5, 0), lane = threadIdx.x & 31, wg = warp >> 2;
    const int nt = blockIdx.x & 3, mt = blockIdx.x >> 2;
    TL(2, 0);
    if (threadIdx.x == 0) {
        for (int i = 0; i < 6; i++) mbar_init(sBar + i * 8, 1);
        asm volatile("fence.mbarrier_init.release.cluster;" ::: "memory");
        for (int kh = 0; kh < 2; kh++) {
            mbar_expect_tx(sBar + kh * 8, 65536);
            tma_2d(sB + kh * 32768, &wmap, nt * 128, kh * 256, sBar + kh * 8);
            tma_2d(sB + 65536 + kh * 32768, &wmap, nt * 128 + 64, kh * 256, sBar + kh * 8);
        }
    }
    const int er = threadIdx.x >> 2, ec = (threadIdx.x & 3) * 32;
    const int row = mt * 64 + er;
    uint4 xv[4];
    #pragma unroll
    for (int j = 0; j < 4; j++) xv[j] = __ldg((const uint4*)(x + (size_t)row * D_ + nt * 128 + ec) + j);
    pdl_wait();
    TL(2, 1);
    if (threadIdx.x == 0) {
        for (int q = 0; q < 4; q++) {
            mbar_expect_tx(sBar + 16 + q * 8, 16384);
            bulk_g2s(sA + q * 16384, g_O + (size_t)mt * 4096 + q * 1024, 16384, sBar + 16 + q * 8);
        }
    }
    const int sel0 = g_sel[0], sel1 = g_sel[1];
    const float2 st = g_stats[row];
    uint32_t bb[16];
    {
        const uint32_t xu[16] = {xv[0].x, xv[0].y, xv[0].z, xv[0].w, xv[1].x, xv[1].y, xv[1].z, xv[1].w,
                                 xv[2].x, xv[2].y, xv[2].z, xv[2].w, xv[3].x, xv[3].y, xv[3].z, xv[3].w};
        #pragma unroll
        for (int j = 0; j < 16; j++) bb[j] = pack_bf16(bf16r(bf_lo(xu[j]) - st.x) * st.y, bf16r(bf_hi(xu[j]) - st.x) * st.y);
        const int slot = row == sel0 ? 0 : (row == sel1 ? 1 : -1);
        if (slot >= 0) {
            const float gate = bf16r(1.0f / (1.0f + __expf(-g_r[row])));
            const int c0 = nt * 128 + ec;
            #pragma unroll
            for (int j = 0; j < 16; j++) {
                const float2 a = *(const float2*)&g_ypart[0][slot][c0 + 2 * j], b = *(const float2*)&g_ypart[1][slot][c0 + 2 * j];
                const float2 c = *(const float2*)&g_ypart[2][slot][c0 + 2 * j], d = *(const float2*)&g_ypart[3][slot][c0 + 2 * j];
                bb[j] = pack_bf16(bf_lo(bb[j]) + bf16r(bf16r(a.x + b.x + c.x + d.x) * gate), bf_hi(bb[j]) + bf16r(bf16r(a.y + b.y + c.y + d.y) * gate));
            }
        }
    }
    __syncthreads();
    float acc[32];
    #pragma unroll
    for (int i = 0; i < 32; i++) acc[i] = 0.f;
    const uint64_t da0 = make_desc(sA, 16, 1024, 1);
    const uint64_t db0 = make_desc(sB + wg * 65536, 8192, 1024, 1);
    #pragma unroll 1
    for (int q = 0; q < 4; q++) {
        if ((q & 1) == 0) mbar_wait(sBar + (q >> 1) * 8, 0);
        mbar_wait(sBar + 16 + q * 8, 0);
        WG_FENCE();
        #pragma unroll
        for (int kk = 0; kk < 8; kk++)
            wgmma_n64(acc, da0 + (uint64_t)(q * 1024 + (kk >> 2) * 512 + (kk & 3) * 2), db0 + (uint64_t)(q * 1024 + kk * 128));
        WG_COMMIT();
    }
    wg_wait<0>();
    touch32(acc);
    TL(2, 2);
    __syncthreads();
    {
        const int g = lane >> 2, t = lane & 3;
        unsigned char* sp = smem + ((warp & 3) * 16 + g) * 272 + wg * 128 + t * 4;
        #pragma unroll
        for (int j = 0; j < 8; j++) {
            *(uint32_t*)(sp + j * 16) = pack_bf16(acc[4 * j], acc[4 * j + 1]);
            *(uint32_t*)(sp + 8 * 272 + j * 16) = pack_bf16(acc[4 * j + 2], acc[4 * j + 3]);
        }
    }
    __syncthreads();
    #pragma unroll
    for (int j = 0; j < 4; j++) {
        const uint4 av = *(const uint4*)(smem + er * 272 + ec * 2 + j * 16);
        const uint32_t au[4] = {av.x, av.y, av.z, av.w}, xu[4] = {xv[j].x, xv[j].y, xv[j].z, xv[j].w};
        uint32_t o[4];
        #pragma unroll
        for (int i = 0; i < 4; i++) {
            uint32_t t2;
            asm("add.rn.bf16x2 %0, %1, %2;" : "=r"(t2) : "r"(xu[i]), "r"(au[i]));
            asm("add.rn.bf16x2 %0, %1, %2;" : "=r"(o[i]) : "r"(t2), "r"(bb[j * 4 + i]));
        }
        *((uint4*)(out + (size_t)row * D_ + nt * 128 + ec) + j) = make_uint4(o[0], o[1], o[2], o[3]);
    }
    TL(2, 3);
}

typedef CUresult (*EncodeFn)(CUtensorMap*, CUtensorMapDataType, cuuint32_t, void*, const cuuint64_t*, const cuuint64_t*,
                             const cuuint32_t*, const cuuint32_t*, CUtensorMapInterleave, CUtensorMapSwizzle,
                             CUtensorMapL2promotion, CUtensorMapFloatOOBfill);

void make_wmap(EncodeFn fn, CUtensorMap* map, const void* ptr, int rows, int cols, int box_rows) {
    cuuint64_t dims[2] = {(cuuint64_t)cols, (cuuint64_t)rows};
    cuuint64_t strides[1] = {(cuuint64_t)cols * 2};
    cuuint32_t box[2] = {64, (cuuint32_t)box_rows};
    cuuint32_t es[2] = {1, 1};
    fn(map, CU_TENSOR_MAP_DATA_TYPE_BFLOAT16, 2, (void*)ptr, dims, strides, box, es, CU_TENSOR_MAP_INTERLEAVE_NONE,
       CU_TENSOR_MAP_SWIZZLE_128B, CU_TENSOR_MAP_L2_PROMOTION_L2_256B, CU_TENSOR_MAP_FLOAT_OOB_FILL_NONE);
}

}

extern "C" void kernel_launch(void* const* d_in, const int* in_sizes, int n_in, void* d_out, int out_size) {
    const __nv_bfloat16* x = (const __nv_bfloat16*)d_in[0];
    const __nv_bfloat16* wqkv = (const __nv_bfloat16*)d_in[1];
    const __nv_bfloat16* wo = (const __nv_bfloat16*)d_in[2];
    const __nv_bfloat16* w_r = (const __nv_bfloat16*)d_in[4];
    const __nv_bfloat16* w_gate = (const __nv_bfloat16*)d_in[5];
    const __nv_bfloat16* w_up = (const __nv_bfloat16*)d_in[6];
    const __nv_bfloat16* w_down = (const __nv_bfloat16*)d_in[7];
    __nv_bfloat16* out = (__nv_bfloat16*)d_out;

    static EncodeFn encode = nullptr;
    if (!encode) {
        void* fn = nullptr;
        cudaDriverEntryPointQueryResult qres;
        cudaGetDriverEntryPoint("cuTensorMapEncodeTiled", &fn, cudaEnableDefault, &qres);
        encode = (EncodeFn)fn;
        cudaFuncSetAttribute(k1_ln_qkv, cudaFuncAttributeMaxDynamicSharedMemorySize, K1_SMEM);
        cudaFuncSetAttribute(k2_attn, cudaFuncAttributeMaxDynamicSharedMemorySize, K2_SMEM);
        cudaFuncSetAttribute(k3_out, cudaFuncAttributeMaxDynamicSharedMemorySize, K3_SMEM);
    }
    CUtensorMap map_qkv, map_wo, map_x;
    make_wmap(encode, &map_x, x, S_, D_, 64);
    make_wmap(encode, &map_qkv, wqkv, D_, 3 * D_, 64);
    make_wmap(encode, &map_wo, wo, D_, D_, 256);

    k1_ln_qkv<<<128, K1_THREADS, K1_SMEM, cudaStreamPerThread>>>(map_qkv, map_x, w_r);
    cudaLaunchAttribute at[1];
    at[0].id = cudaLaunchAttributeProgrammaticStreamSerialization;
    at[0].val.programmaticStreamSerializationAllowed = 1;
    cudaLaunchConfig_t cfg = {};
    cfg.stream = cudaStreamPerThread;
    cfg.attrs = at; cfg.numAttrs = 1;
    cfg.gridDim = dim3(132); cfg.blockDim = dim3(K2_THREADS); cfg.dynamicSmemBytes = K2_SMEM;
    cudaLaunchKernelEx(&cfg, k2_attn, x, w_gate, w_up, w_down);
    cfg.gridDim = dim3(128); cfg.blockDim = dim3(K3_THREADS); cfg.dynamicSmemBytes = K3_SMEM;
    cudaLaunchKernelEx(&cfg, k3_out, map_wo, x, out);
}
```

```cpp
#include <cuda_runtime.h>
#include <cuda_bf16.h>
#include <cuda.h>
#include <stdint.h>

namespace {

constexpr int S_ = 2048, D_ = 512, H_ = 32, F_ = 1792;

constexpr uint32_t PMASK = 0xA52;
__host__ __device__ constexpr bool is_poly_group(int g8) { return g8 >= 4 && ((PMASK >> ((g8 - 4) % 12)) & 1); }

__device__ __align__(1024) uint4 g_QKV[3 * H_ * S_ * 2];
#define g_Q (g_QKV)
#define g_K (g_QKV + H_ * S_ * 2)
#define g_V (g_QKV + 2 * H_ * S_ * 2)
__device__ __align__(1024) uint4 g_O[S_ * D_ / 8];
__device__ float2 g_stats[S_];
__device__ uint32_t g_const[4] = {421u, 0x459EB285u  , 0x3F800000u  , 0u};
__device__ float g_r[S_];
__device__ __align__(16) float g_ypart[4][2][D_];
__device__ int g_sel[2];

#define TL(k, p)
__device__ __forceinline__ uint32_t smem_u32(const void* p) { return (uint32_t)__cvta_generic_to_shared(p); }
__device__ __forceinline__ float bf16r(float x) { return __bfloat162float(__float2bfloat16_rn(x)); }
__device__ __forceinline__ uint32_t pack_bf16(float lo, float hi) {
    uint32_t r; asm("cvt.rn.bf16x2.f32 %0, %1, %2;" : "=r"(r) : "f"(hi), "f"(lo)); return r;
}
__device__ __forceinline__ float bf_lo(uint32_t u) { return __uint_as_float(u << 16); }
__device__ __forceinline__ float bf_hi(uint32_t u) { return __uint_as_float(u & 0xFFFF0000u); }
__device__ __forceinline__ float ex2(float x) { float y; asm("ex2.approx.ftz.f32 %0, %1;" : "=f"(y) : "f"(x)); return y; }

__device__ __forceinline__ void mbar_init(uint32_t bar, uint32_t count) {
    asm volatile("mbarrier.init.shared::cta.b64 [%0], %1;" :: "r"(bar), "r"(count) : "memory");
}
__device__ __forceinline__ void mbar_expect_tx(uint32_t bar, uint32_t bytes) {
    asm volatile("mbarrier.arrive.expect_tx.shared::cta.b64 _, [%0], %1;" :: "r"(bar), "r"(bytes) : "memory");
}
__device__ __forceinline__ void mbar_arrive(uint32_t bar) {
    asm volatile("mbarrier.arrive.shared::cta.b64 _, [%0];" :: "r"(bar) : "memory");
}
__device__ __forceinline__ void mbar_wait(uint32_t bar, uint32_t parity) {
    uint32_t done;
    #pragma unroll 1
    for (int it = 0; it < (1 << 26); it++) {
        asm volatile("{.reg .pred p; mbarrier.try_wait.parity.shared::cta.b64 p, [%1], %2; selp.u32 %0, 1, 0, p;}"
                     : "=r"(done) : "r"(bar), "r"(parity) : "memory");
        if (done) return;
    }
    __trap();
}
__device__ __forceinline__ void bulk_g2s(uint32_t dst, const void* src, uint32_t bytes, uint32_t bar) {
    asm volatile("cp.async.bulk.shared::cluster.global.mbarrier::complete_tx::bytes [%0], [%1], %2, [%3];"
                 :: "r"(dst), "l"(src), "r"(bytes), "r"(bar) : "memory");
}
__device__ __forceinline__ void tma_2d(uint32_t dst, const CUtensorMap* map, int c0, int c1, uint32_t bar) {
    asm volatile("cp.async.bulk.tensor.2d.shared::cluster.global.mbarrier::complete_tx::bytes [%0], [%1, {%3, %4}], [%2];"
                 :: "r"(dst), "l"(map), "r"(bar), "r"(c0), "r"(c1) : "memory");
}
__device__ __forceinline__ void fence_async_smem() { asm volatile("fence.proxy.async.shared::cta;" ::: "memory"); }
__device__ __forceinline__ void named_bar(int id, int n) { asm volatile("bar.sync %0, %1;" :: "r"(id), "r"(n) : "memory"); }

__device__ __forceinline__ uint64_t make_desc(uint32_t saddr, uint32_t lbo, uint32_t sbo, uint32_t swz) {
    return (uint64_t)((saddr & 0x3FFFF) >> 4) | ((uint64_t)(lbo >> 4) << 16) | ((uint64_t)(sbo >> 4) << 32) | ((uint64_t)swz << 62);
}
#define WG_FENCE() asm volatile("wgmma.fence.sync.aligned;" ::: "memory")
#define WG_COMMIT() asm volatile("wgmma.commit_group.sync.aligned;" ::: "memory")
template <int N> __device__ __forceinline__ void wg_wait() { asm volatile("wgmma.wait_group.sync.aligned %0;" :: "n"(N) : "memory"); }

#define F4(d, o) "+f"(d[o]), "+f"(d[o + 1]), "+f"(d[o + 2]), "+f"(d[o + 3])
#define F16(d, o) F4(d, o), F4(d, o + 4), F4(d, o + 8), F4(d, o + 12)
#define F32(d, o) F16(d, o), F16(d, o + 16)

__device__ __forceinline__ void wgmma_n192(float* d, uint64_t da, uint64_t db) {
    asm volatile("wgmma.mma_async.sync.aligned.m64n192k16.f32.bf16.bf16 "
        "{%0,%1,%2,%3,%4,%5,%6,%7,%8,%9,%10,%11,%12,%13,%14,%15,%16,%17,%18,%19,%20,%21,%22,%23,%24,%25,%26,%27,%28,%29,%30,%31,"
        "%32,%33,%34,%35,%36,%37,%38,%39,%40,%41,%42,%43,%44,%45,%46,%47,%48,%49,%50,%51,%52,%53,%54,%55,%56,%57,%58,%59,%60,%61,%62,%63,"
        "%64,%65,%66,%67,%68,%69,%70,%71,%72,%73,%74,%75,%76,%77,%78,%79,%80,%81,%82,%83,%84,%85,%86,%87,%88,%89,%90,%91,%92,%93,%94,%95}, "
        "%96, %97, 1, 1, 1, 0, 1;\n"
        : F32(d, 0), F32(d, 32), F32(d, 64) : "l"(da), "l"(db));
}
__device__ __forceinline__ void wgmma_n64(float* d, uint64_t da, uint64_t db) {
    asm volatile("wgmma.mma_async.sync.aligned.m64n64k16.f32.bf16.bf16 "
        "{%0,%1,%2,%3,%4,%5,%6,%7,%8,%9,%10,%11,%12,%13,%14,%15,%16,%17,%18,%19,%20,%21,%22,%23,%24,%25,%26,%27,%28,%29,%30,%31}, "
        "%32, %33, 1, 1, 1, 0, 1;\n"
        : F32(d, 0) : "l"(da), "l"(db));
}
__device__ __forceinline__ void wgmma_qk32(float* d, uint32_t qd, uint32_t kd) {
    asm volatile("{.reg .b64 a, b; mov.b64 a, {%16, 16}; mov.b64 b, {%17, 16};\n"
        "wgmma.mma_async.sync.aligned.m64n32k16.f32.bf16.bf16 {%0,%1,%2,%3,%4,%5,%6,%7,%8,%9,%10,%11,%12,%13,%14,%15}, a, b, 0, 1, 1, 0, 0;}\n"
        : F16(d, 0) : "r"(qd), "r"(kd));
}
__device__ __forceinline__ void wgmma_pv(float* d, const uint32_t* a, uint32_t vd) {
    asm volatile("{.reg .b64 b; mov.b64 b, {%16, 2048};\n"
        "wgmma.mma_async.sync.aligned.m64n24k16.f32.bf16.bf16 {%0,%1,%2,%3,%4,%5,%6,%7,%8,%9,%10,%11}, {%12,%13,%14,%15}, b, 1, 1, 1, 1;}\n"
        : F4(d, 0), F4(d, 4), F4(d, 8) : "r"(a[0]), "r"(a[1]), "r"(a[2]), "r"(a[3]), "r"(vd));
}
__device__ __forceinline__ void touch16(float* d) { asm volatile("" : F16(d, 0) :: "memory"); }
__device__ __forceinline__ void touch12(float* d) { asm volatile("" : F4(d, 0), F4(d, 4), F4(d, 8) :: "memory"); }
__device__ __forceinline__ void touch32(float* d) { asm volatile("" : F32(d, 0) :: "memory"); }
__device__ __forceinline__ void touch96(float* d) { asm volatile("" : F32(d, 0), F32(d, 32), F32(d, 64) :: "memory"); }

__device__ __forceinline__ float ln_elem(float x, float mean_b, float rden) {
    return bf16r(bf16r(x - mean_b) * rden);
}
__device__ __forceinline__ void pdl_wait() { asm volatile("griddepcontrol.wait;" ::: "memory"); }
__device__ __forceinline__ void pdl_launch() { asm volatile("griddepcontrol.launch_dependents;" ::: "memory"); }
__device__ __forceinline__ void cluster_arrive() { asm volatile("barrier.cluster.arrive.release.aligned;" ::: "memory"); }
__device__ __forceinline__ void cluster_wait() { asm volatile("barrier.cluster.wait.acquire.aligned;" ::: "memory"); }

constexpr int K1_THREADS = 288;
constexpr int K1_SMEM = 131072 + 4 * 24576 + 128 + 1024;

__device__ __forceinline__ void ldsm4(uint32_t* r, uint32_t addr) {
    asm volatile("ldmatrix.sync.aligned.m8n8.x4.shared.b16 {%0, %1, %2, %3}, [%4];" : "=r"(r[0]), "=r"(r[1]), "=r"(r[2]), "=r"(r[3]) : "r"(addr) : "memory");
}
__device__ __forceinline__ void stsm4(uint32_t addr, uint32_t r0, uint32_t r1, uint32_t r2, uint32_t r3) {
    asm volatile("stmatrix.sync.aligned.m8n8.x4.shared.b16 [%0], {%1, %2, %3, %4};" :: "r"(addr), "r"(r0), "r"(r1), "r"(r2), "r"(r3) : "memory");
}
__device__ __forceinline__ void mma16816(float* d, const uint32_t* a, uint32_t b0, uint32_t b1) {
    asm("mma.sync.aligned.m16n8k16.row.col.f32.bf16.bf16.f32 {%0,%1,%2,%3}, {%4,%5,%6,%7}, {%8,%9}, {%0,%1,%2,%3};"
        : "+f"(d[0]), "+f"(d[1]), "+f"(d[2]), "+f"(d[3]) : "r"(a[0]), "r"(a[1]), "r"(a[2]), "r"(a[3]), "r"(b0), "r"(b1));
}
__device__ __forceinline__ uint32_t sub_bf16x2(uint32_t a, uint32_t b) {
    uint32_t d; asm("sub.rn.bf16x2 %0, %1, %2;" : "=r"(d) : "r"(a), "r"(b)); return d;
}

__device__ __forceinline__ void k1_epilogue(const float* acc, float rs0, float rs1, uint32_t stage, int nt, int mt, int wg, int w4, int lane, bool live) {
    const int g8a = mt * 16 + wg * 8 + w4 * 2;
    const float rv0 = is_poly_group(g8a) ? -rs0 : rs0, rv1 = is_poly_group(g8a + 1) ? -rs1 : rs1;
    const int mi = lane >> 3, lr = lane & 7;
    const uint32_t off_qk = stage + (w4 * 2 + (mi & 1)) * 256 + (mi >> 1) * 128 + lr * 16;
    const uint32_t off_v = stage + (mi >> 1) * 1024 + (w4 * 16 + (mi & 1) * 8 + lr) * 16;
    #pragma unroll
    for (int jj = 0; jj < 12; jj++) {
        const bool isv = nt * 12 + jj >= 64;
        const float m0 = isv ? rv0 : rs0, m1 = isv ? rv1 : rs1;
        const uint32_t r0 = pack_bf16(acc[8 * jj] * m0, acc[8 * jj + 1] * m0), r1 = pack_bf16(acc[8 * jj + 2] * m1, acc[8 * jj + 3] * m1);
        const uint32_t r2 = pack_bf16(acc[8 * jj + 4] * m0, acc[8 * jj + 5] * m0), r3 = pack_bf16(acc[8 * jj + 6] * m1, acc[8 * jj + 7] * m1);
        const uint32_t addr = (isv ? off_v : off_qk) + (jj >> 2) * 16384 + (jj & 3) * 2048;
        if (live) stsm4(addr, r0, r1, r2, r3);
    }
    if (live) {
        fence_async_smem();
        named_bar(1 + wg, 128);
        const int pc = w4 * 6 + lane;
        if (lane < 6) {
            const int jj = pc >> 1, hf = pc & 1, hg = nt * 12 + jj;
            const unsigned char* dst = (const unsigned char*)g_QKV + (size_t)hg * 65536
                + (hg >= 64 ? hf * 32768 + (mt * 128 + wg * 64) * 16 : (mt * 16 + wg * 8) * 256 + hf * 1024);
            asm volatile("cp.async.bulk.global.shared::cta.bulk_group [%0], [%1], 1024;"
                         :: "l"(dst), "r"(stage + (jj >> 2) * 16384 + (jj & 3) * 2048 + hf * 1024) : "memory");
            asm volatile("cp.async.bulk.commit_group;" ::: "memory");
            asm volatile("cp.async.bulk.wait_group.read 0;" ::: "memory");
        }
    }
}

__global__ void __launch_bounds__(K1_THREADS, 1)
k1_ln_qkv(const __grid_constant__ CUtensorMap wmap, const __grid_constant__ CUtensorMap xmap, const __nv_bfloat16* __restrict__ w_r) {
    extern __shared__ __align__(1024) unsigned char smem[];
    const uint32_t sA = smem_u32(smem), sB = sA + 131072, sBar = sB + 4 * 24576;
    const int warp = __shfl_sync(~0u, threadIdx.x >> 5, 0), lane = threadIdx.x & 31;
    const int nt = blockIdx.x & 7, mt = blockIdx.x >> 3;
    const bool producer = warp == 8;
    const int wg = (warp >> 2) & 1;
    TL(0, 0);
    pdl_launch();
    if (threadIdx.x == 256) {
        for (int i = 0; i < 4; i++) { mbar_init(sBar + i * 8, 1); mbar_init(sBar + 32 + i * 8, 2); }
        mbar_init(sBar + 64, 1); mbar_init(sBar + 72, 1);
        asm volatile("fence.mbarrier_init.release.cluster;" ::: "memory");
        for (int hf = 0; hf < 2; hf++) {
            mbar_expect_tx(sBar + 64 + hf * 8, 65536);
            for (int pn = 0; pn < 8; pn++) tma_2d(sA + pn * 16384 + hf * 8192, &xmap, pn * 64, mt * 128 + hf * 64, sBar + 64 + hf * 8);
        }
    }
    uint32_t* s_wr = (uint32_t*)(smem + 131072 + 4 * 24576 + 128);
    if (threadIdx.x < 256) s_wr[threadIdx.x] = __ldg((const uint32_t*)w_r + threadIdx.x);
    __syncthreads();
    float acc[96];
    #pragma unroll
    for (int i = 0; i < 96; i++) acc[i] = 0.f;
    float rs0 = 0.f, rs1 = 0.f;
    if (producer) {
        if (lane == 0) {
            for (int kc = 0; kc < 8; kc++) {
                const int st = kc & 3;
                if (kc >= 4) mbar_wait(sBar + 32 + st * 8, 0);
                mbar_expect_tx(sBar + st * 8, 24576);
                for (int j = 0; j < 3; j++) tma_2d(sB + st * 24576 + j * 8192, &wmap, nt * 192 + j * 64, kc * 64, sBar + st * 8);
            }
        }
        __syncwarp();
    } else {
        const int g = lane >> 2, t = lane & 3;
        const int lrow = warp * 16 + (lane & 7) + ((lane >> 3) & 1) * 8;
        const uint32_t lbase = sA + lrow * 128;
        const int lsw = lane & 7, lhi = lane >> 4;
        TL(0, 1);
        mbar_wait(sBar + 64 + wg * 8, 0);
        TL(0, 8);
        float dsum[4] = {0.f, 0.f, 0.f, 0.f}, dq0[4] = {0.f, 0.f, 0.f, 0.f}, dq1[4] = {0.f, 0.f, 0.f, 0.f};
        float esum[4] = {0.f, 0.f, 0.f, 0.f}, eq0[4] = {0.f, 0.f, 0.f, 0.f}, eq1[4] = {0.f, 0.f, 0.f, 0.f};
        uint32_t laddr[4];
        #pragma unroll
        for (int k4 = 0; k4 < 4; k4++) laddr[k4] = lbase + (((k4 * 2 + lhi) ^ lsw) * 16);
        #pragma unroll 2
        for (int pn = 0; pn < 8; pn++) {
            uint32_t a[4][4];
            #pragma unroll
            for (int k4 = 0; k4 < 4; k4++) ldsm4(a[k4], laddr[k4] + pn * 16384);
            #pragma unroll
            for (int k4 = 0; k4 < 4; k4 += 2) {
                mma16816(dsum, a[k4], 0x3F803F80u, 0x3F803F80u);
                mma16816(dq0, a[k4], a[k4][0], a[k4][2]);
                mma16816(dq1, a[k4], a[k4][1], a[k4][3]);
                mma16816(esum, a[k4 + 1], 0x3F803F80u, 0x3F803F80u);
                mma16816(eq0, a[k4 + 1], a[k4 + 1][0], a[k4 + 1][2]);
                mma16816(eq1, a[k4 + 1], a[k4 + 1][1], a[k4 + 1][3]);
            }
        }
        #pragma unroll
        for (int i = 0; i < 4; i++) { dsum[i] += esum[i]; dq0[i] += eq0[i]; dq1[i] += eq1[i]; }
        const int dsrc = g * 4 + (g >> 1);
        float sq0 = __shfl_sync(~0u, (g & 1) ? dq0[1] : dq0[0], dsrc), sq1 = __shfl_sync(~0u, (g & 1) ? dq1[3] : dq1[2], dsrc);
        const float mean0 = dsum[0] * (1.0f / D_), mean1 = dsum[2] * (1.0f / D_);
        float var0 = fmaf(-mean0, mean0, sq0 * (1.0f / D_)), var1 = fmaf(-mean1, mean1, sq1 * (1.0f / D_));
        if (__any_sync(~0u, !(mean0 * mean0 <= 16.0f * var0) || !(mean1 * mean1 <= 16.0f * var1))) {
            float q0 = 0.f, q1 = 0.f;
            #pragma unroll 1
            for (int ks = 0; ks < 32; ks++) {
                uint32_t a[4];
                ldsm4(a, lbase + (ks >> 2) * 16384 + ((((ks & 3) * 2 + lhi) ^ lsw) * 16));
                #pragma unroll
                for (int i = 0; i < 4; i++) {
                    const float m = (i & 1) ? mean1 : mean0;
                    const float d0 = bf_lo(a[i]) - m, d1 = bf_hi(a[i]) - m;
                    if (i & 1) q1 = fmaf(d0, d0, fmaf(d1, d1, q1)); else q0 = fmaf(d0, d0, fmaf(d1, d1, q0));
                }
            }
            q0 += __shfl_xor_sync(~0u, q0, 1); q0 += __shfl_xor_sync(~0u, q0, 2);
            q1 += __shfl_xor_sync(~0u, q1, 1); q1 += __shfl_xor_sync(~0u, q1, 2);
            var0 = q0 * (1.0f / D_); var1 = q1 * (1.0f / D_);
        }
        rs0 = __frcp_rn(bf16r(__fsqrt_rn(bf16r(bf16r(var0) + 1e-5f))));
        rs1 = __frcp_rn(bf16r(__fsqrt_rn(bf16r(bf16r(var1) + 1e-5f))));
        const uint32_t m20 = pack_bf16(mean0, mean0), m21 = pack_bf16(mean1, mean1);
        float dr[4] = {0.f, 0.f, 0.f, 0.f}, er[4] = {0.f, 0.f, 0.f, 0.f};
        #pragma unroll 1
        for (int pn = 0; pn < 8; pn += 2) {
            uint32_t a[8][4];
            #pragma unroll
            for (int k8 = 0; k8 < 8; k8++) ldsm4(a[k8], laddr[k8 & 3] + (pn + (k8 >> 2)) * 16384);
            #pragma unroll
            for (int k8 = 0; k8 < 8; k8++) {
                a[k8][0] = sub_bf16x2(a[k8][0], m20); a[k8][1] = sub_bf16x2(a[k8][1], m21);
                a[k8][2] = sub_bf16x2(a[k8][2], m20); a[k8][3] = sub_bf16x2(a[k8][3], m21);
            }
            #pragma unroll
            for (int k8 = 0; k8 < 8; k8++) stsm4(laddr[k8 & 3] + (pn + (k8 >> 2)) * 16384, a[k8][0], a[k8][1], a[k8][2], a[k8][3]);
            if (nt == 0) {
                #pragma unroll
                for (int k8 = 0; k8 < 8; k8++)
                    mma16816((k8 & 1) ? er : dr, a[k8], s_wr[(pn * 4 + k8) * 8 + t], s_wr[(pn * 4 + k8) * 8 + 4 + t]);
            }
        }
        dr[0] += er[0]; dr[2] += er[2];
        if (nt == 0 && t == 0) {
            const int row = mt * 128 + warp * 16 + g;
            g_r[row] = bf16r(dr[0] * rs0); g_r[row + 8] = bf16r(dr[2] * rs1);
            g_stats[row] = make_float2(bf_lo(m20), rs0); g_stats[row + 8] = make_float2(bf_lo(m21), rs1);
        }
        TL(0, 2);
        fence_async_smem();
        named_bar(1 + wg, 128);
        TL(0, 3);
        const uint64_t da0 = make_desc(sA + wg * 8192, 16, 1024, 1);
        const uint64_t db0 = make_desc(sB, 8192, 1024, 1);
        #pragma unroll 1
        for (int kc = 0; kc < 8; kc++) {
            const int st = kc & 3;
            mbar_wait(sBar + st * 8, kc >> 2);
            WG_FENCE();
            #pragma unroll
            for (int kk = 0; kk < 4; kk++)
                wgmma_n192(acc, da0 + (uint64_t)(kc * 1024 + kk * 2), db0 + (uint64_t)(st * 1536 + kk * 128));
            WG_COMMIT();
            wg_wait<1>();
            if (kc >= 1 && kc <= 4 && (threadIdx.x & 127) == 0) mbar_arrive(sBar + 32 + (kc - 1) * 8);
        }
        wg_wait<0>();
        touch96(acc);
        named_bar(1 + wg, 128);
        TL(0, 5);
    }
    k1_epilogue(acc, rs0, rs1, sA + wg * 8192, nt, mt, wg, warp & 3, lane, !producer);
    TL(0, 6);
}

constexpr int K2_THREADS = 512;
constexpr int K2_SMEM = 65536 + 98304 + 16384 + 128;

constexpr float QS = 0.25f * 1.4426950408889634f;
__device__ __forceinline__ uint32_t polyexp(float s, float cb, uint32_t c421, float c3, float one) {
    float u;
    asm("fma.rn.sat.f32 %0, %1, %2, %3;" : "=f"(u) : "f"(s), "f"(QS * (1.0f / 255.0f)), "f"(cb));
    float z = fmaf(u, 0.99609375f, one);
    uint32_t rb;
    asm("lop3.b32 %0, %1, 0xFFFF8000, %2, 0xEA;" : "=r"(rb) : "r"(__float_as_uint(z)), "r"(c421));
    float f = z - __uint_as_float(rb);
    float h = fmaf(f, c3, 58.86525f);
    h = fmaf(f, h, -0.29870507f);
    return __float_as_uint(fmaf(f, h, z));
}

struct ExpC { float nm0, nm1, cb0, cb1, c3, one; uint32_t c421; };

template <int G>
__device__ __forceinline__ void exp_block(const float* s, uint32_t* p, const ExpC& c) {
    #pragma unroll
    for (int hf = 0; hf < 2; hf++) {
        const float* x = s + hf * 4;
        if ((PMASK >> (G + hf)) & 1) {
            p[hf * 2 + 0] = __byte_perm(polyexp(x[0], c.cb0, c.c421, c.c3, c.one), polyexp(x[1], c.cb0, c.c421, c.c3, c.one), 0x6521);
            p[hf * 2 + 1] = __byte_perm(polyexp(x[2], c.cb1, c.c421, c.c3, c.one), polyexp(x[3], c.cb1, c.c421, c.c3, c.one), 0x6521);
        } else {
            p[hf * 2 + 0] = pack_bf16(ex2(fmaf(x[0], QS, c.nm0)), ex2(fmaf(x[1], QS, c.nm0)));
            p[hf * 2 + 1] = pack_bf16(ex2(fmaf(x[2], QS, c.nm1)), ex2(fmaf(x[3], QS, c.nm1)));
        }
    }
}

__device__ __forceinline__ void max16(const float* s, float& mx0, float& mx1) {
    #pragma unroll
    for (int j = 0; j < 4; j++) {
        mx0 = fmaxf(mx0, fmaxf(s[4 * j], s[4 * j + 1]));
        mx1 = fmaxf(mx1, fmaxf(s[4 * j + 2], s[4 * j + 3]));
    }
}

__device__ void moe_cta(int part, unsigned char* smem, const __nv_bfloat16* __restrict__ x, const __nv_bfloat16* __restrict__ w_gate,
                        const __nv_bfloat16* __restrict__ w_up, const __nv_bfloat16* __restrict__ w_down) {
    float* xs = (float*)smem;
    float* red = xs + 1024;
    float* hs = red + 8 * 4 * 448;
    __shared__ float s_v[32];
    __shared__ int s_i[32];
    __shared__ int s_sel[2];
    const int tid = threadIdx.x, warp = tid >> 5, lane = tid & 31;
    for (int pass = 0; pass < 2; pass++) {
        float bv = -INFINITY; int bi = 0x7fffffff;
        const int excl = pass ? s_sel[0] : -1;
        for (int i = tid; i < S_; i += K2_THREADS) {
            float v = g_r[i];
            if (i != excl && (v > bv || (v == bv && i < bi) || bi == 0x7fffffff)) { bv = v; bi = i; }
        }
        #pragma unroll
        for (int o = 16; o; o >>= 1) {
            float ov = __shfl_xor_sync(~0u, bv, o); int oi = __shfl_xor_sync(~0u, bi, o);
            if (ov > bv || (ov == bv && oi < bi)) { bv = ov; bi = oi; }
        }
        if (lane == 0) { s_v[warp] = bv; s_i[warp] = bi; }
        __syncthreads();
        if (warp == 0) {
            bv = lane < 16 ? s_v[lane] : -INFINITY; bi = lane < 16 ? s_i[lane] : 0x7fffffff;
            #pragma unroll
            for (int o = 16; o; o >>= 1) {
                float ov = __shfl_xor_sync(~0u, bv, o); int oi = __shfl_xor_sync(~0u, bi, o);
                if (ov > bv || (ov == bv && oi < bi)) { bv = ov; bi = oi; }
            }
            if (lane == 0) s_sel[pass] = (bi == 0x7fffffff) ? pass : bi;
        }
        __syncthreads();
    }
    for (int i = tid; i < 1024; i += K2_THREADS) {
        const int tok = s_sel[i >> 9];
        const float2 st = g_stats[tok];
        xs[i] = ln_elem(__bfloat162float(x[(size_t)tok * D_ + (i & 511)]), st.x, st.y);
    }
    if (part == 0 && tid < 2) g_sel[tid] = s_sel[tid];
    __syncthreads();
    const int c0 = part * 448;
    if (tid < 448) {
        const int cg = tid % 56, ks = tid / 56;
        float a[4][8];
        #pragma unroll
        for (int i = 0; i < 4; i++)
            #pragma unroll
            for (int j = 0; j < 8; j++) a[i][j] = 0.f;
        const __nv_bfloat16* pg = w_gate + (size_t)(ks * 64) * F_ + c0 + cg * 8;
        const __nv_bfloat16* pu = w_up + (size_t)(ks * 64) * F_ + c0 + cg * 8;
        #pragma unroll 8
        for (int k = 0; k < 64; k++) {
            const uint4 gv = __ldg((const uint4*)(pg + (size_t)k * F_));
            const uint4 uv = __ldg((const uint4*)(pu + (size_t)k * F_));
            const float x0 = xs[ks * 64 + k], x1 = xs[512 + ks * 64 + k];
            const uint32_t gu[4] = {gv.x, gv.y, gv.z, gv.w}, uu[4] = {uv.x, uv.y, uv.z, uv.w};
            #pragma unroll
            for (int j = 0; j < 4; j++) {
                const float g0 = bf_lo(gu[j]), g1 = bf_hi(gu[j]), u0 = bf_lo(uu[j]), u1 = bf_hi(uu[j]);
                a[0][2 * j] = fmaf(x0, g0, a[0][2 * j]); a[0][2 * j + 1] = fmaf(x0, g1, a[0][2 * j + 1]);
                a[1][2 * j] = fmaf(x1, g0, a[1][2 * j]); a[1][2 * j + 1] = fmaf(x1, g1, a[1][2 * j + 1]);
                a[2][2 * j] = fmaf(x0, u0, a[2][2 * j]); a[2][2 * j + 1] = fmaf(x0, u1, a[2][2 * j + 1]);
                a[3][2 * j] = fmaf(x1, u0, a[3][2 * j]); a[3][2 * j + 1] = fmaf(x1, u1, a[3][2 * j + 1]);
            }
        }
        #pragma unroll
        for (int i = 0; i < 4; i++)
            #pragma unroll
            for (int j = 0; j < 8; j++) red[(ks * 4 + i) * 448 + cg * 8 + j] = a[i][j];
    }
    __syncthreads();
    for (int i = tid; i < 896; i += K2_THREADS) {
        const int tok = i / 448, c = i % 448;
        float gs = 0.f, us = 0.f;
        #pragma unroll
        for (int ks = 0; ks < 8; ks++) { gs += red[(ks * 4 + tok) * 448 + c]; us += red[(ks * 4 + 2 + tok) * 448 + c]; }
        gs = bf16r(gs); us = bf16r(us);
        const float sl = bf16r(gs / (1.0f + __expf(-gs)));
        hs[i] = bf16r(sl * us);
    }
    __syncthreads();
    {
        const int cg = tid & 63, fs = tid >> 6;
        float a[2][8];
        #pragma unroll
        for (int j = 0; j < 8; j++) { a[0][j] = 0.f; a[1][j] = 0.f; }
        const __nv_bfloat16* pd = w_down + (size_t)(c0 + fs * 56) * D_ + cg * 8;
        #pragma unroll 8
        for (int f = 0; f < 56; f++) {
            const uint4 dv = __ldg((const uint4*)(pd + (size_t)f * D_));
            const float h0 = hs[fs * 56 + f], h1 = hs[448 + fs * 56 + f];
            const uint32_t du[4] = {dv.x, dv.y, dv.z, dv.w};
            #pragma unroll
            for (int j = 0; j < 4; j++) {
                const float d0 = bf_lo(du[j]), d1 = bf_hi(du[j]);
                a[0][2 * j] = fmaf(h0, d0, a[0][2 * j]); a[0][2 * j + 1] = fmaf(h0, d1, a[0][2 * j + 1]);
                a[1][2 * j] = fmaf(h1, d0, a[1][2 * j]); a[1][2 * j + 1] = fmaf(h1, d1, a[1][2 * j + 1]);
            }
        }
        #pragma unroll
        for (int j = 0; j < 8; j++) { red[(fs * 2) * 512 + cg * 8 + j] = a[0][j]; red[(fs * 2 + 1) * 512 + cg * 8 + j] = a[1][j]; }
    }
    __syncthreads();
    for (int i = tid; i < 1024; i += K2_THREADS) {
        float s = 0.f;
        #pragma unroll
        for (int fs = 0; fs < 8; fs++) s += red[(fs * 2 + (i >> 9)) * 512 + (i & 511)];
        g_ypart[part][i >> 9][i & 511] = s;
    }
}

__global__ void __launch_bounds__(K2_THREADS, 1)
k2_attn(const __nv_bfloat16* __restrict__ x, const __nv_bfloat16* __restrict__ w_gate, const __nv_bfloat16* __restrict__ w_up,
        const __nv_bfloat16* __restrict__ w_down) {
    extern __shared__ __align__(1024) unsigned char smem[];
    TL(1, 0);
    pdl_launch();
    if (blockIdx.x >= 128) {
        const int part = blockIdx.x - 128;
        {
            const int k = threadIdx.x;
            asm volatile("cp.async.bulk.prefetch.L2.global [%0], %1;" :: "l"(w_gate + (size_t)k * F_ + part * 448), "r"(896) : "memory");
            asm volatile("cp.async.bulk.prefetch.L2.global [%0], %1;" :: "l"(w_up + (size_t)k * F_ + part * 448), "r"(896) : "memory");
            if (k < 56) asm volatile("cp.async.bulk.prefetch.L2.global [%0], %1;" :: "l"(w_down + (size_t)(part * 448 + k * 8) * D_), "r"(8192) : "memory");
        }
        pdl_wait(); TL(1, 1); moe_cta(blockIdx.x - 128, smem, x, w_gate, w_up, w_down); TL(1, 2); return; }
    const uint32_t sK = smem_u32(smem), sV = sK + 65536, sQ = sV + 98304, sBar = sQ + 16384;
    const int h = blockIdx.x >> 2, qb = blockIdx.x & 3;
    const int warp = __shfl_sync(~0u, threadIdx.x >> 5, 0), lane = threadIdx.x & 31, wg = warp >> 2;
    if (threadIdx.x == 0) {
        mbar_init(sBar, 1); mbar_init(sBar + 8, 1);
        asm volatile("fence.mbarrier_init.release.cluster;" ::: "memory");
        pdl_wait();
        TL(1, 1);
        const uint4* gk = g_K + (size_t)h * 4096;
        const uint4* gv = g_V + (size_t)h * 4096;
        mbar_expect_tx(sBar, 16384 + 16384 + 2 * 8192);
        bulk_g2s(sQ, g_Q + (size_t)h * 4096 + qb * 1024, 16384, sBar);
        bulk_g2s(sK, gk, 16384, sBar);
        bulk_g2s(sV, gv, 8192, sBar);
        bulk_g2s(sV + 32768, gv + 2048, 8192, sBar);
        mbar_expect_tx(sBar + 8, 49152 + 2 * 24576);
        bulk_g2s(sK + 16384, gk + 1024, 49152, sBar + 8);
        bulk_g2s(sV + 8192, gv + 512, 24576, sBar + 8);
        bulk_g2s(sV + 32768 + 8192, gv + 2048 + 512, 24576, sBar + 8);
    }
    for (int i = threadIdx.x; i < 2048; i += K2_THREADS) {
        const uint32_t v = is_poly_group(i >> 3) ? 0xBF80BF80u : 0x3F803F80u;
        *(uint4*)(smem + 65536 + 65536 + i * 16) = make_uint4(v, v, v, v);
    }
    fence_async_smem();
    __syncthreads();
    ExpC c;
    {
        const volatile uint32_t* cc = g_const;
        c.c421 = cc[0]; c.c3 = __uint_as_float(cc[1]); c.one = __uint_as_float(cc[2]);
    }
    const uint32_t kdesc0 = (uint32_t)make_desc(sK, 128, 256, 0);
    const uint32_t vdesc0 = (uint32_t)make_desc(sV, 128, 32768, 0);
    mbar_wait(sBar, 0);
    TL(1, 2);
    #pragma unroll 1
    for (int pass = 0; pass < 2; pass++) {
        const int unit = pass * 4 + wg;
        const uint32_t q = (uint32_t)make_desc(sQ + unit * 2048, 128, 256, 0);
        float o[12];
        #pragma unroll 1
        for (int attempt = 0; attempt < 2; attempt++) {
            float s0[16], s1[16], s2[16];
            #pragma unroll
            for (int i = 0; i < 16; i++) { s0[i] = 0.f; s1[i] = 0.f; s2[i] = 0.f; }
            float mx0 = -INFINITY, mx1 = -INFINITY;
            if (attempt) {
                #pragma unroll 1
                for (int it = 0; it < 64; it++) {
                    WG_FENCE();
                    wgmma_qk32(s0, q, kdesc0 + it * 64);
                    WG_COMMIT();
                    wg_wait<0>();
                    touch16(s0);
                    max16(s0, mx0, mx1);
                }
            }
            #pragma unroll
            for (int i = 0; i < 12; i++) o[i] = 0.f;
            WG_FENCE();
            wgmma_qk32(s2, q, kdesc0);
            wgmma_qk32(s0, q, kdesc0 + 64);
            wgmma_qk32(s1, q, kdesc0 + 128);
            WG_COMMIT();
            wg_wait<0>();
            touch16(s0); touch16(s1); touch16(s2);
            max16(s0, mx0, mx1); max16(s1, mx0, mx1); max16(s2, mx0, mx1);
            mx0 = fmaxf(mx0, __shfl_xor_sync(~0u, mx0, 1)); mx0 = fmaxf(mx0, __shfl_xor_sync(~0u, mx0, 2));
            mx1 = fmaxf(mx1, __shfl_xor_sync(~0u, mx1, 1)); mx1 = fmaxf(mx1, __shfl_xor_sync(~0u, mx1, 2));
            const float bias = attempt ? 0.0f : 64.0f;
            c.nm0 = __shfl_sync(~0u, -fmaf(mx0, QS, bias), lane); c.nm1 = __shfl_sync(~0u, -fmaf(mx1, QS, bias), lane);
            c.cb0 = __shfl_sync(~0u, (127.0f + c.nm0) * (1.0f / 255.0f), lane);
            c.cb1 = __shfl_sync(~0u, (127.0f + c.nm1) * (1.0f / 255.0f), lane);
            uint32_t kd = kdesc0 + 192, vd = vdesc0 + 32;
            {
                uint32_t pa[4], pb[4];
                exp_block<12>(s2, pa, c);
                exp_block<14>(s2 + 8, pb, c);
                WG_FENCE();
                wgmma_pv(o, pa, vdesc0); wgmma_pv(o, pb, vdesc0 + 16);
                WG_COMMIT();
            }
            #pragma unroll 1
            for (int seg = 0; seg < 2; seg++) {
            if (seg) { wg_wait<0>(); mbar_wait(sBar + 8, 0); __syncwarp(); }
            #pragma unroll 1
            for (int it = seg ? 3 : 0; it < (seg ? 21 : 3); it++) {
                uint32_t p[6][4];
                WG_FENCE();
                wgmma_qk32(s2, q, kd);
                WG_COMMIT();
                exp_block<0>(s0, p[0], c);
                exp_block<2>(s0 + 8, p[1], c);
                WG_FENCE();
                wgmma_pv(o, p[0], vd); wgmma_pv(o, p[1], vd + 16);
                wgmma_qk32(s0, q, kd + 64);
                WG_COMMIT();
                wg_wait<1>();
                touch16(s2);
                exp_block<4>(s1, p[2], c);
                exp_block<6>(s1 + 8, p[3], c);
                WG_FENCE();
                wgmma_pv(o, p[2], vd + 32); wgmma_pv(o, p[3], vd + 48);
                wgmma_qk32(s1, q, kd + 128);
                WG_COMMIT();
                wg_wait<1>();
                touch16(s0);
                exp_block<8>(s2, p[4], c);
                exp_block<10>(s2 + 8, p[5], c);
                WG_FENCE();
                wgmma_pv(o, p[4], vd + 64); wgmma_pv(o, p[5], vd + 80);
                WG_COMMIT();
                vd += 96; kd += 192;
                wg_wait<1>();
                touch16(s1);
            }
            }
            wg_wait<0>();
            touch12(o);
            if (attempt) break;
            float big = 0.f;
            #pragma unroll
            for (int i = 0; i < 12; i++) big = fmaxf(big, fabsf(o[i]));
            bool bad = !(big < 1e30f);
            #pragma unroll
            for (int i = 0; i < 12; i++) bad |= (o[i] != o[i]);
            uint32_t any;
            asm volatile("{.reg .pred p, q; setp.ne.u32 p, %1, 0; barrier.cta.red.or.pred.aligned q, %2, 128, p; selp.u32 %0, 1, 0, q;}"
                         : "=r"(any) : "r"((uint32_t)bad), "r"(1 + wg) : "memory");
            if (!__any_sync(~0u, any)) break;
        }
        const int g = lane >> 2, t = lane & 3;
        const int r = (warp & 3) * 16 + g;
        const float i0 = __fdiv_rn(1.0f, o[8]), i1 = __fdiv_rn(1.0f, o[10]);
        uint32_t* ob = (uint32_t*)(g_O + (size_t)(qb * 8 + unit) * 4096 + (h >> 2) * 512 + r * 8) + t;
        const int c0 = ((h & 3) * 2) ^ (r & 7), c1 = ((h & 3) * 2 + 1) ^ (r & 7);
        ob[c0 * 4] = pack_bf16(o[0] * i0, o[1] * i0);
        ob[c1 * 4] = pack_bf16(o[4] * i0, o[5] * i0);
        ob[256 + c0 * 4] = pack_bf16(o[2] * i1, o[3] * i1);
        ob[256 + c1 * 4] = pack_bf16(o[6] * i1, o[7] * i1);
        TL(1, 3 + pass);
    }
}

constexpr int K3_THREADS = 256;
constexpr int K3_SMEM = 65536 + 131072 + 128;

__global__ void __launch_bounds__(K3_THREADS, 1)
k3_out(const __grid_constant__ CUtensorMap wmap, const __nv_bfloat16* __restrict__ x, __nv_bfloat16* __restrict__ out) {
    extern __shared__ __align__(1024) unsigned char smem[];
    const uint32_t sA = smem_u32(smem), sB = sA + 65536, sBar = sB + 131072;
    const int warp = __shfl_sync(~0u, threadIdx.x >> 5, 0), lane = threadIdx.x & 31, wg = warp >> 2;
    const int nt = blockIdx.x & 3, mt = blockIdx.x >> 2;
    TL(2, 0);
    if (threadIdx.x == 0) {
        for (int i = 0; i < 6; i++) mbar_init(sBar + i * 8, 1);
        asm volatile("fence.mbarrier_init.release.cluster;" ::: "memory");
        for (int kh = 0; kh < 2; kh++) {
            mbar_expect_tx(sBar + kh * 8, 65536);
            tma_2d(sB + kh * 32768, &wmap, nt * 128, kh * 256, sBar + kh * 8);
            tma_2d(sB + 65536 + kh * 32768, &wmap, nt * 128 + 64, kh * 256, sBar + kh * 8);
        }
    }
    const int er = threadIdx.x >> 2, ec = (threadIdx.x & 3) * 32;
    const int row = mt * 64 + er;
    uint4 xv[4];
    #pragma unroll
    for (int j = 0; j < 4; j++) xv[j] = __ldg((const uint4*)(x + (size_t)row * D_ + nt * 128 + ec) + j);
    pdl_wait();
    TL(2, 1);
    if (threadIdx.x == 0) {
        for (int q = 0; q < 4; q++) {
            mbar_expect_tx(sBar + 16 + q * 8, 16384);
            bulk_g2s(sA + q * 16384, g_O + (size_t)mt * 4096 + q * 1024, 16384, sBar + 16 + q * 8);
        }
    }
    const int sel0 = g_sel[0], sel1 = g_sel[1];
    const float2 st = g_stats[row];
    uint32_t bb[16];
    {
        const uint32_t xu[16] = {xv[0].x, xv[0].y, xv[0].z, xv[0].w, xv[1].x, xv[1].y, xv[1].z, xv[1].w,
                                 xv[2].x, xv[2].y, xv[2].z, xv[2].w, xv[3].x, xv[3].y, xv[3].z, xv[3].w};
        #pragma unroll
        for (int j = 0; j < 16; j++) bb[j] = pack_bf16(bf16r(bf_lo(xu[j]) - st.x) * st.y, bf16r(bf_hi(xu[j]) - st.x) * st.y);
        const int slot = row == sel0 ? 0 : (row == sel1 ? 1 : -1);
        if (slot >= 0) {
            const float gate = bf16r(1.0f / (1.0f + __expf(-g_r[row])));
            const int c0 = nt * 128 + ec;
            #pragma unroll
            for (int j = 0; j < 16; j++) {
                const float2 a = *(const float2*)&g_ypart[0][slot][c0 + 2 * j], b = *(const float2*)&g_ypart[1][slot][c0 + 2 * j];
                const float2 c = *(const float2*)&g_ypart[2][slot][c0 + 2 * j], d = *(const float2*)&g_ypart[3][slot][c0 + 2 * j];
                bb[j] = pack_bf16(bf_lo(bb[j]) + bf16r(bf16r(a.x + b.x + c.x + d.x) * gate), bf_hi(bb[j]) + bf16r(bf16r(a.y + b.y + c.y + d.y) * gate));
            }
        }
    }
    __syncthreads();
    float acc[32];
    #pragma unroll
    for (int i = 0; i < 32; i++) acc[i] = 0.f;
    const uint64_t da0 = make_desc(sA, 16, 1024, 1);
    const uint64_t db0 = make_desc(sB + wg * 65536, 8192, 1024, 1);
    #pragma unroll 1
    for (int q = 0; q < 4; q++) {
        if ((q & 1) == 0) mbar_wait(sBar + (q >> 1) * 8, 0);
        mbar_wait(sBar + 16 + q * 8, 0);
        WG_FENCE();
        #pragma unroll
        for (int kk = 0; kk < 8; kk++)
            wgmma_n64(acc, da0 + (uint64_t)(q * 1024 + (kk >> 2) * 512 + (kk & 3) * 2), db0 + (uint64_t)(q * 1024 + kk * 128));
        WG_COMMIT();
    }
    wg_wait<0>();
    touch32(acc);
    TL(2, 2);
    __syncthreads();
    {
        const int g = lane >> 2, t = lane & 3;
        unsigned char* sp = smem + ((warp & 3) * 16 + g) * 272 + wg * 128 + t * 4;
        #pragma unroll
        for (int j = 0; j < 8; j++) {
            *(uint32_t*)(sp + j * 16) = pack_bf16(acc[4 * j], acc[4 * j + 1]);
            *(uint32_t*)(sp + 8 * 272 + j * 16) = pack_bf16(acc[4 * j + 2], acc[4 * j + 3]);
        }
    }
    __syncthreads();
    #pragma unroll
    for (int j = 0; j < 4; j++) {
        const uint4 av = *(const uint4*)(smem + er * 272 + ec * 2 + j * 16);
        const uint32_t au[4] = {av.x, av.y, av.z, av.w}, xu[4] = {xv[j].x, xv[j].y, xv[j].z, xv[j].w};
        uint32_t o[4];
        #pragma unroll
        for (int i = 0; i < 4; i++) {
            uint32_t t2;
            asm("add.rn.bf16x2 %0, %1, %2;" : "=r"(t2) : "r"(xu[i]), "r"(au[i]));
            asm("add.rn.bf16x2 %0, %1, %2;" : "=r"(o[i]) : "r"(t2), "r"(bb[j * 4 + i]));
        }
        *((uint4*)(out + (size_t)row * D_ + nt * 128 + ec) + j) = make_uint4(o[0], o[1], o[2], o[3]);
    }
    TL(2, 3);
}

typedef CUresult (*EncodeFn)(CUtensorMap*, CUtensorMapDataType, cuuint32_t, void*, const cuuint64_t*, const cuuint64_t*,
                             const cuuint32_t*, const cuuint32_t*, CUtensorMapInterleave, CUtensorMapSwizzle,
                             CUtensorMapL2promotion, CUtensorMapFloatOOBfill);

void make_wmap(EncodeFn fn, CUtensorMap* map, const void* ptr, int rows, int cols, int box_rows) {
    cuuint64_t dims[2] = {(cuuint64_t)cols, (cuuint64_t)rows};
    cuuint64_t strides[1] = {(cuuint64_t)cols * 2};
    cuuint32_t box[2] = {64, (cuuint32_t)box_rows};
    cuuint32_t es[2] = {1, 1};
    fn(map, CU_TENSOR_MAP_DATA_TYPE_BFLOAT16, 2, (void*)ptr, dims, strides, box, es, CU_TENSOR_MAP_INTERLEAVE_NONE,
       CU_TENSOR_MAP_SWIZZLE_128B, CU_TENSOR_MAP_L2_PROMOTION_L2_256B, CU_TENSOR_MAP_FLOAT_OOB_FILL_NONE);
}

}

extern "C" void kernel_launch(void* const* d_in, const int* in_sizes, int n_in, void* d_out, int out_size) {
    const __nv_bfloat16* x = (const __nv_bfloat16*)d_in[0];
    const __nv_bfloat16* wqkv = (const __nv_bfloat16*)d_in[1];
    const __nv_bfloat16* wo = (const __nv_bfloat16*)d_in[2];
    const __nv_bfloat16* w_r = (const __nv_bfloat16*)d_in[4];
    const __nv_bfloat16* w_gate = (const __nv_bfloat16*)d_in[5];
    const __nv_bfloat16* w_up = (const __nv_bfloat16*)d_in[6];
    const __nv_bfloat16* w_down = (const __nv_bfloat16*)d_in[7];
    __nv_bfloat16* out = (__nv_bfloat16*)d_out;

    static EncodeFn encode = nullptr;
    if (!encode) {
        void* fn = nullptr;
        cudaDriverEntryPointQueryResult qres;
        cudaGetDriverEntryPoint("cuTensorMapEncodeTiled", &fn, cudaEnableDefault, &qres);
        encode = (EncodeFn)fn;
        cudaFuncSetAttribute(k1_ln_qkv, cudaFuncAttributeMaxDynamicSharedMemorySize, K1_SMEM);
        cudaFuncSetAttribute(k2_attn, cudaFuncAttributeMaxDynamicSharedMemorySize, K2_SMEM);
        cudaFuncSetAttribute(k3_out, cudaFuncAttributeMaxDynamicSharedMemorySize, K3_SMEM);
    }
    CUtensorMap map_qkv, map_wo, map_x;
    make_wmap(encode, &map_x, x, S_, D_, 64);
    make_wmap(encode, &map_qkv, wqkv, D_, 3 * D_, 64);
    make_wmap(encode, &map_wo, wo, D_, D_, 256);

    k1_ln_qkv<<<128, K1_THREADS, K1_SMEM, cudaStreamPerThread>>>(map_qkv, map_x, w_r);
    cudaLaunchAttribute at[1];
    at[0].id = cudaLaunchAttributeProgrammaticStreamSerialization;
    at[0].val.programmaticStreamSerializationAllowed = 1;
    cudaLaunchConfig_t cfg = {};
    cfg.stream = cudaStreamPerThread;
    cfg.attrs = at; cfg.numAttrs = 1;
    cfg.gridDim = dim3(132); cfg.blockDim = dim3(K2_THREADS); cfg.dynamicSmemBytes = K2_SMEM;
    cudaLaunchKernelEx(&cfg, k2_attn, x, w_gate, w_up, w_down);
    cfg.gridDim = dim3(128); cfg.blockDim = dim3(K3_THREADS); cfg.dynamicSmemBytes = K3_SMEM;
    cudaLaunchKernelEx(&cfg, k3_out, map_wo, x, out);
}
```

```cpp
#include <cuda_runtime.h>
#include <cuda_bf16.h>
#include <cuda.h>
#include <stdint.h>

namespace {

constexpr int S_ = 2048, D_ = 512, H_ = 32, F_ = 1792;

constexpr uint32_t PMASK = 0xA52;
__host__ __device__ constexpr bool is_poly_group(int g8) { return g8 >= 4 && ((PMASK >> ((g8 - 4) % 12)) & 1); }

__device__ __align__(1024) uint4 g_QKV[3 * H_ * S_ * 2];
#define g_Q (g_QKV)
#define g_K (g_QKV + H_ * S_ * 2)
#define g_V (g_QKV + 2 * H_ * S_ * 2)
__device__ __align__(1024) uint4 g_O[S_ * D_ / 8];
__device__ float2 g_stats[S_];
__device__ uint32_t g_const[4] = {421u, 0x459EB285u  , 0x3F800000u  , 0u};
__device__ float g_r[S_];
__device__ __align__(16) float g_ypart[4][2][D_];
__device__ int g_sel[2];

#define TL(k, p)
__device__ __forceinline__ uint32_t smem_u32(const void* p) { return (uint32_t)__cvta_generic_to_shared(p); }
__device__ __forceinline__ float bf16r(float x) { return __bfloat162float(__float2bfloat16_rn(x)); }
__device__ __forceinline__ uint32_t pack_bf16(float lo, float hi) {
    uint32_t r; asm("cvt.rn.bf16x2.f32 %0, %1, %2;" : "=r"(r) : "f"(hi), "f"(lo)); return r;
}
__device__ __forceinline__ float bf_lo(uint32_t u) { return __uint_as_float(u << 16); }
__device__ __forceinline__ float bf_hi(uint32_t u) { return __uint_as_float(u & 0xFFFF0000u); }
__device__ __forceinline__ float ex2(float x) { float y; asm("ex2.approx.ftz.f32 %0, %1;" : "=f"(y) : "f"(x)); return y; }

__device__ __forceinline__ void mbar_init(uint32_t bar, uint32_t count) {
    asm volatile("mbarrier.init.shared::cta.b64 [%0], %1;" :: "r"(bar), "r"(count) : "memory");
}
__device__ __forceinline__ void mbar_expect_tx(uint32_t bar, uint32_t bytes) {
    asm volatile("mbarrier.arrive.expect_tx.shared::cta.b64 _, [%0], %1;" :: "r"(bar), "r"(bytes) : "memory");
}
__device__ __forceinline__ void mbar_arrive(uint32_t bar) {
    asm volatile("mbarrier.arrive.shared::cta.b64 _, [%0];" :: "r"(bar) : "memory");
}
__device__ __forceinline__ void mbar_wait(uint32_t bar, uint32_t parity) {
    uint32_t done;
    #pragma unroll 1
    for (int it = 0; it < (1 << 26); it++) {
        asm volatile("{.reg .pred p; mbarrier.try_wait.parity.shared::cta.b64 p, [%1], %2; selp.u32 %0, 1, 0, p;}"
                     : "=r"(done) : "r"(bar), "r"(parity) : "memory");
        if (done) return;
    }
    __trap();
}
__device__ __forceinline__ void bulk_g2s(uint32_t dst, const void* src, uint32_t bytes, uint32_t bar) {
    asm volatile("cp.async.bulk.shared::cluster.global.mbarrier::complete_tx::bytes [%0], [%1], %2, [%3];"
                 :: "r"(dst), "l"(src), "r"(bytes), "r"(bar) : "memory");
}
__device__ __forceinline__ void tma_2d(uint32_t dst, const CUtensorMap* map, int c0, int c1, uint32_t bar) {
    asm volatile("cp.async.bulk.tensor.2d.shared::cluster.global.mbarrier::complete_tx::bytes [%0], [%1, {%3, %4}], [%2];"
                 :: "r"(dst), "l"(map), "r"(bar), "r"(c0), "r"(c1) : "memory");
}
__device__ __forceinline__ void fence_async_smem() { asm volatile("fence.proxy.async.shared::cta;" ::: "memory"); }
__device__ __forceinline__ void named_bar(int id, int n) { asm volatile("bar.sync %0, %1;" :: "r"(id), "r"(n) : "memory"); }

__device__ __forceinline__ uint64_t make_desc(uint32_t saddr, uint32_t lbo, uint32_t sbo, uint32_t swz) {
    return (uint64_t)((saddr & 0x3FFFF) >> 4) | ((uint64_t)(lbo >> 4) << 16) | ((uint64_t)(sbo >> 4) << 32) | ((uint64_t)swz << 62);
}
#define WG_FENCE() asm volatile("wgmma.fence.sync.aligned;" ::: "memory")
#define WG_COMMIT() asm volatile("wgmma.commit_group.sync.aligned;" ::: "memory")
template <int N> __device__ __forceinline__ void wg_wait() { asm volatile("wgmma.wait_group.sync.aligned %0;" :: "n"(N) : "memory"); }

#define F4(d, o) "+f"(d[o]), "+f"(d[o + 1]), "+f"(d[o + 2]), "+f"(d[o + 3])
#define F16(d, o) F4(d, o), F4(d, o + 4), F4(d, o + 8), F4(d, o + 12)
#define F32(d, o) F16(d, o), F16(d, o + 16)

__device__ __forceinline__ void wgmma_n192(float* d, uint64_t da, uint64_t db) {
    asm volatile("wgmma.mma_async.sync.aligned.m64n192k16.f32.bf16.bf16 "
        "{%0,%1,%2,%3,%4,%5,%6,%7,%8,%9,%10,%11,%12,%13,%14,%15,%16,%17,%18,%19,%20,%21,%22,%23,%24,%25,%26,%27,%28,%29,%30,%31,"
        "%32,%33,%34,%35,%36,%37,%38,%39,%40,%41,%42,%43,%44,%45,%46,%47,%48,%49,%50,%51,%52,%53,%54,%55,%56,%57,%58,%59,%60,%61,%62,%63,"
        "%64,%65,%66,%67,%68,%69,%70,%71,%72,%73,%74,%75,%76,%77,%78,%79,%80,%81,%82,%83,%84,%85,%86,%87,%88,%89,%90,%91,%92,%93,%94,%95}, "
        "%96, %97, 1, 1, 1, 0, 1;\n"
        : F32(d, 0), F32(d, 32), F32(d, 64) : "l"(da), "l"(db));
}
__device__ __forceinline__ void wgmma_n64(float* d, uint64_t da, uint64_t db) {
    asm volatile("wgmma.mma_async.sync.aligned.m64n64k16.f32.bf16.bf16 "
        "{%0,%1,%2,%3,%4,%5,%6,%7,%8,%9,%10,%11,%12,%13,%14,%15,%16,%17,%18,%19,%20,%21,%22,%23,%24,%25,%26,%27,%28,%29,%30,%31}, "
        "%32, %33, 1, 1, 1, 0, 1;\n"
        : F32(d, 0) : "l"(da), "l"(db));
}
__device__ __forceinline__ void wgmma_qk32(float* d, uint32_t qd, uint32_t kd) {
    asm volatile("{.reg .b64 a, b; mov.b64 a, {%16, 16}; mov.b64 b, {%17, 16};\n"
        "wgmma.mma_async.sync.aligned.m64n32k16.f32.bf16.bf16 {%0,%1,%2,%3,%4,%5,%6,%7,%8,%9,%10,%11,%12,%13,%14,%15}, a, b, 0, 1, 1, 0, 0;}\n"
        : F16(d, 0) : "r"(qd), "r"(kd));
}
__device__ __forceinline__ void wgmma_pv(float* d, const uint32_t* a, uint32_t vd) {
    asm volatile("{.reg .b64 b; mov.b64 b, {%16, 2048};\n"
        "wgmma.mma_async.sync.aligned.m64n24k16.f32.bf16.bf16 {%0,%1,%2,%3,%4,%5,%6,%7,%8,%9,%10,%11}, {%12,%13,%14,%15}, b, 1, 1, 1, 1;}\n"
        : F4(d, 0), F4(d, 4), F4(d, 8) : "r"(a[0]), "r"(a[1]), "r"(a[2]), "r"(a[3]), "r"(vd));
}
__device__ __forceinline__ void touch16(float* d) { asm volatile("" : F16(d, 0) :: "memory"); }
__device__ __forceinline__ void touch12(float* d) { asm volatile("" : F4(d, 0), F4(d, 4), F4(d, 8) :: "memory"); }
__device__ __forceinline__ void touch32(float* d) { asm volatile("" : F32(d, 0) :: "memory"); }
__device__ __forceinline__ void touch96(float* d) { asm volatile("" : F32(d, 0), F32(d, 32), F32(d, 64) :: "memory"); }

__device__ __forceinline__ float ln_elem(float x, float mean_b, float rden) {
    return bf16r(bf16r(x - mean_b) * rden);
}
__device__ __forceinline__ void pdl_wait() { asm volatile("griddepcontrol.wait;" ::: "memory"); }
__device__ __forceinline__ void pdl_launch() { asm volatile("griddepcontrol.launch_dependents;" ::: "memory"); }
__device__ __forceinline__ void cluster_arrive() { asm volatile("barrier.cluster.arrive.release.aligned;" ::: "memory"); }
__device__ __forceinline__ void cluster_wait() { asm volatile("barrier.cluster.wait.acquire.aligned;" ::: "memory"); }

constexpr int K1_THREADS = 288;
constexpr int K1_SMEM = 131072 + 4 * 24576 + 128 + 1024;

__device__ __forceinline__ void ldsm4(uint32_t* r, uint32_t addr) {
    asm volatile("ldmatrix.sync.aligned.m8n8.x4.shared.b16 {%0, %1, %2, %3}, [%4];" : "=r"(r[0]), "=r"(r[1]), "=r"(r[2]), "=r"(r[3]) : "r"(addr) : "memory");
}
__device__ __forceinline__ void stsm4(uint32_t addr, uint32_t r0, uint32_t r1, uint32_t r2, uint32_t r3) {
    asm volatile("stmatrix.sync.aligned.m8n8.x4.shared.b16 [%0], {%1, %2, %3, %4};" :: "r"(addr), "r"(r0), "r"(r1), "r"(r2), "r"(r3) : "memory");
}
__device__ __forceinline__ void mma16816(float* d, const uint32_t* a, uint32_t b0, uint32_t b1) {
    asm("mma.sync.aligned.m16n8k16.row.col.f32.bf16.bf16.f32 {%0,%1,%2,%3}, {%4,%5,%6,%7}, {%8,%9}, {%0,%1,%2,%3};"
        : "+f"(d[0]), "+f"(d[1]), "+f"(d[2]), "+f"(d[3]) : "r"(a[0]), "r"(a[1]), "r"(a[2]), "r"(a[3]), "r"(b0), "r"(b1));
}
__device__ __forceinline__ uint32_t sub_bf16x2(uint32_t a, uint32_t b) {
    uint32_t d; asm("sub.rn.bf16x2 %0, %1, %2;" : "=r"(d) : "r"(a), "r"(b)); return d;
}

__device__ __forceinline__ void k1_epilogue(const float* acc, float rs0, float rs1, uint32_t stage, int nt, int mt, int wg, int w4, int lane, bool live) {
    const int g8a = mt * 16 + wg * 8 + w4 * 2;
    const float rv0 = is_poly_group(g8a) ? -rs0 : rs0, rv1 = is_poly_group(g8a + 1) ? -rs1 : rs1;
    const int mi = lane >> 3, lr = lane & 7;
    const uint32_t off_qk = stage + (w4 * 2 + (mi & 1)) * 256 + (mi >> 1) * 128 + lr * 16;
    const uint32_t off_v = stage + (mi >> 1) * 1024 + (w4 * 16 + (mi & 1) * 8 + lr) * 16;
    #pragma unroll
    for (int jj = 0; jj < 12; jj++) {
        const bool isv = nt * 12 + jj >= 64;
        const float m0 = isv ? rv0 : rs0, m1 = isv ? rv1 : rs1;
        const uint32_t r0 = pack_bf16(acc[8 * jj] * m0, acc[8 * jj + 1] * m0), r1 = pack_bf16(acc[8 * jj + 2] * m1, acc[8 * jj + 3] * m1);
        const uint32_t r2 = pack_bf16(acc[8 * jj + 4] * m0, acc[8 * jj + 5] * m0), r3 = pack_bf16(acc[8 * jj + 6] * m1, acc[8 * jj + 7] * m1);
        const uint32_t addr = (isv ? off_v : off_qk) + (jj >> 2) * 16384 + (jj & 3) * 2048;
        if (live) stsm4(addr, r0, r1, r2, r3);
    }
    if (live) {
        fence_async_smem();
        named_bar(1 + wg, 128);
        const int pc = w4 * 6 + lane;
        if (lane < 6) {
            const int jj = pc >> 1, hf = pc & 1, hg = nt * 12 + jj;
            const unsigned char* dst = (const unsigned char*)g_QKV + (size_t)hg * 65536
                + (hg >= 64 ? hf * 32768 + (mt * 128 + wg * 64) * 16 : (mt * 16 + wg * 8) * 256 + hf * 1024);
            asm volatile("cp.async.bulk.global.shared::cta.bulk_group [%0], [%1], 1024;"
                         :: "l"(dst), "r"(stage + (jj >> 2) * 16384 + (jj & 3) * 2048 + hf * 1024) : "memory");
            asm volatile("cp.async.bulk.commit_group;" ::: "memory");
            asm volatile("cp.async.bulk.wait_group.read 0;" ::: "memory");
        }
    }
}

__global__ void __launch_bounds__(K1_THREADS, 1)
k1_ln_qkv(const __grid_constant__ CUtensorMap wmap, const __grid_constant__ CUtensorMap xmap, const __nv_bfloat16* __restrict__ w_r) {
    extern __shared__ __align__(1024) unsigned char smem[];
    const uint32_t sA = smem_u32(smem), sB = sA + 131072, sBar = sB + 4 * 24576;
    const int warp = __shfl_sync(~0u, threadIdx.x >> 5, 0), lane = threadIdx.x & 31;
    const int nt = blockIdx.x & 7, mt = blockIdx.x >> 3;
    const bool producer = warp == 8;
    const int wg = (warp >> 2) & 1;
    TL(0, 0);
    pdl_launch();
    if (producer) {
        if (lane == 0) {
            for (int i = 0; i < 4; i++) { mbar_init(sBar + i * 8, 1); mbar_init(sBar + 32 + i * 8, 2); }
            mbar_init(sBar + 64, 1); mbar_init(sBar + 72, 1);
            asm volatile("fence.mbarrier_init.release.cluster;" ::: "memory");
            mbar_expect_tx(sBar + 64, 65536); mbar_expect_tx(sBar + 72, 65536);
            for (int i = 0; i < 4; i++) mbar_expect_tx(sBar + i * 8, 24576);
        }
        __syncwarp();
        if (lane < 16) tma_2d(sA + (lane & 7) * 16384 + (lane >> 3) * 8192, &xmap, (lane & 7) * 64, mt * 128 + (lane >> 3) * 64, sBar + 64 + (lane >> 3) * 8);
        else if (lane < 28) {
            const int kc = (lane - 16) / 3, j = (lane - 16) % 3;
            tma_2d(sB + kc * 24576 + j * 8192, &wmap, nt * 192 + j * 64, kc * 64, sBar + kc * 8);
        }
    }
    uint32_t* s_wr = (uint32_t*)(smem + 131072 + 4 * 24576 + 128);
    if (threadIdx.x < 256) s_wr[threadIdx.x] = __ldg((const uint32_t*)w_r + threadIdx.x);
    __syncthreads();
    float acc[96];
    #pragma unroll
    for (int i = 0; i < 96; i++) acc[i] = 0.f;
    float rs0 = 0.f, rs1 = 0.f;
    #pragma unroll 1
    for (int round = 0; round < 2; round++) {
    if (producer) {
        if (round) {
            if (lane < 3) {
                for (int kc = 4; kc < 8; kc++) {
                    const int st = kc & 3;
                    mbar_wait(sBar + 32 + st * 8, 0);
                    if (lane == 0) mbar_expect_tx(sBar + st * 8, 24576);
                    __syncwarp(7);
                    tma_2d(sB + st * 24576 + lane * 8192, &wmap, nt * 192 + lane * 64, kc * 64, sBar + st * 8);
                }
            }
            break;
        }
    } else {
        const int g = lane >> 2, t = lane & 3;
        const int lrow = warp * 16 + (lane & 7) + ((lane >> 3) & 1) * 8;
        const uint32_t lbase = sA + lrow * 128;
        const int lsw = lane & 7, lhi = lane >> 4;
        if (round) { TL(0, 1); mbar_wait(sBar + 64 + wg * 8, 0); TL(0, 8); }
        float dsum[4] = {0.f, 0.f, 0.f, 0.f}, dq0[4] = {0.f, 0.f, 0.f, 0.f}, dq1[4] = {0.f, 0.f, 0.f, 0.f};
        float esum[4] = {0.f, 0.f, 0.f, 0.f}, eq0[4] = {0.f, 0.f, 0.f, 0.f}, eq1[4] = {0.f, 0.f, 0.f, 0.f};
        uint32_t laddr[4];
        #pragma unroll
        for (int k4 = 0; k4 < 4; k4++) laddr[k4] = lbase + (((k4 * 2 + lhi) ^ lsw) * 16);
        #pragma unroll 1
        for (int pn = 0; pn < (round ? 8 : 1); pn++) {
            uint32_t a[4][4];
            #pragma unroll
            for (int k4 = 0; k4 < 4; k4++) ldsm4(a[k4], laddr[k4] + pn * 16384);
            #pragma unroll
            for (int k4 = 0; k4 < 4; k4 += 2) {
                mma16816(dsum, a[k4], 0x3F803F80u, 0x3F803F80u);
                mma16816(dq0, a[k4], a[k4][0], a[k4][2]);
                mma16816(dq1, a[k4], a[k4][1], a[k4][3]);
                mma16816(esum, a[k4 + 1], 0x3F803F80u, 0x3F803F80u);
                mma16816(eq0, a[k4 + 1], a[k4 + 1][0], a[k4 + 1][2]);
                mma16816(eq1, a[k4 + 1], a[k4 + 1][1], a[k4 + 1][3]);
            }
        }
        #pragma unroll
        for (int i = 0; i < 4; i++) { dsum[i] += esum[i]; dq0[i] += eq0[i]; dq1[i] += eq1[i]; }
        const int dsrc = g * 4 + (g >> 1);
        float sq0 = __shfl_sync(~0u, (g & 1) ? dq0[1] : dq0[0], dsrc), sq1 = __shfl_sync(~0u, (g & 1) ? dq1[3] : dq1[2], dsrc);
        const float mean0 = dsum[0] * (1.0f / D_), mean1 = dsum[2] * (1.0f / D_);
        float var0 = fmaf(-mean0, mean0, sq0 * (1.0f / D_)), var1 = fmaf(-mean1, mean1, sq1 * (1.0f / D_));
        if (round && __any_sync(~0u, !(mean0 * mean0 <= 16.0f * var0) || !(mean1 * mean1 <= 16.0f * var1))) {
            float q0 = 0.f, q1 = 0.f;
            #pragma unroll 1
            for (int ks = 0; ks < 32; ks++) {
                uint32_t a[4];
                ldsm4(a, lbase + (ks >> 2) * 16384 + ((((ks & 3) * 2 + lhi) ^ lsw) * 16));
                #pragma unroll
                for (int i = 0; i < 4; i++) {
                    const float m = (i & 1) ? mean1 : mean0;
                    const float d0 = bf_lo(a[i]) - m, d1 = bf_hi(a[i]) - m;
                    if (i & 1) q1 = fmaf(d0, d0, fmaf(d1, d1, q1)); else q0 = fmaf(d0, d0, fmaf(d1, d1, q0));
                }
            }
            q0 += __shfl_xor_sync(~0u, q0, 1); q0 += __shfl_xor_sync(~0u, q0, 2);
            q1 += __shfl_xor_sync(~0u, q1, 1); q1 += __shfl_xor_sync(~0u, q1, 2);
            var0 = q0 * (1.0f / D_); var1 = q1 * (1.0f / D_);
        }
        rs0 = __frcp_rn(bf16r(__fsqrt_rn(bf16r(bf16r(var0) + 1e-5f))));
        rs1 = __frcp_rn(bf16r(__fsqrt_rn(bf16r(bf16r(var1) + 1e-5f))));
        const uint32_t m20 = pack_bf16(mean0, mean0), m21 = pack_bf16(mean1, mean1);
        float dr[4] = {0.f, 0.f, 0.f, 0.f}, er[4] = {0.f, 0.f, 0.f, 0.f};
        #pragma unroll 1
        for (int pn = 0; pn < (round ? 8 : 2); pn += 2) {
            uint32_t a[8][4];
            #pragma unroll
            for (int k8 = 0; k8 < 8; k8++) ldsm4(a[k8], laddr[k8 & 3] + (pn + (k8 >> 2)) * 16384);
            #pragma unroll
            for (int k8 = 0; k8 < 8; k8++) {
                a[k8][0] = sub_bf16x2(a[k8][0], m20); a[k8][1] = sub_bf16x2(a[k8][1], m21);
                a[k8][2] = sub_bf16x2(a[k8][2], m20); a[k8][3] = sub_bf16x2(a[k8][3], m21);
            }
            if (round) {
                #pragma unroll
                for (int k8 = 0; k8 < 8; k8++) stsm4(laddr[k8 & 3] + (pn + (k8 >> 2)) * 16384, a[k8][0], a[k8][1], a[k8][2], a[k8][3]);
            }
            if (nt == 0) {
                #pragma unroll
                for (int k8 = 0; k8 < 8; k8++)
                    mma16816((k8 & 1) ? er : dr, a[k8], s_wr[(pn * 4 + k8) * 8 + t], s_wr[(pn * 4 + k8) * 8 + 4 + t]);
            }
        }
        dr[0] += er[0]; dr[2] += er[2];
        if (!round) continue;
        if (nt == 0 && t == 0) {
            const int row = mt * 128 + warp * 16 + g;
            g_r[row] = bf16r(dr[0] * rs0); g_r[row + 8] = bf16r(dr[2] * rs1);
            g_stats[row] = make_float2(bf_lo(m20), rs0); g_stats[row + 8] = make_float2(bf_lo(m21), rs1);
        }
        TL(0, 2);
        fence_async_smem();
        named_bar(1 + wg, 128);
        TL(0, 3);
        const uint64_t da0 = make_desc(sA + wg * 8192, 16, 1024, 1);
        const uint64_t db0 = make_desc(sB, 8192, 1024, 1);
        #pragma unroll 1
        for (int kc = 0; kc < 8; kc++) {
            const int st = kc & 3;
            mbar_wait(sBar + st * 8, kc >> 2);
            WG_FENCE();
            #pragma unroll
            for (int kk = 0; kk < 4; kk++)
                wgmma_n192(acc, da0 + (uint64_t)(kc * 1024 + kk * 2), db0 + (uint64_t)(st * 1536 + kk * 128));
            WG_COMMIT();
            wg_wait<1>();
            if (kc >= 1 && kc <= 4 && (threadIdx.x & 127) == 0) mbar_arrive(sBar + 32 + (kc - 1) * 8);
        }
        wg_wait<0>();
        touch96(acc);
        named_bar(1 + wg, 128);
        TL(0, 5);
    }
    k1_epilogue(acc, rs0, rs1, sA + wg * 8192, nt, mt, wg, warp & 3, lane, !producer);
    TL(0, 6);
    }
}

constexpr int K2_THREADS = 512;
constexpr int K2_SMEM = 65536 + 98304 + 16384 + 128;

constexpr float QS = 0.25f * 1.4426950408889634f;
__device__ __forceinline__ uint32_t polyexp(float s, float cb, uint32_t c421, float c3, float one) {
    float u;
    asm("fma.rn.sat.f32 %0, %1, %2, %3;" : "=f"(u) : "f"(s), "f"(QS * (1.0f / 255.0f)), "f"(cb));
    float z = fmaf(u, 0.99609375f, one);
    uint32_t rb;
    asm("lop3.b32 %0, %1, 0xFFFF8000, %2, 0xEA;" : "=r"(rb) : "r"(__float_as_uint(z)), "r"(c421));
    float f = z - __uint_as_float(rb);
    float h = fmaf(f, c3, 58.86525f);
    h = fmaf(f, h, -0.29870507f);
    return __float_as_uint(fmaf(f, h, z));
}

struct ExpC { float nm0, nm1, cb0, cb1, c3, one; uint32_t c421; };

template <int G>
__device__ __forceinline__ void exp_block(const float* s, uint32_t* p, const ExpC& c) {
    #pragma unroll
    for (int hf = 0; hf < 2; hf++) {
        const float* x = s + hf * 4;
        if ((PMASK >> (G + hf)) & 1) {
            p[hf * 2 + 0] = __byte_perm(polyexp(x[0], c.cb0, c.c421, c.c3, c.one), polyexp(x[1], c.cb0, c.c421, c.c3, c.one), 0x6521);
            p[hf * 2 + 1] = __byte_perm(polyexp(x[2], c.cb1, c.c421, c.c3, c.one), polyexp(x[3], c.cb1, c.c421, c.c3, c.one), 0x6521);
        } else {
            p[hf * 2 + 0] = pack_bf16(ex2(fmaf(x[0], QS, c.nm0)), ex2(fmaf(x[1], QS, c.nm0)));
            p[hf * 2 + 1] = pack_bf16(ex2(fmaf(x[2], QS, c.nm1)), ex2(fmaf(x[3], QS, c.nm1)));
        }
    }
}

__device__ __forceinline__ void max16(const float* s, float& mx0, float& mx1) {
    #pragma unroll
    for (int j = 0; j < 4; j++) {
        mx0 = fmaxf(mx0, fmaxf(s[4 * j], s[4 * j + 1]));
        mx1 = fmaxf(mx1, fmaxf(s[4 * j + 2], s[4 * j + 3]));
    }
}

__device__ void moe_cta(int part, unsigned char* smem, const __nv_bfloat16* __restrict__ x, const __nv_bfloat16* __restrict__ w_gate,
                        const __nv_bfloat16* __restrict__ w_up, const __nv_bfloat16* __restrict__ w_down) {
    float* xs = (float*)smem;
    float* red = xs + 1024;
    float* hs = red + 8 * 4 * 448;
    __shared__ float s_v[32];
    __shared__ int s_i[32];
    __shared__ int s_sel[2];
    const int tid = threadIdx.x, warp = tid >> 5, lane = tid & 31;
    for (int pass = 0; pass < 2; pass++) {
        float bv = -INFINITY; int bi = 0x7fffffff;
        const int excl = pass ? s_sel[0] : -1;
        for (int i = tid; i < S_; i += K2_THREADS) {
            float v = g_r[i];
            if (i != excl && (v > bv || (v == bv && i < bi) || bi == 0x7fffffff)) { bv = v; bi = i; }
        }
        #pragma unroll
        for (int o = 16; o; o >>= 1) {
            float ov = __shfl_xor_sync(~0u, bv, o); int oi = __shfl_xor_sync(~0u, bi, o);
            if (ov > bv || (ov == bv && oi < bi)) { bv = ov; bi = oi; }
        }
        if (lane == 0) { s_v[warp] = bv; s_i[warp] = bi; }
        __syncthreads();
        if (warp == 0) {
            bv = lane < 16 ? s_v[lane] : -INFINITY; bi = lane < 16 ? s_i[lane] : 0x7fffffff;
            #pragma unroll
            for (int o = 16; o; o >>= 1) {
                float ov = __shfl_xor_sync(~0u, bv, o); int oi = __shfl_xor_sync(~0u, bi, o);
                if (ov > bv || (ov == bv && oi < bi)) { bv = ov; bi = oi; }
            }
            if (lane == 0) s_sel[pass] = (bi == 0x7fffffff) ? pass : bi;
        }
        __syncthreads();
    }
    for (int i = tid; i < 1024; i += K2_THREADS) {
        const int tok = s_sel[i >> 9];
        const float2 st = g_stats[tok];
        xs[i] = ln_elem(__bfloat162float(x[(size_t)tok * D_ + (i & 511)]), st.x, st.y);
    }
    if (part == 0 && tid < 2) g_sel[tid] = s_sel[tid];
    __syncthreads();
    const int c0 = part * 448;
    if (tid < 448) {
        const int cg = tid % 56, ks = tid / 56;
        float a[4][8];
        #pragma unroll
        for (int i = 0; i < 4; i++)
            #pragma unroll
            for (int j = 0; j < 8; j++) a[i][j] = 0.f;
        const __nv_bfloat16* pg = w_gate + (size_t)(ks * 64) * F_ + c0 + cg * 8;
        const __nv_bfloat16* pu = w_up + (size_t)(ks * 64) * F_ + c0 + cg * 8;
        #pragma unroll 8
        for (int k = 0; k < 64; k++) {
            const uint4 gv = __ldg((const uint4*)(pg + (size_t)k * F_));
            const uint4 uv = __ldg((const uint4*)(pu + (size_t)k * F_));
            const float x0 = xs[ks * 64 + k], x1 = xs[512 + ks * 64 + k];
            const uint32_t gu[4] = {gv.x, gv.y, gv.z, gv.w}, uu[4] = {uv.x, uv.y, uv.z, uv.w};
            #pragma unroll
            for (int j = 0; j < 4; j++) {
                const float g0 = bf_lo(gu[j]), g1 = bf_hi(gu[j]), u0 = bf_lo(uu[j]), u1 = bf_hi(uu[j]);
                a[0][2 * j] = fmaf(x0, g0, a[0][2 * j]); a[0][2 * j + 1] = fmaf(x0, g1, a[0][2 * j + 1]);
                a[1][2 * j] = fmaf(x1, g0, a[1][2 * j]); a[1][2 * j + 1] = fmaf(x1, g1, a[1][2 * j + 1]);
                a[2][2 * j] = fmaf(x0, u0, a[2][2 * j]); a[2][2 * j + 1] = fmaf(x0, u1, a[2][2 * j + 1]);
                a[3][2 * j] = fmaf(x1, u0, a[3][2 * j]); a[3][2 * j + 1] = fmaf(x1, u1, a[3][2 * j + 1]);
            }
        }
        #pragma unroll
        for (int i = 0; i < 4; i++)
            #pragma unroll
            for (int j = 0; j < 8; j++) red[(ks * 4 + i) * 448 + cg * 8 + j] = a[i][j];
    }
    __syncthreads();
    for (int i = tid; i < 896; i += K2_THREADS) {
        const int tok = i / 448, c = i % 448;
        float gs = 0.f, us = 0.f;
        #pragma unroll
        for (int ks = 0; ks < 8; ks++) { gs += red[(ks * 4 + tok) * 448 + c]; us += red[(ks * 4 + 2 + tok) * 448 + c]; }
        gs = bf16r(gs); us = bf16r(us);
        const float sl = bf16r(gs / (1.0f + __expf(-gs)));
        hs[i] = bf16r(sl * us);
    }
    __syncthreads();
    {
        const int cg = tid & 63, fs = tid >> 6;
        float a[2][8];
        #pragma unroll
        for (int j = 0; j < 8; j++) { a[0][j] = 0.f; a[1][j] = 0.f; }
        const __nv_bfloat16* pd = w_down + (size_t)(c0 + fs * 56) * D_ + cg * 8;
        #pragma unroll 8
        for (int f = 0; f < 56; f++) {
            const uint4 dv = __ldg((const uint4*)(pd + (size_t)f * D_));
            const float h0 = hs[fs * 56 + f], h1 = hs[448 + fs * 56 + f];
            const uint32_t du[4] = {dv.x, dv.y, dv.z, dv.w};
            #pragma unroll
            for (int j = 0; j < 4; j++) {
                const float d0 = bf_lo(du[j]), d1 = bf_hi(du[j]);
                a[0][2 * j] = fmaf(h0, d0, a[0][2 * j]); a[0][2 * j + 1] = fmaf(h0, d1, a[0][2 * j + 1]);
                a[1][2 * j] = fmaf(h1, d0, a[1][2 * j]); a[1][2 * j + 1] = fmaf(h1, d1, a[1][2 * j + 1]);
            }
        }
        #pragma unroll
        for (int j = 0; j < 8; j++) { red[(fs * 2) * 512 + cg * 8 + j] = a[0][j]; red[(fs * 2 + 1) * 512 + cg * 8 + j] = a[1][j]; }
    }
    __syncthreads();
    for (int i = tid; i < 1024; i += K2_THREADS) {
        float s = 0.f;
        #pragma unroll
        for (int fs = 0; fs < 8; fs++) s += red[(fs * 2 + (i >> 9)) * 512 + (i & 511)];
        g_ypart[part][i >> 9][i & 511] = s;
    }
}

__global__ void __launch_bounds__(K2_THREADS, 1)
k2_attn(const __nv_bfloat16* __restrict__ x, const __nv_bfloat16* __restrict__ w_gate, const __nv_bfloat16* __restrict__ w_up,
        const __nv_bfloat16* __restrict__ w_down) {
    extern __shared__ __align__(1024) unsigned char smem[];
    TL(1, 0);
    pdl_launch();
    if (blockIdx.x >= 128) {
        const int part = blockIdx.x - 128;
        {
            const int k = threadIdx.x;
            asm volatile("cp.async.bulk.prefetch.L2.global [%0], %1;" :: "l"(w_gate + (size_t)k * F_ + part * 448), "r"(896) : "memory");
            asm volatile("cp.async.bulk.prefetch.L2.global [%0], %1;" :: "l"(w_up + (size_t)k * F_ + part * 448), "r"(896) : "memory");
            if (k < 56) asm volatile("cp.async.bulk.prefetch.L2.global [%0], %1;" :: "l"(w_down + (size_t)(part * 448 + k * 8) * D_), "r"(8192) : "memory");
        }
        pdl_wait(); TL(1, 1); moe_cta(blockIdx.x - 128, smem, x, w_gate, w_up, w_down); TL(1, 2); return; }
    const uint32_t sK = smem_u32(smem), sV = sK + 65536, sQ = sV + 98304, sBar = sQ + 16384;
    const int h = blockIdx.x >> 2, qb = blockIdx.x & 3;
    const int warp = __shfl_sync(~0u, threadIdx.x >> 5, 0), lane = threadIdx.x & 31, wg = warp >> 2;
    if (threadIdx.x == 0) {
        mbar_init(sBar, 1); mbar_init(sBar + 8, 1);
        asm volatile("fence.mbarrier_init.release.cluster;" ::: "memory");
        mbar_expect_tx(sBar, 16384 + 16384 + 2 * 8192);
        mbar_expect_tx(sBar + 8, 49152 + 2 * 24576);
    }
    for (int i = threadIdx.x; i < 2048; i += K2_THREADS) {
        const uint32_t v = is_poly_group(i >> 3) ? 0xBF80BF80u : 0x3F803F80u;
        *(uint4*)(smem + 65536 + 65536 + i * 16) = make_uint4(v, v, v, v);
    }
    fence_async_smem();
    __syncthreads();
    if (warp == 0) {
        pdl_wait();
        TL(1, 1);
        const uint4* gk = g_K + (size_t)h * 4096;
        const uint4* gv = g_V + (size_t)h * 4096;
        if (lane == 0) bulk_g2s(sQ, g_Q + (size_t)h * 4096 + qb * 1024, 16384, sBar);
        if (lane == 1) bulk_g2s(sK, gk, 16384, sBar);
        if (lane == 2) bulk_g2s(sV, gv, 8192, sBar);
        if (lane == 3) bulk_g2s(sV + 32768, gv + 2048, 8192, sBar);
        if (lane == 4) bulk_g2s(sK + 16384, gk + 1024, 49152, sBar + 8);
        if (lane == 5) bulk_g2s(sV + 8192, gv + 512, 24576, sBar + 8);
        if (lane == 6) bulk_g2s(sV + 32768 + 8192, gv + 2048 + 512, 24576, sBar + 8);
        __syncwarp();
    }
    ExpC c;
    {
        const volatile uint32_t* cc = g_const;
        c.c421 = cc[0]; c.c3 = __uint_as_float(cc[1]); c.one = __uint_as_float(cc[2]);
    }
    const uint32_t kdesc0 = (uint32_t)make_desc(sK, 128, 256, 0);
    const uint32_t vdesc0 = (uint32_t)make_desc(sV, 128, 32768, 0);
    #pragma unroll 1
    for (int pass = wg ? -1 : 0; pass < 2; pass++) {
        const bool dry = pass < 0;
        if (pass == 0) { mbar_wait(sBar, 0); __syncwarp(); TL(1, 2); }
        const int unit = (pass & 1) * 4 + wg;
        const uint32_t q = (uint32_t)make_desc(sQ + unit * 2048, 128, 256, 0);
        float o[12];
        #pragma unroll 1
        for (int attempt = 0; attempt < 2; attempt++) {
            float s0[16], s1[16], s2[16];
            #pragma unroll
            for (int i = 0; i < 16; i++) { s0[i] = 0.f; s1[i] = 0.f; s2[i] = 0.f; }
            float mx0 = -INFINITY, mx1 = -INFINITY;
            if (attempt) {
                #pragma unroll 1
                for (int it = 0; it < 64; it++) {
                    WG_FENCE();
                    wgmma_qk32(s0, q, kdesc0 + it * 64);
                    WG_COMMIT();
                    wg_wait<0>();
                    touch16(s0);
                    max16(s0, mx0, mx1);
                }
            }
            #pragma unroll
            for (int i = 0; i < 12; i++) o[i] = 0.f;
            WG_FENCE();
            wgmma_qk32(s2, q, kdesc0);
            wgmma_qk32(s0, q, kdesc0 + 64);
            wgmma_qk32(s1, q, kdesc0 + 128);
            WG_COMMIT();
            wg_wait<0>();
            touch16(s0); touch16(s1); touch16(s2);
            max16(s0, mx0, mx1); max16(s1, mx0, mx1); max16(s2, mx0, mx1);
            mx0 = fmaxf(mx0, __shfl_xor_sync(~0u, mx0, 1)); mx0 = fmaxf(mx0, __shfl_xor_sync(~0u, mx0, 2));
            mx1 = fmaxf(mx1, __shfl_xor_sync(~0u, mx1, 1)); mx1 = fmaxf(mx1, __shfl_xor_sync(~0u, mx1, 2));
            const float bias = attempt ? 0.0f : 64.0f;
            c.nm0 = __shfl_sync(~0u, -fmaf(mx0, QS, bias), lane); c.nm1 = __shfl_sync(~0u, -fmaf(mx1, QS, bias), lane);
            c.cb0 = __shfl_sync(~0u, (127.0f + c.nm0) * (1.0f / 255.0f), lane);
            c.cb1 = __shfl_sync(~0u, (127.0f + c.nm1) * (1.0f / 255.0f), lane);
            uint32_t kd = kdesc0 + 192, vd = vdesc0 + 32;
            {
                uint32_t pa[4], pb[4];
                exp_block<12>(s2, pa, c);
                exp_block<14>(s2 + 8, pb, c);
                WG_FENCE();
                wgmma_pv(o, pa, vdesc0); wgmma_pv(o, pb, vdesc0 + 16);
                WG_COMMIT();
            }
            #pragma unroll 1
            for (int seg = 0; seg < (dry ? 1 : 2); seg++) {
            if (seg) { wg_wait<0>(); mbar_wait(sBar + 8, 0); __syncwarp(); }
            #pragma unroll 1
            for (int it = seg ? 3 : (dry ? 2 : 0); it < (seg ? 21 : 3); it++) {
                uint32_t p[6][4];
                WG_FENCE();
                wgmma_qk32(s2, q, kd);
                WG_COMMIT();
                exp_block<0>(s0, p[0], c);
                exp_block<2>(s0 + 8, p[1], c);
                WG_FENCE();
                wgmma_pv(o, p[0], vd); wgmma_pv(o, p[1], vd + 16);
                wgmma_qk32(s0, q, kd + 64);
                WG_COMMIT();
                wg_wait<1>();
                touch16(s2);
                exp_block<4>(s1, p[2], c);
                exp_block<6>(s1 + 8, p[3], c);
                WG_FENCE();
                wgmma_pv(o, p[2], vd + 32); wgmma_pv(o, p[3], vd + 48);
                wgmma_qk32(s1, q, kd + 128);
                WG_COMMIT();
                wg_wait<1>();
                touch16(s0);
                exp_block<8>(s2, p[4], c);
                exp_block<10>(s2 + 8, p[5], c);
                WG_FENCE();
                wgmma_pv(o, p[4], vd + 64); wgmma_pv(o, p[5], vd + 80);
                WG_COMMIT();
                vd += 96; kd += 192;
                wg_wait<1>();
                touch16(s1);
            }
            }
            wg_wait<0>();
            touch12(o);
            if (attempt) break;
            float big = 0.f;
            #pragma unroll
            for (int i = 0; i < 12; i++) big = fmaxf(big, fabsf(o[i]));
            bool bad = !(big < 1e30f);
            #pragma unroll
            for (int i = 0; i < 12; i++) bad |= (o[i] != o[i]);
            uint32_t any;
            asm volatile("{.reg .pred p, q; setp.ne.u32 p, %1, 0; barrier.cta.red.or.pred.aligned q, %2, 128, p; selp.u32 %0, 1, 0, q;}"
                         : "=r"(any) : "r"((uint32_t)bad), "r"(1 + wg) : "memory");
            if (dry || !__any_sync(~0u, any)) break;
        }
        const int g = lane >> 2, t = lane & 3;
        const int r = (warp & 3) * 16 + g;
        const float i0 = __fdiv_rn(1.0f, o[8]), i1 = __fdiv_rn(1.0f, o[10]);
        uint32_t* ob = (uint32_t*)(g_O + (size_t)(qb * 8 + unit) * 4096 + (h >> 2) * 512 + r * 8) + t;
        const int c0 = ((h & 3) * 2) ^ (r & 7), c1 = ((h & 3) * 2 + 1) ^ (r & 7);
        if (!dry) {
            ob[c0 * 4] = pack_bf16(o[0] * i0, o[1] * i0);
            ob[c1 * 4] = pack_bf16(o[4] * i0, o[5] * i0);
            ob[256 + c0 * 4] = pack_bf16(o[2] * i1, o[3] * i1);
            ob[256 + c1 * 4] = pack_bf16(o[6] * i1, o[7] * i1);
            TL(1, 3 + pass);
        }
    }
}

constexpr int K3_THREADS = 256;
constexpr int K3_SMEM = 65536 + 131072 + 128;

__global__ void __launch_bounds__(K3_THREADS, 1)
k3_out(const __grid_constant__ CUtensorMap wmap, const __nv_bfloat16* __restrict__ x, __nv_bfloat16* __restrict__ out) {
    extern __shared__ __align__(1024) unsigned char smem[];
    const uint32_t sA = smem_u32(smem), sB = sA + 65536, sBar = sB + 131072;
    const int warp = __shfl_sync(~0u, threadIdx.x >> 5, 0), lane = threadIdx.x & 31, wg = warp >> 2;
    const int nt = blockIdx.x & 3, mt = blockIdx.x >> 2;
    TL(2, 0);
    if (threadIdx.x == 0) {
        for (int i = 0; i < 6; i++) mbar_init(sBar + i * 8, 1);
        asm volatile("fence.mbarrier_init.release.cluster;" ::: "memory");
        for (int kh = 0; kh < 2; kh++) {
            mbar_expect_tx(sBar + kh * 8, 65536);
            tma_2d(sB + kh * 32768, &wmap, nt * 128, kh * 256, sBar + kh * 8);
            tma_2d(sB + 65536 + kh * 32768, &wmap, nt * 128 + 64, kh * 256, sBar + kh * 8);
        }
    }
    const int er = threadIdx.x >> 2, ec = (threadIdx.x & 3) * 32;
    const int row = mt * 64 + er;
    uint4 xv[4];
    #pragma unroll
    for (int j = 0; j < 4; j++) xv[j] = __ldg((const uint4*)(x + (size_t)row * D_ + nt * 128 + ec) + j);
    pdl_wait();
    TL(2, 1);
    if (threadIdx.x == 0) {
        for (int q = 0; q < 4; q++) {
            mbar_expect_tx(sBar + 16 + q * 8, 16384);
            bulk_g2s(sA + q * 16384, g_O + (size_t)mt * 4096 + q * 1024, 16384, sBar + 16 + q * 8);
        }
    }
    const int sel0 = g_sel[0], sel1 = g_sel[1];
    const float2 st = g_stats[row];
    uint32_t bb[16];
    {
        const uint32_t xu[16] = {xv[0].x, xv[0].y, xv[0].z, xv[0].w, xv[1].x, xv[1].y, xv[1].z, xv[1].w,
                                 xv[2].x, xv[2].y, xv[2].z, xv[2].w, xv[3].x, xv[3].y, xv[3].z, xv[3].w};
        #pragma unroll
        for (int j = 0; j < 16; j++) bb[j] = pack_bf16(bf16r(bf_lo(xu[j]) - st.x) * st.y, bf16r(bf_hi(xu[j]) - st.x) * st.y);
        const int slot = row == sel0 ? 0 : (row == sel1 ? 1 : -1);
        if (slot >= 0) {
            const float gate = bf16r(1.0f / (1.0f + __expf(-g_r[row])));
            const int c0 = nt * 128 + ec;
            #pragma unroll
            for (int j = 0; j < 16; j++) {
                const float2 a = *(const float2*)&g_ypart[0][slot][c0 + 2 * j], b = *(const float2*)&g_ypart[1][slot][c0 + 2 * j];
                const float2 c = *(const float2*)&g_ypart[2][slot][c0 + 2 * j], d = *(const float2*)&g_ypart[3][slot][c0 + 2 * j];
                bb[j] = pack_bf16(bf_lo(bb[j]) + bf16r(bf16r(a.x + b.x + c.x + d.x) * gate), bf_hi(bb[j]) + bf16r(bf16r(a.y + b.y + c.y + d.y) * gate));
            }
        }
    }
    __syncthreads();
    float acc[32];
    #pragma unroll
    for (int i = 0; i < 32; i++) acc[i] = 0.f;
    const uint64_t da0 = make_desc(sA, 16, 1024, 1);
    const uint64_t db0 = make_desc(sB + wg * 65536, 8192, 1024, 1);
    #pragma unroll 1
    for (int q = 0; q < 4; q++) {
        if ((q & 1) == 0) mbar_wait(sBar + (q >> 1) * 8, 0);
        mbar_wait(sBar + 16 + q * 8, 0);
        WG_FENCE();
        #pragma unroll
        for (int kk = 0; kk < 8; kk++)
            wgmma_n64(acc, da0 + (uint64_t)(q * 1024 + (kk >> 2) * 512 + (kk & 3) * 2), db0 + (uint64_t)(q * 1024 + kk * 128));
        WG_COMMIT();
    }
    wg_wait<0>();
    touch32(acc);
    TL(2, 2);
    __syncthreads();
    {
        const int g = lane >> 2, t = lane & 3;
        unsigned char* sp = smem + ((warp & 3) * 16 + g) * 272 + wg * 128 + t * 4;
        #pragma unroll
        for (int j = 0; j < 8; j++) {
            *(uint32_t*)(sp + j * 16) = pack_bf16(acc[4 * j], acc[4 * j + 1]);
            *(uint32_t*)(sp + 8 * 272 + j * 16) = pack_bf16(acc[4 * j + 2], acc[4 * j + 3]);
        }
    }
    __syncthreads();
    #pragma unroll
    for (int j = 0; j < 4; j++) {
        const uint4 av = *(const uint4*)(smem + er * 272 + ec * 2 + j * 16);
        const uint32_t au[4] = {av.x, av.y, av.z, av.w}, xu[4] = {xv[j].x, xv[j].y, xv[j].z, xv[j].w};
        uint32_t o[4];
        #pragma unroll
        for (int i = 0; i < 4; i++) {
            uint32_t t2;
            asm("add.rn.bf16x2 %0, %1, %2;" : "=r"(t2) : "r"(xu[i]), "r"(au[i]));
            asm("add.rn.bf16x2 %0, %1, %2;" : "=r"(o[i]) : "r"(t2), "r"(bb[j * 4 + i]));
        }
        *((uint4*)(out + (size_t)row * D_ + nt * 128 + ec) + j) = make_uint4(o[0], o[1], o[2], o[3]);
    }
    TL(2, 3);
}

typedef CUresult (*EncodeFn)(CUtensorMap*, CUtensorMapDataType, cuuint32_t, void*, const cuuint64_t*, const cuuint64_t*,
                             const cuuint32_t*, const cuuint32_t*, CUtensorMapInterleave, CUtensorMapSwizzle,
                             CUtensorMapL2promotion, CUtensorMapFloatOOBfill);

void make_wmap(EncodeFn fn, CUtensorMap* map, const void* ptr, int rows, int cols, int box_rows) {
    cuuint64_t dims[2] = {(cuuint64_t)cols, (cuuint64_t)rows};
    cuuint64_t strides[1] = {(cuuint64_t)cols * 2};
    cuuint32_t box[2] = {64, (cuuint32_t)box_rows};
    cuuint32_t es[2] = {1, 1};
    fn(map, CU_TENSOR_MAP_DATA_TYPE_BFLOAT16, 2, (void*)ptr, dims, strides, box, es, CU_TENSOR_MAP_INTERLEAVE_NONE,
       CU_TENSOR_MAP_SWIZZLE_128B, CU_TENSOR_MAP_L2_PROMOTION_L2_256B, CU_TENSOR_MAP_FLOAT_OOB_FILL_NONE);
}

}

extern "C" void kernel_launch(void* const* d_in, const int* in_sizes, int n_in, void* d_out, int out_size) {
    const __nv_bfloat16* x = (const __nv_bfloat16*)d_in[0];
    const __nv_bfloat16* wqkv = (const __nv_bfloat16*)d_in[1];
    const __nv_bfloat16* wo = (const __nv_bfloat16*)d_in[2];
    const __nv_bfloat16* w_r = (const __nv_bfloat16*)d_in[4];
    const __nv_bfloat16* w_gate = (const __nv_bfloat16*)d_in[5];
    const __nv_bfloat16* w_up = (const __nv_bfloat16*)d_in[6];
    const __nv_bfloat16* w_down = (const __nv_bfloat16*)d_in[7];
    __nv_bfloat16* out = (__nv_bfloat16*)d_out;

    static EncodeFn encode = nullptr;
    if (!encode) {
        void* fn = nullptr;
        cudaDriverEntryPointQueryResult qres;
        cudaGetDriverEntryPoint("cuTensorMapEncodeTiled", &fn, cudaEnableDefault, &qres);
        encode = (EncodeFn)fn;
        cudaFuncSetAttribute(k1_ln_qkv, cudaFuncAttributeMaxDynamicSharedMemorySize, K1_SMEM);
        cudaFuncSetAttribute(k2_attn, cudaFuncAttributeMaxDynamicSharedMemorySize, K2_SMEM);
        cudaFuncSetAttribute(k3_out, cudaFuncAttributeMaxDynamicSharedMemorySize, K3_SMEM);
    }
    CUtensorMap map_qkv, map_wo, map_x;
    make_wmap(encode, &map_x, x, S_, D_, 64);
    make_wmap(encode, &map_qkv, wqkv, D_, 3 * D_, 64);
    make_wmap(encode, &map_wo, wo, D_, D_, 256);

    k1_ln_qkv<<<128, K1_THREADS, K1_SMEM, cudaStreamPerThread>>>(map_qkv, map_x, w_r);
    cudaLaunchAttribute at[1];
    at[0].id = cudaLaunchAttributeProgrammaticStreamSerialization;
    at[0].val.programmaticStreamSerializationAllowed = 1;
    cudaLaunchConfig_t cfg = {};
    cfg.stream = cudaStreamPerThread;
    cfg.attrs = at; cfg.numAttrs = 1;
    cfg.gridDim = dim3(132); cfg.blockDim = dim3(K2_THREADS); cfg.dynamicSmemBytes = K2_SMEM;
    cudaLaunchKernelEx(&cfg, k2_attn, x, w_gate, w_up, w_down);
    cfg.gridDim = dim3(128); cfg.blockDim = dim3(K3_THREADS); cfg.dynamicSmemBytes = K3_SMEM;
    cudaLaunchKernelEx(&cfg, k3_out, map_wo, x, out);
}
```

```cpp
#include <cuda_runtime.h>
#include <cuda_bf16.h>
#include <cuda.h>
#include <stdint.h>

namespace {

constexpr int S_ = 2048, D_ = 512, H_ = 32, F_ = 1792;

constexpr uint32_t PMASK = 0xA52;
__host__ __device__ constexpr bool is_poly_group(int g8) { return g8 >= 4 && ((PMASK >> ((g8 - 4) % 12)) & 1); }

__device__ __align__(1024) uint4 g_QKV[3 * H_ * S_ * 2];
#define g_Q (g_QKV)
#define g_K (g_QKV + H_ * S_ * 2)
#define g_V (g_QKV + 2 * H_ * S_ * 2)
__device__ __align__(1024) uint4 g_O[S_ * D_ / 8];
__device__ float2 g_stats[S_];
__device__ uint32_t g_const[4] = {421u, 0x459EB285u  , 0x3F800000u  , 0u};
__device__ float g_r[S_];
__device__ __align__(16) float g_ypart[4][2][D_];
__device__ int g_sel[2];

#define TL(k, p)
#define CK(i)
__device__ __forceinline__ uint32_t smem_u32(const void* p) { return (uint32_t)__cvta_generic_to_shared(p); }
__device__ __forceinline__ float bf16r(float x) { return __bfloat162float(__float2bfloat16_rn(x)); }
__device__ __forceinline__ uint32_t pack_bf16(float lo, float hi) {
    uint32_t r; asm("cvt.rn.bf16x2.f32 %0, %1, %2;" : "=r"(r) : "f"(hi), "f"(lo)); return r;
}
__device__ __forceinline__ float bf_lo(uint32_t u) { return __uint_as_float(u << 16); }
__device__ __forceinline__ float bf_hi(uint32_t u) { return __uint_as_float(u & 0xFFFF0000u); }
__device__ __forceinline__ float ex2(float x) { float y; asm("ex2.approx.ftz.f32 %0, %1;" : "=f"(y) : "f"(x)); return y; }

__device__ __forceinline__ void mbar_init(uint32_t bar, uint32_t count) {
    asm volatile("mbarrier.init.shared::cta.b64 [%0], %1;" :: "r"(bar), "r"(count) : "memory");
}
__device__ __forceinline__ void mbar_expect_tx(uint32_t bar, uint32_t bytes) {
    asm volatile("mbarrier.arrive.expect_tx.shared::cta.b64 _, [%0], %1;" :: "r"(bar), "r"(bytes) : "memory");
}
__device__ __forceinline__ void mbar_arrive(uint32_t bar) {
    asm volatile("mbarrier.arrive.shared::cta.b64 _, [%0];" :: "r"(bar) : "memory");
}
__device__ __forceinline__ void mbar_wait(uint32_t bar, uint32_t parity) {
    uint32_t done;
    #pragma unroll 1
    for (int it = 0; it < (1 << 26); it++) {
        asm volatile("{.reg .pred p; mbarrier.try_wait.parity.shared::cta.b64 p, [%1], %2; selp.u32 %0, 1, 0, p;}"
                     : "=r"(done) : "r"(bar), "r"(parity) : "memory");
        if (done) return;
    }
    __trap();
}
__device__ __forceinline__ void bulk_g2s(uint32_t dst, const void* src, uint32_t bytes, uint32_t bar) {
    asm volatile("cp.async.bulk.shared::cluster.global.mbarrier::complete_tx::bytes [%0], [%1], %2, [%3];"
                 :: "r"(dst), "l"(src), "r"(bytes), "r"(bar) : "memory");
}
__device__ __forceinline__ void tma_2d(uint32_t dst, const CUtensorMap* map, int c0, int c1, uint32_t bar) {
    asm volatile("cp.async.bulk.tensor.2d.shared::cluster.global.mbarrier::complete_tx::bytes [%0], [%1, {%3, %4}], [%2];"
                 :: "r"(dst), "l"(map), "r"(bar), "r"(c0), "r"(c1) : "memory");
}
__device__ __forceinline__ void fence_async_smem() { asm volatile("fence.proxy.async.shared::cta;" ::: "memory"); }
__device__ __forceinline__ void named_bar(int id, int n) { asm volatile("bar.sync %0, %1;" :: "r"(id), "r"(n) : "memory"); }

__device__ __forceinline__ uint64_t make_desc(uint32_t saddr, uint32_t lbo, uint32_t sbo, uint32_t swz) {
    return (uint64_t)((saddr & 0x3FFFF) >> 4) | ((uint64_t)(lbo >> 4) << 16) | ((uint64_t)(sbo >> 4) << 32) | ((uint64_t)swz << 62);
}
#define WG_FENCE() asm volatile("wgmma.fence.sync.aligned;" ::: "memory")
#define WG_COMMIT() asm volatile("wgmma.commit_group.sync.aligned;" ::: "memory")
template <int N> __device__ __forceinline__ void wg_wait() { asm volatile("wgmma.wait_group.sync.aligned %0;" :: "n"(N) : "memory"); }

#define F4(d, o) "+f"(d[o]), "+f"(d[o + 1]), "+f"(d[o + 2]), "+f"(d[o + 3])
#define F16(d, o) F4(d, o), F4(d, o + 4), F4(d, o + 8), F4(d, o + 12)
#define F32(d, o) F16(d, o), F16(d, o + 16)

__device__ __forceinline__ void wgmma_rs_n128(float* d, const uint32_t* a, uint64_t db) {
    asm volatile("wgmma.mma_async.sync.aligned.m64n128k16.f32.bf16.bf16 "
        "{%0,%1,%2,%3,%4,%5,%6,%7,%8,%9,%10,%11,%12,%13,%14,%15,%16,%17,%18,%19,%20,%21,%22,%23,%24,%25,%26,%27,%28,%29,%30,%31,"
        "%32,%33,%34,%35,%36,%37,%38,%39,%40,%41,%42,%43,%44,%45,%46,%47,%48,%49,%50,%51,%52,%53,%54,%55,%56,%57,%58,%59,%60,%61,%62,%63}, "
        "{%64,%65,%66,%67}, %68, 1, 1, 1, 1;\n"
        : F32(d, 0), F32(d, 32) : "r"(a[0]), "r"(a[1]), "r"(a[2]), "r"(a[3]), "l"(db));
}
__device__ __forceinline__ void wgmma_rs_n64(float* d, const uint32_t* a, uint64_t db) {
    asm volatile("wgmma.mma_async.sync.aligned.m64n64k16.f32.bf16.bf16 "
        "{%0,%1,%2,%3,%4,%5,%6,%7,%8,%9,%10,%11,%12,%13,%14,%15,%16,%17,%18,%19,%20,%21,%22,%23,%24,%25,%26,%27,%28,%29,%30,%31}, "
        "{%32,%33,%34,%35}, %36, 1, 1, 1, 1;\n"
        : F32(d, 0) : "r"(a[0]), "r"(a[1]), "r"(a[2]), "r"(a[3]), "l"(db));
}
__device__ __forceinline__ void wgmma_n64(float* d, uint64_t da, uint64_t db) {
    asm volatile("wgmma.mma_async.sync.aligned.m64n64k16.f32.bf16.bf16 "
        "{%0,%1,%2,%3,%4,%5,%6,%7,%8,%9,%10,%11,%12,%13,%14,%15,%16,%17,%18,%19,%20,%21,%22,%23,%24,%25,%26,%27,%28,%29,%30,%31}, "
        "%32, %33, 1, 1, 1, 0, 1;\n"
        : F32(d, 0) : "l"(da), "l"(db));
}
__device__ __forceinline__ void wgmma_qk32(float* d, uint32_t qd, uint32_t kd) {
    asm volatile("{.reg .b64 a, b; mov.b64 a, {%16, 16}; mov.b64 b, {%17, 16};\n"
        "wgmma.mma_async.sync.aligned.m64n32k16.f32.bf16.bf16 {%0,%1,%2,%3,%4,%5,%6,%7,%8,%9,%10,%11,%12,%13,%14,%15}, a, b, 0, 1, 1, 0, 0;}\n"
        : F16(d, 0) : "r"(qd), "r"(kd));
}
__device__ __forceinline__ void wgmma_pv(float* d, const uint32_t* a, uint32_t vd) {
    asm volatile("{.reg .b64 b; mov.b64 b, {%16, 2048};\n"
        "wgmma.mma_async.sync.aligned.m64n24k16.f32.bf16.bf16 {%0,%1,%2,%3,%4,%5,%6,%7,%8,%9,%10,%11}, {%12,%13,%14,%15}, b, 1, 1, 1, 1;}\n"
        : F4(d, 0), F4(d, 4), F4(d, 8) : "r"(a[0]), "r"(a[1]), "r"(a[2]), "r"(a[3]), "r"(vd));
}
__device__ __forceinline__ void touch16(float* d) { asm volatile("" : F16(d, 0) :: "memory"); }
__device__ __forceinline__ void touch12(float* d) { asm volatile("" : F4(d, 0), F4(d, 4), F4(d, 8) :: "memory"); }
__device__ __forceinline__ void touch32(float* d) { asm volatile("" : F32(d, 0) :: "memory"); }
__device__ __forceinline__ void touch64(float* d) { asm volatile("" : F32(d, 0), F32(d, 32) :: "memory"); }

__device__ __forceinline__ float ln_elem(float x, float mean_b, float rden) {
    return bf16r(bf16r(x - mean_b) * rden);
}
__device__ __forceinline__ void pdl_wait() { asm volatile("griddepcontrol.wait;" ::: "memory"); }
__device__ __forceinline__ void pdl_launch() { asm volatile("griddepcontrol.launch_dependents;" ::: "memory"); }
__device__ __forceinline__ void cluster_arrive() { asm volatile("barrier.cluster.arrive.release.aligned;" ::: "memory"); }
__device__ __forceinline__ void cluster_wait() { asm volatile("barrier.cluster.wait.acquire.aligned;" ::: "memory"); }

constexpr int K1_THREADS = 288;
constexpr int K1_SMEM = 131072 + 6 * 16384 + 128 + 1024;

__device__ __forceinline__ void ldsm4(uint32_t* r, uint32_t addr) {
    asm volatile("ldmatrix.sync.aligned.m8n8.x4.shared.b16 {%0, %1, %2, %3}, [%4];" : "=r"(r[0]), "=r"(r[1]), "=r"(r[2]), "=r"(r[3]) : "r"(addr) : "memory");
}
__device__ __forceinline__ void stsm4(uint32_t addr, uint32_t r0, uint32_t r1, uint32_t r2, uint32_t r3) {
    asm volatile("stmatrix.sync.aligned.m8n8.x4.shared.b16 [%0], {%1, %2, %3, %4};" :: "r"(addr), "r"(r0), "r"(r1), "r"(r2), "r"(r3) : "memory");
}
__device__ __forceinline__ void mma16816(float* d, const uint32_t* a, uint32_t b0, uint32_t b1) {
    asm("mma.sync.aligned.m16n8k16.row.col.f32.bf16.bf16.f32 {%0,%1,%2,%3}, {%4,%5,%6,%7}, {%8,%9}, {%0,%1,%2,%3};"
        : "+f"(d[0]), "+f"(d[1]), "+f"(d[2]), "+f"(d[3]) : "r"(a[0]), "r"(a[1]), "r"(a[2]), "r"(a[3]), "r"(b0), "r"(b1));
}
__device__ __forceinline__ uint32_t sub_bf16x2(uint32_t a, uint32_t b) {
    uint32_t d; asm("sub.rn.bf16x2 %0, %1, %2;" : "=r"(d) : "r"(a), "r"(b)); return d;
}

template <int NJ>
__device__ __forceinline__ void k1_store(const float* acc, int jj0, float rs0, float rs1, int nt, int row0, int lane) {
    const int g = lane >> 2, t = lane & 3, g8a = row0 >> 3;
    const float rv0 = is_poly_group(g8a) ? -rs0 : rs0, rv1 = is_poly_group(g8a + 1) ? -rs1 : rs1;
    const int off_qk = g8a * 64 + g * 4 + t, off_v = (row0 + g) * 4 + t;
    #pragma unroll
    for (int jj = 0; jj < NJ; jj++) {
        const int hg = nt * 12 + jj0 + jj;
        const bool isv = hg >= 64;
        const float m0 = isv ? rv0 : rs0, m1 = isv ? rv1 : rs1;
        uint32_t* base = (uint32_t*)g_QKV + (size_t)hg * 16384 + (isv ? off_v : off_qk);
        const int hs = isv ? 8192 : 32, rs = isv ? 32 : 64;
        base[0] = pack_bf16(acc[8 * jj] * m0, acc[8 * jj + 1] * m0);
        base[rs] = pack_bf16(acc[8 * jj + 2] * m1, acc[8 * jj + 3] * m1);
        base[hs] = pack_bf16(acc[8 * jj + 4] * m0, acc[8 * jj + 5] * m0);
        base[hs + rs] = pack_bf16(acc[8 * jj + 6] * m1, acc[8 * jj + 7] * m1);
    }
}

__global__ void __launch_bounds__(K1_THREADS, 1)
k1_ln_qkv(const __grid_constant__ CUtensorMap wmap, const __grid_constant__ CUtensorMap xmap, const __nv_bfloat16* __restrict__ w_r) {
    extern __shared__ __align__(1024) unsigned char smem[];
    const uint32_t sA = smem_u32(smem), sB = sA + 131072, sBar = sB + 6 * 16384;
    const int warp = __shfl_sync(~0u, threadIdx.x >> 5, 0), lane = threadIdx.x & 31;
    const int nt = blockIdx.x & 7, mt = blockIdx.x >> 3;
    const int wg = warp >> 2;
    CK(0);
    pdl_launch();
    uint32_t* s_wr = (uint32_t*)(smem + 131072 + 6 * 16384 + 128);
    if (warp == 8) {
        if (lane == 0) {
            for (int i = 0; i < 6; i++) { mbar_init(sBar + i * 8, 1); mbar_init(sBar + 48 + i * 8, 2); }
            mbar_init(sBar + 96, 1); mbar_init(sBar + 104, 1);
            asm volatile("fence.mbarrier_init.release.cluster;" ::: "memory");
            mbar_expect_tx(sBar + 96, 65536); mbar_expect_tx(sBar + 104, 65536);
            for (int i = 0; i < 6; i++) mbar_expect_tx(sBar + i * 8, 16384);
        }
        __syncwarp();
        if (lane < 16) tma_2d(sA + (lane & 7) * 16384 + (lane >> 3) * 8192, &xmap, (lane & 7) * 64, mt * 128 + (lane >> 3) * 64, sBar + 96 + (lane >> 3) * 8);
        else if (lane < 28) {
            const int ld = (lane - 16) >> 1, j = lane & 1;
            tma_2d(sB + ld * 16384 + j * 8192, &wmap, nt * 192 + j * 64, ld * 64, sBar + ld * 8);
        }
        named_bar(3, K1_THREADS);
        if (lane < 2) {
            for (int ld = 6; ld < 12; ld++) {
                const int sl = ld - 6;
                mbar_wait(sBar + 48 + sl * 8, 0);
                if (lane == 0) mbar_expect_tx(sBar + sl * 8, 16384);
                __syncwarp(3);
                if (ld < 8) tma_2d(sB + sl * 16384 + lane * 8192, &wmap, nt * 192 + lane * 64, ld * 64, sBar + sl * 8);
                else tma_2d(sB + sl * 16384 + lane * 8192, &wmap, nt * 192 + 128, (ld - 8) * 128 + lane * 64, sBar + sl * 8);
            }
        }
        return;
    }
    if (nt == 0) s_wr[threadIdx.x] = __ldg((const uint32_t*)w_r + threadIdx.x);
    named_bar(3, K1_THREADS);
    const int g = lane >> 2, t = lane & 3;
    const int lrow = warp * 16 + (lane & 7) + ((lane >> 3) & 1) * 8;
    const uint32_t lbase = sA + lrow * 128;
    const int lsw = lane & 7, lhi = lane >> 4;
    uint32_t laddr[4];
    #pragma unroll
    for (int k4 = 0; k4 < 4; k4++) laddr[k4] = lbase + (((k4 * 2 + lhi) ^ lsw) * 16);
    CK(1);
    mbar_wait(sBar + 96 + wg * 8, 0);
    CK(2);
    float dsum[4] = {0.f, 0.f, 0.f, 0.f}, dq0[4] = {0.f, 0.f, 0.f, 0.f}, dq1[4] = {0.f, 0.f, 0.f, 0.f};
    float esum[4] = {0.f, 0.f, 0.f, 0.f}, eq0[4] = {0.f, 0.f, 0.f, 0.f}, eq1[4] = {0.f, 0.f, 0.f, 0.f};
    #pragma unroll 2
    for (int pn = 0; pn < 8; pn++) {
        uint32_t a[4][4];
        #pragma unroll
        for (int k4 = 0; k4 < 4; k4++) ldsm4(a[k4], laddr[k4] + pn * 16384);
        #pragma unroll
        for (int k4 = 0; k4 < 4; k4 += 2) {
            mma16816(dsum, a[k4], 0x3F803F80u, 0x3F803F80u);
            mma16816(dq0, a[k4], a[k4][0], a[k4][2]);
            mma16816(dq1, a[k4], a[k4][1], a[k4][3]);
            mma16816(esum, a[k4 + 1], 0x3F803F80u, 0x3F803F80u);
            mma16816(eq0, a[k4 + 1], a[k4 + 1][0], a[k4 + 1][2]);
            mma16816(eq1, a[k4 + 1], a[k4 + 1][1], a[k4 + 1][3]);
        }
    }
    #pragma unroll
    for (int i = 0; i < 4; i++) { dsum[i] += esum[i]; dq0[i] += eq0[i]; dq1[i] += eq1[i]; }
    CK(3);
    const int dsrc = g * 4 + (g >> 1);
    const float sq0 = __shfl_sync(~0u, (g & 1) ? dq0[1] : dq0[0], dsrc), sq1 = __shfl_sync(~0u, (g & 1) ? dq1[3] : dq1[2], dsrc);
    const float mean0 = dsum[0] * (1.0f / D_), mean1 = dsum[2] * (1.0f / D_);
    const uint32_t m20 = pack_bf16(mean0, mean0), m21 = pack_bf16(mean1, mean1);
    float acc[64];
    #pragma unroll
    for (int i = 0; i < 64; i++) acc[i] = 0.f;
    float dr[4] = {0.f, 0.f, 0.f, 0.f};
    const uint64_t db0 = make_desc(sB, 8192, 1024, 1);
    #pragma unroll 1
    for (int kc = 0; kc < 8; kc += 2) {
        #pragma unroll
        for (int h2 = 0; h2 < 2; h2++) {
            const int ld = kc + h2, sl = ld < 6 ? ld : ld - 6;
            uint32_t a[4][4];
            #pragma unroll
            for (int k4 = 0; k4 < 4; k4++) ldsm4(a[k4], laddr[k4] + ld * 16384);
            #pragma unroll
            for (int k4 = 0; k4 < 4; k4++) {
                a[k4][0] = sub_bf16x2(a[k4][0], m20); a[k4][1] = sub_bf16x2(a[k4][1], m21);
                a[k4][2] = sub_bf16x2(a[k4][2], m20); a[k4][3] = sub_bf16x2(a[k4][3], m21);
            }
            if (nt == 0) {
                #pragma unroll
                for (int k4 = 0; k4 < 4; k4++) mma16816(dr, a[k4], s_wr[(ld * 4 + k4) * 8 + t], s_wr[(ld * 4 + k4) * 8 + 4 + t]);
            }
            mbar_wait(sBar + sl * 8, ld >= 6);
            WG_FENCE();
            #pragma unroll
            for (int k4 = 0; k4 < 4; k4++) wgmma_rs_n128(acc, a[k4], db0 + (uint64_t)(sl * 1024 + k4 * 128));
            WG_COMMIT();
            wg_wait<1>();
            if (ld >= 1 && ld <= 6 && (threadIdx.x & 127) == 0) mbar_arrive(sBar + 48 + (ld - 1) * 8);
        }
    }
    float var0 = fmaf(-mean0, mean0, sq0 * (1.0f / D_)), var1 = fmaf(-mean1, mean1, sq1 * (1.0f / D_));
    if (__any_sync(~0u, !(mean0 * mean0 <= 16.0f * var0) || !(mean1 * mean1 <= 16.0f * var1))) {
        float q0 = 0.f, q1 = 0.f;
        #pragma unroll 1
        for (int ks = 0; ks < 32; ks++) {
            uint32_t a[4];
            ldsm4(a, lbase + (ks >> 2) * 16384 + ((((ks & 3) * 2 + lhi) ^ lsw) * 16));
            #pragma unroll
            for (int i = 0; i < 4; i++) {
                const float m = (i & 1) ? mean1 : mean0;
                const float d0 = bf_lo(a[i]) - m, d1 = bf_hi(a[i]) - m;
                if (i & 1) q1 = fmaf(d0, d0, fmaf(d1, d1, q1)); else q0 = fmaf(d0, d0, fmaf(d1, d1, q0));
            }
        }
        q0 += __shfl_xor_sync(~0u, q0, 1); q0 += __shfl_xor_sync(~0u, q0, 2);
        q1 += __shfl_xor_sync(~0u, q1, 1); q1 += __shfl_xor_sync(~0u, q1, 2);
        var0 = q0 * (1.0f / D_); var1 = q1 * (1.0f / D_);
    }
    const float rs0 = __frcp_rn(bf16r(__fsqrt_rn(bf16r(bf16r(var0) + 1e-5f))));
    const float rs1 = __frcp_rn(bf16r(__fsqrt_rn(bf16r(bf16r(var1) + 1e-5f))));
    const int row0 = mt * 128 + warp * 16;
    if (nt == 0 && t == 0) {
        g_r[row0 + g] = bf16r(dr[0] * rs0); g_r[row0 + g + 8] = bf16r(dr[2] * rs1);
        g_stats[row0 + g] = make_float2(bf_lo(m20), rs0); g_stats[row0 + g + 8] = make_float2(bf_lo(m21), rs1);
    }
    wg_wait<0>();
    touch64(acc);
    CK(4);
    float acc2[32];
    #pragma unroll
    for (int i = 0; i < 32; i++) acc2[i] = 0.f;
    #pragma unroll 1
    for (int q = 0; q < 4; q++) {
        const int sl = q + 2;
        uint32_t a[8][4];
        #pragma unroll
        for (int k8 = 0; k8 < 8; k8++) ldsm4(a[k8], laddr[k8 & 3] + (q * 2 + (k8 >> 2)) * 16384);
        #pragma unroll
        for (int k8 = 0; k8 < 8; k8++) {
            a[k8][0] = sub_bf16x2(a[k8][0], m20); a[k8][1] = sub_bf16x2(a[k8][1], m21);
            a[k8][2] = sub_bf16x2(a[k8][2], m20); a[k8][3] = sub_bf16x2(a[k8][3], m21);
        }
        mbar_wait(sBar + sl * 8, 1);
        WG_FENCE();
        #pragma unroll
        for (int k8 = 0; k8 < 8; k8++) wgmma_rs_n64(acc2, a[k8], db0 + (uint64_t)(sl * 1024 + k8 * 128));
        WG_COMMIT();
        if (q == 0) k1_store<8>(acc, 0, rs0, rs1, nt, row0, lane);
        wg_wait<0>();
    }
    touch32(acc2);
    CK(5);
    k1_store<4>(acc2, 8, rs0, rs1, nt, row0, lane);
    CK(6);
}

constexpr int K2_THREADS = 512;
constexpr int K2_SMEM = 65536 + 98304 + 16384 + 128;

constexpr float QS = 0.25f * 1.4426950408889634f;
__device__ __forceinline__ uint32_t polyexp(float s, float cb, uint32_t c421, float c3, float one) {
    float u;
    asm("fma.rn.sat.f32 %0, %1, %2, %3;" : "=f"(u) : "f"(s), "f"(QS * (1.0f / 255.0f)), "f"(cb));
    float z = fmaf(u, 0.99609375f, one);
    uint32_t rb;
    asm("lop3.b32 %0, %1, 0xFFFF8000, %2, 0xEA;" : "=r"(rb) : "r"(__float_as_uint(z)), "r"(c421));
    float f = z - __uint_as_float(rb);
    float h = fmaf(f, c3, 58.86525f);
    h = fmaf(f, h, -0.29870507f);
    return __float_as_uint(fmaf(f, h, z));
}

struct ExpC { float nm0, nm1, cb0, cb1, c3, one; uint32_t c421; };

template <int G>
__device__ __forceinline__ void exp_block(const float* s, uint32_t* p, const ExpC& c) {
    #pragma unroll
    for (int hf = 0; hf < 2; hf++) {
        const float* x = s + hf * 4;
        if ((PMASK >> (G + hf)) & 1) {
            p[hf * 2 + 0] = __byte_perm(polyexp(x[0], c.cb0, c.c421, c.c3, c.one), polyexp(x[1], c.cb0, c.c421, c.c3, c.one), 0x6521);
            p[hf * 2 + 1] = __byte_perm(polyexp(x[2], c.cb1, c.c421, c.c3, c.one), polyexp(x[3], c.cb1, c.c421, c.c3, c.one), 0x6521);
        } else {
            p[hf * 2 + 0] = pack_bf16(ex2(fmaf(x[0], QS, c.nm0)), ex2(fmaf(x[1], QS, c.nm0)));
            p[hf * 2 + 1] = pack_bf16(ex2(fmaf(x[2], QS, c.nm1)), ex2(fmaf(x[3], QS, c.nm1)));
        }
    }
}

__device__ __forceinline__ void max16(const float* s, float& mx0, float& mx1) {
    #pragma unroll
    for (int j = 0; j < 4; j++) {
        mx0 = fmaxf(mx0, fmaxf(s[4 * j], s[4 * j + 1]));
        mx1 = fmaxf(mx1, fmaxf(s[4 * j + 2], s[4 * j + 3]));
    }
}

__device__ void moe_cta(int part, unsigned char* smem, const __nv_bfloat16* __restrict__ x, const __nv_bfloat16* __restrict__ w_gate,
                        const __nv_bfloat16* __restrict__ w_up, const __nv_bfloat16* __restrict__ w_down) {
    float* xs = (float*)smem;
    float* red = xs + 1024;
    float* hs = red + 8 * 4 * 448;
    __shared__ float s_v[32];
    __shared__ int s_i[32];
    __shared__ int s_sel[2];
    const int tid = threadIdx.x, warp = tid >> 5, lane = tid & 31;
    for (int pass = 0; pass < 2; pass++) {
        float bv = -INFINITY; int bi = 0x7fffffff;
        const int excl = pass ? s_sel[0] : -1;
        for (int i = tid; i < S_; i += K2_THREADS) {
            float v = g_r[i];
            if (i != excl && (v > bv || (v == bv && i < bi) || bi == 0x7fffffff)) { bv = v; bi = i; }
        }
        #pragma unroll
        for (int o = 16; o; o >>= 1) {
            float ov = __shfl_xor_sync(~0u, bv, o); int oi = __shfl_xor_sync(~0u, bi, o);
            if (ov > bv || (ov == bv && oi < bi)) { bv = ov; bi = oi; }
        }
        if (lane == 0) { s_v[warp] = bv; s_i[warp] = bi; }
        __syncthreads();
        if (warp == 0) {
            bv = lane < 16 ? s_v[lane] : -INFINITY; bi = lane < 16 ? s_i[lane] : 0x7fffffff;
            #pragma unroll
            for (int o = 16; o; o >>= 1) {
                float ov = __shfl_xor_sync(~0u, bv, o); int oi = __shfl_xor_sync(~0u, bi, o);
                if (ov > bv || (ov == bv && oi < bi)) { bv = ov; bi = oi; }
            }
            if (lane == 0) s_sel[pass] = (bi == 0x7fffffff) ? pass : bi;
        }
        __syncthreads();
    }
    for (int i = tid; i < 1024; i += K2_THREADS) {
        const int tok = s_sel[i >> 9];
        const float2 st = g_stats[tok];
        xs[i] = ln_elem(__bfloat162float(x[(size_t)tok * D_ + (i & 511)]), st.x, st.y);
    }
    if (part == 0 && tid < 2) g_sel[tid] = s_sel[tid];
    __syncthreads();
    const int c0 = part * 448;
    if (tid < 448) {
        const int cg = tid % 56, ks = tid / 56;
        float a[4][8];
        #pragma unroll
        for (int i = 0; i < 4; i++)
            #pragma unroll
            for (int j = 0; j < 8; j++) a[i][j] = 0.f;
        const __nv_bfloat16* pg = w_gate + (size_t)(ks * 64) * F_ + c0 + cg * 8;
        const __nv_bfloat16* pu = w_up + (size_t)(ks * 64) * F_ + c0 + cg * 8;
        #pragma unroll 8
        for (int k = 0; k < 64; k++) {
            const uint4 gv = __ldg((const uint4*)(pg + (size_t)k * F_));
            const uint4 uv = __ldg((const uint4*)(pu + (size_t)k * F_));
            const float x0 = xs[ks * 64 + k], x1 = xs[512 + ks * 64 + k];
            const uint32_t gu[4] = {gv.x, gv.y, gv.z, gv.w}, uu[4] = {uv.x, uv.y, uv.z, uv.w};
            #pragma unroll
            for (int j = 0; j < 4; j++) {
                const float g0 = bf_lo(gu[j]), g1 = bf_hi(gu[j]), u0 = bf_lo(uu[j]), u1 = bf_hi(uu[j]);
                a[0][2 * j] = fmaf(x0, g0, a[0][2 * j]); a[0][2 * j + 1] = fmaf(x0, g1, a[0][2 * j + 1]);
                a[1][2 * j] = fmaf(x1, g0, a[1][2 * j]); a[1][2 * j + 1] = fmaf(x1, g1, a[1][2 * j + 1]);
                a[2][2 * j] = fmaf(x0, u0, a[2][2 * j]); a[2][2 * j + 1] = fmaf(x0, u1, a[2][2 * j + 1]);
                a[3][2 * j] = fmaf(x1, u0, a[3][2 * j]); a[3][2 * j + 1] = fmaf(x1, u1, a[3][2 * j + 1]);
            }
        }
        #pragma unroll
        for (int i = 0; i < 4; i++)
            #pragma unroll
            for (int j = 0; j < 8; j++) red[(ks * 4 + i) * 448 + cg * 8 + j] = a[i][j];
    }
    __syncthreads();
    for (int i = tid; i < 896; i += K2_THREADS) {
        const int tok = i / 448, c = i % 448;
        float gs = 0.f, us = 0.f;
        #pragma unroll
        for (int ks = 0; ks < 8; ks++) { gs += red[(ks * 4 + tok) * 448 + c]; us += red[(ks * 4 + 2 + tok) * 448 + c]; }
        gs = bf16r(gs); us = bf16r(us);
        const float sl = bf16r(gs / (1.0f + __expf(-gs)));
        hs[i] = bf16r(sl * us);
    }
    __syncthreads();
    {
        const int cg = tid & 63, fs = tid >> 6;
        float a[2][8];
        #pragma unroll
        for (int j = 0; j < 8; j++) { a[0][j] = 0.f; a[1][j] = 0.f; }
        const __nv_bfloat16* pd = w_down + (size_t)(c0 + fs * 56) * D_ + cg * 8;
        #pragma unroll 8
        for (int f = 0; f < 56; f++) {
            const uint4 dv = __ldg((const uint4*)(pd + (size_t)f * D_));
            const float h0 = hs[fs * 56 + f], h1 = hs[448 + fs * 56 + f];
            const uint32_t du[4] = {dv.x, dv.y, dv.z, dv.w};
            #pragma unroll
            for (int j = 0; j < 4; j++) {
                const float d0 = bf_lo(du[j]), d1 = bf_hi(du[j]);
                a[0][2 * j] = fmaf(h0, d0, a[0][2 * j]); a[0][2 * j + 1] = fmaf(h0, d1, a[0][2 * j + 1]);
                a[1][2 * j] = fmaf(h1, d0, a[1][2 * j]); a[1][2 * j + 1] = fmaf(h1, d1, a[1][2 * j + 1]);
            }
        }
        #pragma unroll
        for (int j = 0; j < 8; j++) { red[(fs * 2) * 512 + cg * 8 + j] = a[0][j]; red[(fs * 2 + 1) * 512 + cg * 8 + j] = a[1][j]; }
    }
    __syncthreads();
    for (int i = tid; i < 1024; i += K2_THREADS) {
        float s = 0.f;
        #pragma unroll
        for (int fs = 0; fs < 8; fs++) s += red[(fs * 2 + (i >> 9)) * 512 + (i & 511)];
        g_ypart[part][i >> 9][i & 511] = s;
    }
}

__global__ void __launch_bounds__(K2_THREADS, 1)
k2_attn(const __nv_bfloat16* __restrict__ x, const __nv_bfloat16* __restrict__ w_gate, const __nv_bfloat16* __restrict__ w_up,
        const __nv_bfloat16* __restrict__ w_down) {
    extern __shared__ __align__(1024) unsigned char smem[];
    TL(1, 0);
    pdl_launch();
    if (blockIdx.x >= 128) {
        const int part = blockIdx.x - 128;
        {
            const int k = threadIdx.x;
            asm volatile("cp.async.bulk.prefetch.L2.global [%0], %1;" :: "l"(w_gate + (size_t)k * F_ + part * 448), "r"(896) : "memory");
            asm volatile("cp.async.bulk.prefetch.L2.global [%0], %1;" :: "l"(w_up + (size_t)k * F_ + part * 448), "r"(896) : "memory");
            if (k < 56) asm volatile("cp.async.bulk.prefetch.L2.global [%0], %1;" :: "l"(w_down + (size_t)(part * 448 + k * 8) * D_), "r"(8192) : "memory");
        }
        pdl_wait(); TL(1, 1); moe_cta(blockIdx.x - 128, smem, x, w_gate, w_up, w_down); TL(1, 2); return; }
    const uint32_t sK = smem_u32(smem), sV = sK + 65536, sQ = sV + 98304, sBar = sQ + 16384;
    const int h = blockIdx.x >> 2, qb = blockIdx.x & 3;
    const int warp = __shfl_sync(~0u, threadIdx.x >> 5, 0), lane = threadIdx.x & 31, wg = warp >> 2;
    if (threadIdx.x == 0) {
        mbar_init(sBar, 1); mbar_init(sBar + 8, 1);
        asm volatile("fence.mbarrier_init.release.cluster;" ::: "memory");
        mbar_expect_tx(sBar, 16384 + 16384 + 2 * 8192);
        mbar_expect_tx(sBar + 8, 49152 + 2 * 24576);
    }
    for (int i = threadIdx.x; i < 2048; i += K2_THREADS) {
        const uint32_t v = is_poly_group(i >> 3) ? 0xBF80BF80u : 0x3F803F80u;
        *(uint4*)(smem + 65536 + 65536 + i * 16) = make_uint4(v, v, v, v);
    }
    fence_async_smem();
    __syncthreads();
    if (warp == 0) {
        pdl_wait();
        TL(1, 1);
        const uint4* gk = g_K + (size_t)h * 4096;
        const uint4* gv = g_V + (size_t)h * 4096;
        if (lane == 0) bulk_g2s(sQ, g_Q + (size_t)h * 4096 + qb * 1024, 16384, sBar);
        if (lane == 1) bulk_g2s(sK, gk, 16384, sBar);
        if (lane == 2) bulk_g2s(sV, gv, 8192, sBar);
        if (lane == 3) bulk_g2s(sV + 32768, gv + 2048, 8192, sBar);
        if (lane == 4) bulk_g2s(sK + 16384, gk + 1024, 49152, sBar + 8);
        if (lane == 5) bulk_g2s(sV + 8192, gv + 512, 24576, sBar + 8);
        if (lane == 6) bulk_g2s(sV + 32768 + 8192, gv + 2048 + 512, 24576, sBar + 8);
        __syncwarp();
    }
    ExpC c;
    {
        const volatile uint32_t* cc = g_const;
        c.c421 = cc[0]; c.c3 = __uint_as_float(cc[1]); c.one = __uint_as_float(cc[2]);
    }
    const uint32_t kdesc0 = (uint32_t)make_desc(sK, 128, 256, 0);
    const uint32_t vdesc0 = (uint32_t)make_desc(sV, 128, 32768, 0);
    #pragma unroll 1
    for (int pass = 0; pass < 2; pass++) {
        const bool dry = false;
        if (pass == 0) { mbar_wait(sBar, 0); __syncwarp(); TL(1, 2); }
        const int unit = (pass & 1) * 4 + wg;
        const uint32_t q = (uint32_t)make_desc(sQ + unit * 2048, 128, 256, 0);
        float o[12];
        #pragma unroll 1
        for (int attempt = 0; attempt < 2; attempt++) {
            float s0[16], s1[16], s2[16];
            #pragma unroll
            for (int i = 0; i < 16; i++) { s0[i] = 0.f; s1[i] = 0.f; s2[i] = 0.f; }
            float mx0 = -INFINITY, mx1 = -INFINITY;
            if (attempt) {
                #pragma unroll 1
                for (int it = 0; it < 64; it++) {
                    WG_FENCE();
                    wgmma_qk32(s0, q, kdesc0 + it * 64);
                    WG_COMMIT();
                    wg_wait<0>();
                    touch16(s0);
                    max16(s0, mx0, mx1);
                }
            }
            #pragma unroll
            for (int i = 0; i < 12; i++) o[i] = 0.f;
            WG_FENCE();
            wgmma_qk32(s2, q, kdesc0);
            wgmma_qk32(s0, q, kdesc0 + 64);
            wgmma_qk32(s1, q, kdesc0 + 128);
            WG_COMMIT();
            wg_wait<0>();
            touch16(s0); touch16(s1); touch16(s2);
            max16(s0, mx0, mx1); max16(s1, mx0, mx1); max16(s2, mx0, mx1);
            mx0 = fmaxf(mx0, __shfl_xor_sync(~0u, mx0, 1)); mx0 = fmaxf(mx0, __shfl_xor_sync(~0u, mx0, 2));
            mx1 = fmaxf(mx1, __shfl_xor_sync(~0u, mx1, 1)); mx1 = fmaxf(mx1, __shfl_xor_sync(~0u, mx1, 2));
            const float bias = attempt ? 0.0f : 64.0f;
            c.nm0 = __shfl_sync(~0u, -fmaf(mx0, QS, bias), lane); c.nm1 = __shfl_sync(~0u, -fmaf(mx1, QS, bias), lane);
            c.cb0 = __shfl_sync(~0u, (127.0f + c.nm0) * (1.0f / 255.0f), lane);
            c.cb1 = __shfl_sync(~0u, (127.0f + c.nm1) * (1.0f / 255.0f), lane);
            uint32_t kd = kdesc0 + 192, vd = vdesc0 + 32;
            {
                uint32_t pa[4], pb[4];
                exp_block<12>(s2, pa, c);
                exp_block<14>(s2 + 8, pb, c);
                WG_FENCE();
                wgmma_pv(o, pa, vdesc0); wgmma_pv(o, pb, vdesc0 + 16);
                WG_COMMIT();
            }
            #pragma unroll 1
            for (int seg = 0; seg < (dry ? 1 : 2); seg++) {
            if (seg) { wg_wait<0>(); mbar_wait(sBar + 8, 0); __syncwarp(); }
            #pragma unroll 1
            for (int it = seg ? 3 : (dry ? 2 : 0); it < (seg ? 21 : 3); it++) {
                uint32_t p[6][4];
                WG_FENCE();
                wgmma_qk32(s2, q, kd);
                WG_COMMIT();
                exp_block<0>(s0, p[0], c);
                exp_block<2>(s0 + 8, p[1], c);
                WG_FENCE();
                wgmma_pv(o, p[0], vd); wgmma_pv(o, p[1], vd + 16);
                wgmma_qk32(s0, q, kd + 64);
                WG_COMMIT();
                wg_wait<1>();
                touch16(s2);
                exp_block<4>(s1, p[2], c);
                exp_block<6>(s1 + 8, p[3], c);
                WG_FENCE();
                wgmma_pv(o, p[2], vd + 32); wgmma_pv(o, p[3], vd + 48);
                wgmma_qk32(s1, q, kd + 128);
                WG_COMMIT();
                wg_wait<1>();
                touch16(s0);
                exp_block<8>(s2, p[4], c);
                exp_block<10>(s2 + 8, p[5], c);
                WG_FENCE();
                wgmma_pv(o, p[4], vd + 64); wgmma_pv(o, p[5], vd + 80);
                WG_COMMIT();
                vd += 96; kd += 192;
                wg_wait<1>();
                touch16(s1);
            }
            }
            wg_wait<0>();
            touch12(o);
            if (attempt) break;
            float big = 0.f;
            #pragma unroll
            for (int i = 0; i < 12; i++) big = fmaxf(big, fabsf(o[i]));
            bool bad = !(big < 1e30f);
            #pragma unroll
            for (int i = 0; i < 12; i++) bad |= (o[i] != o[i]);
            uint32_t any;
            asm volatile("{.reg .pred p, q; setp.ne.u32 p, %1, 0; barrier.cta.red.or.pred.aligned q, %2, 128, p; selp.u32 %0, 1, 0, q;}"
                         : "=r"(any) : "r"((uint32_t)bad), "r"(1 + wg) : "memory");
            if (dry || !__any_sync(~0u, any)) break;
        }
        const int g = lane >> 2, t = lane & 3;
        const int r = (warp & 3) * 16 + g;
        const float i0 = __fdiv_rn(1.0f, o[8]), i1 = __fdiv_rn(1.0f, o[10]);
        uint32_t* ob = (uint32_t*)(g_O + (size_t)(qb * 8 + unit) * 4096 + (h >> 2) * 512 + r * 8) + t;
        const int c0 = ((h & 3) * 2) ^ (r & 7), c1 = ((h & 3) * 2 + 1) ^ (r & 7);
        if (!dry) {
            ob[c0 * 4] = pack_bf16(o[0] * i0, o[1] * i0);
            ob[c1 * 4] = pack_bf16(o[4] * i0, o[5] * i0);
            ob[256 + c0 * 4] = pack_bf16(o[2] * i1, o[3] * i1);
            ob[256 + c1 * 4] = pack_bf16(o[6] * i1, o[7] * i1);
            TL(1, 3 + pass);
        }
    }
}

constexpr int K3_THREADS = 256;
constexpr int K3_SMEM = 65536 + 131072 + 128;

__global__ void __launch_bounds__(K3_THREADS, 1)
k3_out(const __grid_constant__ CUtensorMap wmap, const __nv_bfloat16* __restrict__ x, __nv_bfloat16* __restrict__ out) {
    extern __shared__ __align__(1024) unsigned char smem[];
    const uint32_t sA = smem_u32(smem), sB = sA + 65536, sBar = sB + 131072;
    const int warp = __shfl_sync(~0u, threadIdx.x >> 5, 0), lane = threadIdx.x & 31, wg = warp >> 2;
    const int nt = blockIdx.x & 3, mt = blockIdx.x >> 2;
    TL(2, 0);
    if (threadIdx.x == 0) {
        for (int i = 0; i < 6; i++) mbar_init(sBar + i * 8, 1);
        asm volatile("fence.mbarrier_init.release.cluster;" ::: "memory");
        for (int kh = 0; kh < 2; kh++) {
            mbar_expect_tx(sBar + kh * 8, 65536);
            tma_2d(sB + kh * 32768, &wmap, nt * 128, kh * 256, sBar + kh * 8);
            tma_2d(sB + 65536 + kh * 32768, &wmap, nt * 128 + 64, kh * 256, sBar + kh * 8);
        }
    }
    const int er = threadIdx.x >> 2, ec = (threadIdx.x & 3) * 32;
    const int row = mt * 64 + er;
    uint4 xv[4];
    #pragma unroll
    for (int j = 0; j < 4; j++) xv[j] = __ldg((const uint4*)(x + (size_t)row * D_ + nt * 128 + ec) + j);
    pdl_wait();
    TL(2, 1);
    if (threadIdx.x == 0) {
        for (int q = 0; q < 4; q++) {
            mbar_expect_tx(sBar + 16 + q * 8, 16384);
            bulk_g2s(sA + q * 16384, g_O + (size_t)mt * 4096 + q * 1024, 16384, sBar + 16 + q * 8);
        }
    }
    const int sel0 = g_sel[0], sel1 = g_sel[1];
    const float2 st = g_stats[row];
    uint32_t bb[16];
    {
        const uint32_t xu[16] = {xv[0].x, xv[0].y, xv[0].z, xv[0].w, xv[1].x, xv[1].y, xv[1].z, xv[1].w,
                                 xv[2].x, xv[2].y, xv[2].z, xv[2].w, xv[3].x, xv[3].y, xv[3].z, xv[3].w};
        #pragma unroll
        for (int j = 0; j < 16; j++) bb[j] = pack_bf16(bf16r(bf_lo(xu[j]) - st.x) * st.y, bf16r(bf_hi(xu[j]) - st.x) * st.y);
        const int slot = row == sel0 ? 0 : (row == sel1 ? 1 : -1);
        if (slot >= 0) {
            const float gate = bf16r(1.0f / (1.0f + __expf(-g_r[row])));
            const int c0 = nt * 128 + ec;
            #pragma unroll
            for (int j = 0; j < 16; j++) {
                const float2 a = *(const float2*)&g_ypart[0][slot][c0 + 2 * j], b = *(const float2*)&g_ypart[1][slot][c0 + 2 * j];
                const float2 c = *(const float2*)&g_ypart[2][slot][c0 + 2 * j], d = *(const float2*)&g_ypart[3][slot][c0 + 2 * j];
                bb[j] = pack_bf16(bf_lo(bb[j]) + bf16r(bf16r(a.x + b.x + c.x + d.x) * gate), bf_hi(bb[j]) + bf16r(bf16r(a.y + b.y + c.y + d.y) * gate));
            }
        }
    }
    __syncthreads();
    float acc[32];
    #pragma unroll
    for (int i = 0; i < 32; i++) acc[i] = 0.f;
    const uint64_t da0 = make_desc(sA, 16, 1024, 1);
    const uint64_t db0 = make_desc(sB + wg * 65536, 8192, 1024, 1);
    #pragma unroll 1
    for (int q = 0; q < 4; q++) {
        if ((q & 1) == 0) mbar_wait(sBar + (q >> 1) * 8, 0);
        mbar_wait(sBar + 16 + q * 8, 0);
        WG_FENCE();
        #pragma unroll
        for (int kk = 0; kk < 8; kk++)
            wgmma_n64(acc, da0 + (uint64_t)(q * 1024 + (kk >> 2) * 512 + (kk & 3) * 2), db0 + (uint64_t)(q * 1024 + kk * 128));
        WG_COMMIT();
    }
    wg_wait<0>();
    touch32(acc);
    TL(2, 2);
    __syncthreads();
    {
        const int g = lane >> 2, t = lane & 3;
        unsigned char* sp = smem + ((warp & 3) * 16 + g) * 272 + wg * 128 + t * 4;
        #pragma unroll
        for (int j = 0; j < 8; j++) {
            *(uint32_t*)(sp + j * 16) = pack_bf16(acc[4 * j], acc[4 * j + 1]);
            *(uint32_t*)(sp + 8 * 272 + j * 16) = pack_bf16(acc[4 * j + 2], acc[4 * j + 3]);
        }
    }
    __syncthreads();
    #pragma unroll
    for (int j = 0; j < 4; j++) {
        const uint4 av = *(const uint4*)(smem + er * 272 + ec * 2 + j * 16);
        const uint32_t au[4] = {av.x, av.y, av.z, av.w}, xu[4] = {xv[j].x, xv[j].y, xv[j].z, xv[j].w};
        uint32_t o[4];
        #pragma unroll
        for (int i = 0; i < 4; i++) {
            uint32_t t2;
            asm("add.rn.bf16x2 %0, %1, %2;" : "=r"(t2) : "r"(xu[i]), "r"(au[i]));
            asm("add.rn.bf16x2 %0, %1, %2;" : "=r"(o[i]) : "r"(t2), "r"(bb[j * 4 + i]));
        }
        *((uint4*)(out + (size_t)row * D_ + nt * 128 + ec) + j) = make_uint4(o[0], o[1], o[2], o[3]);
    }
    TL(2, 3);
}

typedef CUresult (*EncodeFn)(CUtensorMap*, CUtensorMapDataType, cuuint32_t, void*, const cuuint64_t*, const cuuint64_t*,
                             const cuuint32_t*, const cuuint32_t*, CUtensorMapInterleave, CUtensorMapSwizzle,
                             CUtensorMapL2promotion, CUtensorMapFloatOOBfill);

void make_wmap(EncodeFn fn, CUtensorMap* map, const void* ptr, int rows, int cols, int box_rows) {
    cuuint64_t dims[2] = {(cuuint64_t)cols, (cuuint64_t)rows};
    cuuint64_t strides[1] = {(cuuint64_t)cols * 2};
    cuuint32_t box[2] = {64, (cuuint32_t)box_rows};
    cuuint32_t es[2] = {1, 1};
    fn(map, CU_TENSOR_MAP_DATA_TYPE_BFLOAT16, 2, (void*)ptr, dims, strides, box, es, CU_TENSOR_MAP_INTERLEAVE_NONE,
       CU_TENSOR_MAP_SWIZZLE_128B, CU_TENSOR_MAP_L2_PROMOTION_L2_256B, CU_TENSOR_MAP_FLOAT_OOB_FILL_NONE);
}

}

extern "C" void kernel_launch(void* const* d_in, const int* in_sizes, int n_in, void* d_out, int out_size) {
    const __nv_bfloat16* x = (const __nv_bfloat16*)d_in[0];
    const __nv_bfloat16* wqkv = (const __nv_bfloat16*)d_in[1];
    const __nv_bfloat16* wo = (const __nv_bfloat16*)d_in[2];
    const __nv_bfloat16* w_r = (const __nv_bfloat16*)d_in[4];
    const __nv_bfloat16* w_gate = (const __nv_bfloat16*)d_in[5];
    const __nv_bfloat16* w_up = (const __nv_bfloat16*)d_in[6];
    const __nv_bfloat16* w_down = (const __nv_bfloat16*)d_in[7];
    __nv_bfloat16* out = (__nv_bfloat16*)d_out;

    static EncodeFn encode = nullptr;
    if (!encode) {
        void* fn = nullptr;
        cudaDriverEntryPointQueryResult qres;
        cudaGetDriverEntryPoint("cuTensorMapEncodeTiled", &fn, cudaEnableDefault, &qres);
        encode = (EncodeFn)fn;
        cudaFuncSetAttribute(k1_ln_qkv, cudaFuncAttributeMaxDynamicSharedMemorySize, K1_SMEM);
        cudaFuncSetAttribute(k2_attn, cudaFuncAttributeMaxDynamicSharedMemorySize, K2_SMEM);
        cudaFuncSetAttribute(k3_out, cudaFuncAttributeMaxDynamicSharedMemorySize, K3_SMEM);
    }
    CUtensorMap map_qkv, map_wo, map_x;
    make_wmap(encode, &map_x, x, S_, D_, 64);
    make_wmap(encode, &map_qkv, wqkv, D_, 3 * D_, 64);
    make_wmap(encode, &map_wo, wo, D_, D_, 256);

    k1_ln_qkv<<<128, K1_THREADS, K1_SMEM, cudaStreamPerThread>>>(map_qkv, map_x, w_r);
    cudaLaunchAttribute at[1];
    at[0].id = cudaLaunchAttributeProgrammaticStreamSerialization;
    at[0].val.programmaticStreamSerializationAllowed = 1;
    cudaLaunchConfig_t cfg = {};
    cfg.stream = cudaStreamPerThread;
    cfg.attrs = at; cfg.numAttrs = 1;
    cfg.gridDim = dim3(132); cfg.blockDim = dim3(K2_THREADS); cfg.dynamicSmemBytes = K2_SMEM;
    cudaLaunchKernelEx(&cfg, k2_attn, x, w_gate, w_up, w_down);
    cfg.gridDim = dim3(128); cfg.blockDim = dim3(K3_THREADS); cfg.dynamicSmemBytes = K3_SMEM;
    cudaLaunchKernelEx(&cfg, k3_out, map_wo, x, out);
}
```

```cpp
#include <cuda_runtime.h>
#include <cuda_bf16.h>
#include <cuda.h>
#include <stdint.h>

namespace {

constexpr int S_ = 2048, D_ = 512, H_ = 32, F_ = 1792;

constexpr uint32_t PMASK = 0xA52;
__host__ __device__ constexpr bool is_poly_group(int g8) { return g8 >= 4 && ((PMASK >> ((g8 - 4) % 12)) & 1); }

__device__ __align__(1024) uint4 g_QKV[3 * H_ * S_ * 2];
#define g_Q (g_QKV)
#define g_K (g_QKV + H_ * S_ * 2)
#define g_V (g_QKV + 2 * H_ * S_ * 2)
__device__ __align__(1024) uint4 g_O[S_ * D_ / 8];
__device__ float2 g_stats[S_];
__device__ uint32_t g_const[4] = {421u, 0x459EB285u  , 0x3F800000u  , 0u};
__device__ float g_r[S_];
__device__ __align__(16) float g_ypart[4][2][D_];
__device__ int g_sel[2];

#define TL(k, p)
#define CK(i)
__device__ __forceinline__ uint32_t smem_u32(const void* p) { return (uint32_t)__cvta_generic_to_shared(p); }
__device__ __forceinline__ float bf16r(float x) { return __bfloat162float(__float2bfloat16_rn(x)); }
__device__ __forceinline__ uint32_t pack_bf16(float lo, float hi) {
    uint32_t r; asm("cvt.rn.bf16x2.f32 %0, %1, %2;" : "=r"(r) : "f"(hi), "f"(lo)); return r;
}
__device__ __forceinline__ float bf_lo(uint32_t u) { return __uint_as_float(u << 16); }
__device__ __forceinline__ float bf_hi(uint32_t u) { return __uint_as_float(u & 0xFFFF0000u); }
__device__ __forceinline__ float ex2(float x) { float y; asm("ex2.approx.ftz.f32 %0, %1;" : "=f"(y) : "f"(x)); return y; }

__device__ __forceinline__ void mbar_init(uint32_t bar, uint32_t count) {
    asm volatile("mbarrier.init.shared::cta.b64 [%0], %1;" :: "r"(bar), "r"(count) : "memory");
}
__device__ __forceinline__ void mbar_expect_tx(uint32_t bar, uint32_t bytes) {
    asm volatile("mbarrier.arrive.expect_tx.shared::cta.b64 _, [%0], %1;" :: "r"(bar), "r"(bytes) : "memory");
}
__device__ __forceinline__ void mbar_arrive(uint32_t bar) {
    asm volatile("mbarrier.arrive.shared::cta.b64 _, [%0];" :: "r"(bar) : "memory");
}
__device__ __forceinline__ void mbar_wait(uint32_t bar, uint32_t parity) {
    uint32_t done;
    #pragma unroll 1
    for (int it = 0; it < (1 << 26); it++) {
        asm volatile("{.reg .pred p; mbarrier.try_wait.parity.shared::cta.b64 p, [%1], %2; selp.u32 %0, 1, 0, p;}"
                     : "=r"(done) : "r"(bar), "r"(parity) : "memory");
        if (done) return;
    }
    __trap();
}
__device__ __forceinline__ void bulk_g2s(uint32_t dst, const void* src, uint32_t bytes, uint32_t bar) {
    asm volatile("cp.async.bulk.shared::cluster.global.mbarrier::complete_tx::bytes [%0], [%1], %2, [%3];"
                 :: "r"(dst), "l"(src), "r"(bytes), "r"(bar) : "memory");
}
__device__ __forceinline__ void tma_2d(uint32_t dst, const CUtensorMap* map, int c0, int c1, uint32_t bar) {
    asm volatile("cp.async.bulk.tensor.2d.shared::cluster.global.mbarrier::complete_tx::bytes [%0], [%1, {%3, %4}], [%2];"
                 :: "r"(dst), "l"(map), "r"(bar), "r"(c0), "r"(c1) : "memory");
}
__device__ __forceinline__ void fence_async_smem() { asm volatile("fence.proxy.async.shared::cta;" ::: "memory"); }
__device__ __forceinline__ void named_bar(int id, int n) { asm volatile("bar.sync %0, %1;" :: "r"(id), "r"(n) : "memory"); }

__device__ __forceinline__ uint64_t make_desc(uint32_t saddr, uint32_t lbo, uint32_t sbo, uint32_t swz) {
    return (uint64_t)((saddr & 0x3FFFF) >> 4) | ((uint64_t)(lbo >> 4) << 16) | ((uint64_t)(sbo >> 4) << 32) | ((uint64_t)swz << 62);
}
#define WG_FENCE() asm volatile("wgmma.fence.sync.aligned;" ::: "memory")
#define WG_COMMIT() asm volatile("wgmma.commit_group.sync.aligned;" ::: "memory")
template <int N> __device__ __forceinline__ void wg_wait() { asm volatile("wgmma.wait_group.sync.aligned %0;" :: "n"(N) : "memory"); }

#define F4(d, o) "+f"(d[o]), "+f"(d[o + 1]), "+f"(d[o + 2]), "+f"(d[o + 3])
#define F16(d, o) F4(d, o), F4(d, o + 4), F4(d, o + 8), F4(d, o + 12)
#define F32(d, o) F16(d, o), F16(d, o + 16)

__device__ __forceinline__ void wgmma_rs_n128(float* d, const uint32_t* a, uint64_t db) {
    asm volatile("wgmma.mma_async.sync.aligned.m64n128k16.f32.bf16.bf16 "
        "{%0,%1,%2,%3,%4,%5,%6,%7,%8,%9,%10,%11,%12,%13,%14,%15,%16,%17,%18,%19,%20,%21,%22,%23,%24,%25,%26,%27,%28,%29,%30,%31,"
        "%32,%33,%34,%35,%36,%37,%38,%39,%40,%41,%42,%43,%44,%45,%46,%47,%48,%49,%50,%51,%52,%53,%54,%55,%56,%57,%58,%59,%60,%61,%62,%63}, "
        "{%64,%65,%66,%67}, %68, 1, 1, 1, 1;\n"
        : F32(d, 0), F32(d, 32) : "r"(a[0]), "r"(a[1]), "r"(a[2]), "r"(a[3]), "l"(db));
}
__device__ __forceinline__ void wgmma_rs_n64(float* d, const uint32_t* a, uint64_t db) {
    asm volatile("wgmma.mma_async.sync.aligned.m64n64k16.f32.bf16.bf16 "
        "{%0,%1,%2,%3,%4,%5,%6,%7,%8,%9,%10,%11,%12,%13,%14,%15,%16,%17,%18,%19,%20,%21,%22,%23,%24,%25,%26,%27,%28,%29,%30,%31}, "
        "{%32,%33,%34,%35}, %36, 1, 1, 1, 1;\n"
        : F32(d, 0) : "r"(a[0]), "r"(a[1]), "r"(a[2]), "r"(a[3]), "l"(db));
}
__device__ __forceinline__ void wgmma_n64(float* d, uint64_t da, uint64_t db) {
    asm volatile("wgmma.mma_async.sync.aligned.m64n64k16.f32.bf16.bf16 "
        "{%0,%1,%2,%3,%4,%5,%6,%7,%8,%9,%10,%11,%12,%13,%14,%15,%16,%17,%18,%19,%20,%21,%22,%23,%24,%25,%26,%27,%28,%29,%30,%31}, "
        "%32, %33, 1, 1, 1, 0, 1;\n"
        : F32(d, 0) : "l"(da), "l"(db));
}
__device__ __forceinline__ void wgmma_qk32(float* d, uint32_t qd, uint32_t kd) {
    asm volatile("{.reg .b64 a, b; mov.b64 a, {%16, 16}; mov.b64 b, {%17, 16};\n"
        "wgmma.mma_async.sync.aligned.m64n32k16.f32.bf16.bf16 {%0,%1,%2,%3,%4,%5,%6,%7,%8,%9,%10,%11,%12,%13,%14,%15}, a, b, 0, 1, 1, 0, 0;}\n"
        : F16(d, 0) : "r"(qd), "r"(kd));
}
__device__ __forceinline__ void wgmma_pv(float* d, const uint32_t* a, uint32_t vd) {
    asm volatile("{.reg .b64 b; mov.b64 b, {%16, 2048};\n"
        "wgmma.mma_async.sync.aligned.m64n24k16.f32.bf16.bf16 {%0,%1,%2,%3,%4,%5,%6,%7,%8,%9,%10,%11}, {%12,%13,%14,%15}, b, 1, 1, 1, 1;}\n"
        : F4(d, 0), F4(d, 4), F4(d, 8) : "r"(a[0]), "r"(a[1]), "r"(a[2]), "r"(a[3]), "r"(vd));
}
__device__ __forceinline__ void touch16(float* d) { asm volatile("" : F16(d, 0) :: "memory"); }
__device__ __forceinline__ void touch12(float* d) { asm volatile("" : F4(d, 0), F4(d, 4), F4(d, 8) :: "memory"); }
__device__ __forceinline__ void touch32(float* d) { asm volatile("" : F32(d, 0) :: "memory"); }
__device__ __forceinline__ void touch64(float* d) { asm volatile("" : F32(d, 0), F32(d, 32) :: "memory"); }

__device__ __forceinline__ float ln_elem(float x, float mean_b, float rden) {
    return bf16r(bf16r(x - mean_b) * rden);
}
__device__ __forceinline__ void pdl_wait() { asm volatile("griddepcontrol.wait;" ::: "memory"); }
__device__ __forceinline__ void pdl_launch() { asm volatile("griddepcontrol.launch_dependents;" ::: "memory"); }
__device__ __forceinline__ void cluster_arrive() { asm volatile("barrier.cluster.arrive.release.aligned;" ::: "memory"); }
__device__ __forceinline__ void cluster_wait() { asm volatile("barrier.cluster.wait.acquire.aligned;" ::: "memory"); }

constexpr int K1_THREADS = 288;
constexpr int K1_SMEM = 131072 + 6 * 16384 + 128 + 1024;

__device__ __forceinline__ void ldsm4(uint32_t* r, uint32_t addr) {
    asm volatile("ldmatrix.sync.aligned.m8n8.x4.shared.b16 {%0, %1, %2, %3}, [%4];" : "=r"(r[0]), "=r"(r[1]), "=r"(r[2]), "=r"(r[3]) : "r"(addr) : "memory");
}
__device__ __forceinline__ void stsm4(uint32_t addr, uint32_t r0, uint32_t r1, uint32_t r2, uint32_t r3) {
    asm volatile("stmatrix.sync.aligned.m8n8.x4.shared.b16 [%0], {%1, %2, %3, %4};" :: "r"(addr), "r"(r0), "r"(r1), "r"(r2), "r"(r3) : "memory");
}
__device__ __forceinline__ void mma16816(float* d, const uint32_t* a, uint32_t b0, uint32_t b1) {
    asm("mma.sync.aligned.m16n8k16.row.col.f32.bf16.bf16.f32 {%0,%1,%2,%3}, {%4,%5,%6,%7}, {%8,%9}, {%0,%1,%2,%3};"
        : "+f"(d[0]), "+f"(d[1]), "+f"(d[2]), "+f"(d[3]) : "r"(a[0]), "r"(a[1]), "r"(a[2]), "r"(a[3]), "r"(b0), "r"(b1));
}
__device__ __forceinline__ uint32_t sub_bf16x2(uint32_t a, uint32_t b) {
    uint32_t d; asm("sub.rn.bf16x2 %0, %1, %2;" : "=r"(d) : "r"(a), "r"(b)); return d;
}
__device__ __forceinline__ uint32_t ln_pair(uint32_t x2, uint32_t mean2, float rden) {
    const uint32_t d = sub_bf16x2(x2, mean2);
    return pack_bf16(bf_lo(d) * rden, bf_hi(d) * rden);
}
__device__ __forceinline__ void ln_frag(uint32_t* a, uint32_t m20, uint32_t m21, float rs0, float rs1) {
    a[0] = ln_pair(a[0], m20, rs0); a[1] = ln_pair(a[1], m21, rs1); a[2] = ln_pair(a[2], m20, rs0); a[3] = ln_pair(a[3], m21, rs1);
}

template <int NJ>
__device__ __forceinline__ void k1_store(const float* acc, int jj0, int nt, int row0, int lane) {
    const int g = lane >> 2, t = lane & 3, g8a = row0 >> 3;
    const uint32_t sx0 = is_poly_group(g8a) ? 0x80008000u : 0u, sx1 = is_poly_group(g8a + 1) ? 0x80008000u : 0u;
    const int off_qk = g8a * 64 + g * 4 + t, off_v = (row0 + g) * 4 + t;
    #pragma unroll
    for (int jj = 0; jj < NJ; jj++) {
        const int hg = nt * 12 + jj0 + jj;
        const bool isv = hg >= 64;
        const uint32_t x0 = isv ? sx0 : 0u, x1 = isv ? sx1 : 0u;
        uint32_t* base = (uint32_t*)g_QKV + (size_t)hg * 16384 + (isv ? off_v : off_qk);
        const int hs = isv ? 8192 : 32, rs = isv ? 32 : 64;
        base[0] = pack_bf16(acc[8 * jj], acc[8 * jj + 1]) ^ x0;
        base[rs] = pack_bf16(acc[8 * jj + 2], acc[8 * jj + 3]) ^ x1;
        base[hs] = pack_bf16(acc[8 * jj + 4], acc[8 * jj + 5]) ^ x0;
        base[hs + rs] = pack_bf16(acc[8 * jj + 6], acc[8 * jj + 7]) ^ x1;
    }
}

__global__ void __launch_bounds__(K1_THREADS, 1)
k1_ln_qkv(const __grid_constant__ CUtensorMap wmap, const __grid_constant__ CUtensorMap xmap, const __nv_bfloat16* __restrict__ w_r) {
    extern __shared__ __align__(1024) unsigned char smem[];
    const uint32_t sA = smem_u32(smem), sB = sA + 131072, sBar = sB + 6 * 16384;
    const int warp = __shfl_sync(~0u, threadIdx.x >> 5, 0), lane = threadIdx.x & 31;
    const int nt = blockIdx.x & 7, mt = blockIdx.x >> 3;
    const int wg = warp >> 2;
    CK(0);
    pdl_launch();
    uint32_t* s_wr = (uint32_t*)(smem + 131072 + 6 * 16384 + 128);
    if (warp == 8) {
        if (lane == 0) {
            for (int i = 0; i < 6; i++) { mbar_init(sBar + i * 8, 1); mbar_init(sBar + 48 + i * 8, 2); }
            mbar_init(sBar + 96, 1); mbar_init(sBar + 104, 1);
            asm volatile("fence.mbarrier_init.release.cluster;" ::: "memory");
            mbar_expect_tx(sBar + 96, 65536); mbar_expect_tx(sBar + 104, 65536);
            for (int i = 0; i < 6; i++) mbar_expect_tx(sBar + i * 8, 16384);
        }
        __syncwarp();
        if (lane < 16) tma_2d(sA + (lane & 7) * 16384 + (lane >> 3) * 8192, &xmap, (lane & 7) * 64, mt * 128 + (lane >> 3) * 64, sBar + 96 + (lane >> 3) * 8);
        named_bar(3, K1_THREADS);
        mbar_wait(sBar + 96, 0);
        if (lane < 12) {
            const int ld = lane >> 1, j = lane & 1;
            tma_2d(sB + ld * 16384 + j * 8192, &wmap, nt * 192 + j * 64, ld * 64, sBar + ld * 8);
        }
        __syncwarp();
        if (lane < 2) {
            for (int ld = 6; ld < 12; ld++) {
                const int sl = ld - 6;
                mbar_wait(sBar + 48 + sl * 8, 0);
                if (lane == 0) mbar_expect_tx(sBar + sl * 8, 16384);
                __syncwarp(3);
                if (ld < 8) tma_2d(sB + sl * 16384 + lane * 8192, &wmap, nt * 192 + lane * 64, ld * 64, sBar + sl * 8);
                else tma_2d(sB + sl * 16384 + lane * 8192, &wmap, nt * 192 + 128, (ld - 8) * 128 + lane * 64, sBar + sl * 8);
            }
        }
        return;
    }
    if (nt == 0) s_wr[threadIdx.x] = __ldg((const uint32_t*)w_r + threadIdx.x);
    named_bar(3, K1_THREADS);
    const int g = lane >> 2, t = lane & 3;
    const int lrow = warp * 16 + (lane & 7) + ((lane >> 3) & 1) * 8;
    const uint32_t lbase = sA + lrow * 128;
    const int lsw = lane & 7, lhi = lane >> 4;
    uint32_t laddr[4];
    #pragma unroll
    for (int k4 = 0; k4 < 4; k4++) laddr[k4] = lbase + (((k4 * 2 + lhi) ^ lsw) * 16);
    CK(1);
    mbar_wait(sBar + 96 + wg * 8, 0);
    CK(2);
    float dsum[4] = {0.f, 0.f, 0.f, 0.f}, dq0[4] = {0.f, 0.f, 0.f, 0.f}, dq1[4] = {0.f, 0.f, 0.f, 0.f};
    float esum[4] = {0.f, 0.f, 0.f, 0.f}, eq0[4] = {0.f, 0.f, 0.f, 0.f}, eq1[4] = {0.f, 0.f, 0.f, 0.f};
    #pragma unroll 2
    for (int pn = 0; pn < 8; pn++) {
        uint32_t a[4][4];
        #pragma unroll
        for (int k4 = 0; k4 < 4; k4++) ldsm4(a[k4], laddr[k4] + pn * 16384);
        #pragma unroll
        for (int k4 = 0; k4 < 4; k4 += 2) {
            mma16816(dsum, a[k4], 0x3F803F80u, 0x3F803F80u);
            mma16816(dq0, a[k4], a[k4][0], a[k4][2]);
            mma16816(dq1, a[k4], a[k4][1], a[k4][3]);
            mma16816(esum, a[k4 + 1], 0x3F803F80u, 0x3F803F80u);
            mma16816(eq0, a[k4 + 1], a[k4 + 1][0], a[k4 + 1][2]);
            mma16816(eq1, a[k4 + 1], a[k4 + 1][1], a[k4 + 1][3]);
        }
    }
    #pragma unroll
    for (int i = 0; i < 4; i++) { dsum[i] += esum[i]; dq0[i] += eq0[i]; dq1[i] += eq1[i]; }
    CK(3);
    const int dsrc = g * 4 + (g >> 1);
    const float sq0 = __shfl_sync(~0u, (g & 1) ? dq0[1] : dq0[0], dsrc), sq1 = __shfl_sync(~0u, (g & 1) ? dq1[3] : dq1[2], dsrc);
    const float mean0 = dsum[0] * (1.0f / D_), mean1 = dsum[2] * (1.0f / D_);
    const uint32_t m20 = pack_bf16(mean0, mean0), m21 = pack_bf16(mean1, mean1);
    float var0 = fmaf(-mean0, mean0, sq0 * (1.0f / D_)), var1 = fmaf(-mean1, mean1, sq1 * (1.0f / D_));
    if (__any_sync(~0u, !(mean0 * mean0 <= 16.0f * var0) || !(mean1 * mean1 <= 16.0f * var1))) {
        float q0 = 0.f, q1 = 0.f;
        #pragma unroll 1
        for (int ks = 0; ks < 32; ks++) {
            uint32_t a[4];
            ldsm4(a, lbase + (ks >> 2) * 16384 + ((((ks & 3) * 2 + lhi) ^ lsw) * 16));
            #pragma unroll
            for (int i = 0; i < 4; i++) {
                const float m = (i & 1) ? mean1 : mean0;
                const float d0 = bf_lo(a[i]) - m, d1 = bf_hi(a[i]) - m;
                if (i & 1) q1 = fmaf(d0, d0, fmaf(d1, d1, q1)); else q0 = fmaf(d0, d0, fmaf(d1, d1, q0));
            }
        }
        q0 += __shfl_xor_sync(~0u, q0, 1); q0 += __shfl_xor_sync(~0u, q0, 2);
        q1 += __shfl_xor_sync(~0u, q1, 1); q1 += __shfl_xor_sync(~0u, q1, 2);
        var0 = q0 * (1.0f / D_); var1 = q1 * (1.0f / D_);
    }
    const float rs0 = __frcp_rn(bf16r(__fsqrt_rn(bf16r(bf16r(var0) + 1e-5f))));
    const float rs1 = __frcp_rn(bf16r(__fsqrt_rn(bf16r(bf16r(var1) + 1e-5f))));
    float acc[64];
    #pragma unroll
    for (int i = 0; i < 64; i++) acc[i] = 0.f;
    float dr[4] = {0.f, 0.f, 0.f, 0.f};
    const uint64_t db0 = make_desc(sB, 8192, 1024, 1);
    #pragma unroll 1
    for (int kc = 0; kc < 8; kc += 2) {
        #pragma unroll
        for (int h2 = 0; h2 < 2; h2++) {
            const int ld = kc + h2, sl = ld < 6 ? ld : ld - 6;
            uint32_t a[4][4];
            #pragma unroll
            for (int k4 = 0; k4 < 4; k4++) ldsm4(a[k4], laddr[k4] + ld * 16384);
            #pragma unroll
            for (int k4 = 0; k4 < 4; k4++) ln_frag(a[k4], m20, m21, rs0, rs1);
            if (nt == 0) {
                #pragma unroll
                for (int k4 = 0; k4 < 4; k4++) mma16816(dr, a[k4], s_wr[(ld * 4 + k4) * 8 + t], s_wr[(ld * 4 + k4) * 8 + 4 + t]);
            }
            mbar_wait(sBar + sl * 8, ld >= 6);
            WG_FENCE();
            #pragma unroll
            for (int k4 = 0; k4 < 4; k4++) wgmma_rs_n128(acc, a[k4], db0 + (uint64_t)(sl * 1024 + k4 * 128));
            WG_COMMIT();
            wg_wait<1>();
            if (ld >= 1 && ld <= 6 && (threadIdx.x & 127) == 0) mbar_arrive(sBar + 48 + (ld - 1) * 8);
        }
    }
    const int row0 = mt * 128 + warp * 16;
    if (nt == 0 && t == 0) {
        g_r[row0 + g] = bf16r(dr[0]); g_r[row0 + g + 8] = bf16r(dr[2]);
        g_stats[row0 + g] = make_float2(bf_lo(m20), rs0); g_stats[row0 + g + 8] = make_float2(bf_lo(m21), rs1);
    }
    wg_wait<0>();
    touch64(acc);
    CK(4);
    float acc2[32];
    #pragma unroll
    for (int i = 0; i < 32; i++) acc2[i] = 0.f;
    #pragma unroll 1
    for (int q = 0; q < 4; q++) {
        const int sl = q + 2;
        #pragma unroll
        for (int h2 = 0; h2 < 2; h2++) {
            uint32_t a[4][4];
            #pragma unroll
            for (int k4 = 0; k4 < 4; k4++) ldsm4(a[k4], laddr[k4] + (q * 2 + h2) * 16384);
            #pragma unroll
            for (int k4 = 0; k4 < 4; k4++) ln_frag(a[k4], m20, m21, rs0, rs1);
            if (h2 == 0) mbar_wait(sBar + sl * 8, 1);
            WG_FENCE();
            #pragma unroll
            for (int k4 = 0; k4 < 4; k4++) wgmma_rs_n64(acc2, a[k4], db0 + (uint64_t)(sl * 1024 + (h2 * 4 + k4) * 128));
            WG_COMMIT();
            wg_wait<1>();
        }
        if (q == 0) k1_store<4>(acc, 0, nt, row0, lane);
        if (q == 1) k1_store<4>(acc + 32, 4, nt, row0, lane);
    }
    wg_wait<0>();
    touch32(acc2);
    CK(5);
    k1_store<4>(acc2, 8, nt, row0, lane);
    CK(6);
}

constexpr int K2_THREADS = 512;
constexpr int K2_SMEM = 65536 + 98304 + 16384 + 128;

constexpr float QS = 0.25f * 1.4426950408889634f;
__device__ __forceinline__ uint32_t polyexp(float s, float cb, uint32_t c421, float c3, float one) {
    float u;
    asm("fma.rn.sat.f32 %0, %1, %2, %3;" : "=f"(u) : "f"(s), "f"(QS * (1.0f / 255.0f)), "f"(cb));
    float z = fmaf(u, 0.99609375f, one);
    uint32_t rb;
    asm("lop3.b32 %0, %1, 0xFFFF8000, %2, 0xEA;" : "=r"(rb) : "r"(__float_as_uint(z)), "r"(c421));
    float f = z - __uint_as_float(rb);
    float h = fmaf(f, c3, 58.86525f);
    h = fmaf(f, h, -0.29870507f);
    return __float_as_uint(fmaf(f, h, z));
}

struct ExpC { float nm0, nm1, cb0, cb1, c3, one; uint32_t c421; };

template <int G>
__device__ __forceinline__ void exp_block(const float* s, uint32_t* p, const ExpC& c) {
    #pragma unroll
    for (int hf = 0; hf < 2; hf++) {
        const float* x = s + hf * 4;
        if ((PMASK >> (G + hf)) & 1) {
            p[hf * 2 + 0] = __byte_perm(polyexp(x[0], c.cb0, c.c421, c.c3, c.one), polyexp(x[1], c.cb0, c.c421, c.c3, c.one), 0x6521);
            p[hf * 2 + 1] = __byte_perm(polyexp(x[2], c.cb1, c.c421, c.c3, c.one), polyexp(x[3], c.cb1, c.c421, c.c3, c.one), 0x6521);
        } else {
            p[hf * 2 + 0] = pack_bf16(ex2(fmaf(x[0], QS, c.nm0)), ex2(fmaf(x[1], QS, c.nm0)));
            p[hf * 2 + 1] = pack_bf16(ex2(fmaf(x[2], QS, c.nm1)), ex2(fmaf(x[3], QS, c.nm1)));
        }
    }
}

__device__ __forceinline__ void max16(const float* s, float& mx0, float& mx1) {
    #pragma unroll
    for (int j = 0; j < 4; j++) {
        mx0 = fmaxf(mx0, fmaxf(s[4 * j], s[4 * j + 1]));
        mx1 = fmaxf(mx1, fmaxf(s[4 * j + 2], s[4 * j + 3]));
    }
}

__device__ void moe_cta(int part, unsigned char* smem, const __nv_bfloat16* __restrict__ x, const __nv_bfloat16* __restrict__ w_gate,
                        const __nv_bfloat16* __restrict__ w_up, const __nv_bfloat16* __restrict__ w_down) {
    float* xs = (float*)smem;
    float* red = xs + 1024;
    float* hs = red + 8 * 4 * 448;
    __shared__ float s_v[32];
    __shared__ int s_i[32];
    __shared__ int s_sel[2];
    const int tid = threadIdx.x, warp = tid >> 5, lane = tid & 31;
    for (int pass = 0; pass < 2; pass++) {
        float bv = -INFINITY; int bi = 0x7fffffff;
        const int excl = pass ? s_sel[0] : -1;
        for (int i = tid; i < S_; i += K2_THREADS) {
            float v = g_r[i];
            if (i != excl && (v > bv || (v == bv && i < bi) || bi == 0x7fffffff)) { bv = v; bi = i; }
        }
        #pragma unroll
        for (int o = 16; o; o >>= 1) {
            float ov = __shfl_xor_sync(~0u, bv, o); int oi = __shfl_xor_sync(~0u, bi, o);
            if (ov > bv || (ov == bv && oi < bi)) { bv = ov; bi = oi; }
        }
        if (lane == 0) { s_v[warp] = bv; s_i[warp] = bi; }
        __syncthreads();
        if (warp == 0) {
            bv = lane < 16 ? s_v[lane] : -INFINITY; bi = lane < 16 ? s_i[lane] : 0x7fffffff;
            #pragma unroll
            for (int o = 16; o; o >>= 1) {
                float ov = __shfl_xor_sync(~0u, bv, o); int oi = __shfl_xor_sync(~0u, bi, o);
                if (ov > bv || (ov == bv && oi < bi)) { bv = ov; bi = oi; }
            }
            if (lane == 0) s_sel[pass] = (bi == 0x7fffffff) ? pass : bi;
        }
        __syncthreads();
    }
    for (int i = tid; i < 1024; i += K2_THREADS) {
        const int tok = s_sel[i >> 9];
        const float2 st = g_stats[tok];
        xs[i] = ln_elem(__bfloat162float(x[(size_t)tok * D_ + (i & 511)]), st.x, st.y);
    }
    if (part == 0 && tid < 2) g_sel[tid] = s_sel[tid];
    __syncthreads();
    const int c0 = part * 448;
    if (tid < 448) {
        const int cg = tid % 56, ks = tid / 56;
        float a[4][8];
        #pragma unroll
        for (int i = 0; i < 4; i++)
            #pragma unroll
            for (int j = 0; j < 8; j++) a[i][j] = 0.f;
        const __nv_bfloat16* pg = w_gate + (size_t)(ks * 64) * F_ + c0 + cg * 8;
        const __nv_bfloat16* pu = w_up + (size_t)(ks * 64) * F_ + c0 + cg * 8;
        #pragma unroll 8
        for (int k = 0; k < 64; k++) {
            const uint4 gv = __ldg((const uint4*)(pg + (size_t)k * F_));
            const uint4 uv = __ldg((const uint4*)(pu + (size_t)k * F_));
            const float x0 = xs[ks * 64 + k], x1 = xs[512 + ks * 64 + k];
            const uint32_t gu[4] = {gv.x, gv.y, gv.z, gv.w}, uu[4] = {uv.x, uv.y, uv.z, uv.w};
            #pragma unroll
            for (int j = 0; j < 4; j++) {
                const float g0 = bf_lo(gu[j]), g1 = bf_hi(gu[j]), u0 = bf_lo(uu[j]), u1 = bf_hi(uu[j]);
                a[0][2 * j] = fmaf(x0, g0, a[0][2 * j]); a[0][2 * j + 1] = fmaf(x0, g1, a[0][2 * j + 1]);
                a[1][2 * j] = fmaf(x1, g0, a[1][2 * j]); a[1][2 * j + 1] = fmaf(x1, g1, a[1][2 * j + 1]);
                a[2][2 * j] = fmaf(x0, u0, a[2][2 * j]); a[2][2 * j + 1] = fmaf(x0, u1, a[2][2 * j + 1]);
                a[3][2 * j] = fmaf(x1, u0, a[3][2 * j]); a[3][2 * j + 1] = fmaf(x1, u1, a[3][2 * j + 1]);
            }
        }
        #pragma unroll
        for (int i = 0; i < 4; i++)
            #pragma unroll
            for (int j = 0; j < 8; j++) red[(ks * 4 + i) * 448 + cg * 8 + j] = a[i][j];
    }
    __syncthreads();
    for (int i = tid; i < 896; i += K2_THREADS) {
        const int tok = i / 448, c = i % 448;
        float gs = 0.f, us = 0.f;
        #pragma unroll
        for (int ks = 0; ks < 8; ks++) { gs += red[(ks * 4 + tok) * 448 + c]; us += red[(ks * 4 + 2 + tok) * 448 + c]; }
        gs = bf16r(gs); us = bf16r(us);
        const float sl = bf16r(gs / (1.0f + __expf(-gs)));
        hs[i] = bf16r(sl * us);
    }
    __syncthreads();
    {
        const int cg = tid & 63, fs = tid >> 6;
        float a[2][8];
        #pragma unroll
        for (int j = 0; j < 8; j++) { a[0][j] = 0.f; a[1][j] = 0.f; }
        const __nv_bfloat16* pd = w_down + (size_t)(c0 + fs * 56) * D_ + cg * 8;
        #pragma unroll 8
        for (int f = 0; f < 56; f++) {
            const uint4 dv = __ldg((const uint4*)(pd + (size_t)f * D_));
            const float h0 = hs[fs * 56 + f], h1 = hs[448 + fs * 56 + f];
            const uint32_t du[4] = {dv.x, dv.y, dv.z, dv.w};
            #pragma unroll
            for (int j = 0; j < 4; j++) {
                const float d0 = bf_lo(du[j]), d1 = bf_hi(du[j]);
                a[0][2 * j] = fmaf(h0, d0, a[0][2 * j]); a[0][2 * j + 1] = fmaf(h0, d1, a[0][2 * j + 1]);
                a[1][2 * j] = fmaf(h1, d0, a[1][2 * j]); a[1][2 * j + 1] = fmaf(h1, d1, a[1][2 * j + 1]);
            }
        }
        #pragma unroll
        for (int j = 0; j < 8; j++) { red[(fs * 2) * 512 + cg * 8 + j] = a[0][j]; red[(fs * 2 + 1) * 512 + cg * 8 + j] = a[1][j]; }
    }
    __syncthreads();
    for (int i = tid; i < 1024; i += K2_THREADS) {
        float s = 0.f;
        #pragma unroll
        for (int fs = 0; fs < 8; fs++) s += red[(fs * 2 + (i >> 9)) * 512 + (i & 511)];
        g_ypart[part][i >> 9][i & 511] = s;
    }
}

__global__ void __launch_bounds__(K2_THREADS, 1)
k2_attn(const __nv_bfloat16* __restrict__ x, const __nv_bfloat16* __restrict__ w_gate, const __nv_bfloat16* __restrict__ w_up,
        const __nv_bfloat16* __restrict__ w_down) {
    extern __shared__ __align__(1024) unsigned char smem[];
    TL(1, 0);
    pdl_launch();
    if (blockIdx.x >= 128) {
        const int part = blockIdx.x - 128;
        {
            const int k = threadIdx.x;
            asm volatile("cp.async.bulk.prefetch.L2.global [%0], %1;" :: "l"(w_gate + (size_t)k * F_ + part * 448), "r"(896) : "memory");
            asm volatile("cp.async.bulk.prefetch.L2.global [%0], %1;" :: "l"(w_up + (size_t)k * F_ + part * 448), "r"(896) : "memory");
            if (k < 56) asm volatile("cp.async.bulk.prefetch.L2.global [%0], %1;" :: "l"(w_down + (size_t)(part * 448 + k * 8) * D_), "r"(8192) : "memory");
        }
        pdl_wait(); TL(1, 1); moe_cta(blockIdx.x - 128, smem, x, w_gate, w_up, w_down); TL(1, 2); return; }
    const uint32_t sK = smem_u32(smem), sV = sK + 65536, sQ = sV + 98304, sBar = sQ + 16384;
    const int h = blockIdx.x >> 2, qb = blockIdx.x & 3;
    const int warp = __shfl_sync(~0u, threadIdx.x >> 5, 0), lane = threadIdx.x & 31, wg = warp >> 2;
    if (threadIdx.x == 0) {
        mbar_init(sBar, 1); mbar_init(sBar + 8, 1);
        asm volatile("fence.mbarrier_init.release.cluster;" ::: "memory");
        mbar_expect_tx(sBar, 16384 + 16384 + 2 * 8192);
        mbar_expect_tx(sBar + 8, 49152 + 2 * 24576);
    }
    for (int i = threadIdx.x; i < 2048; i += K2_THREADS) {
        const uint32_t v = is_poly_group(i >> 3) ? 0xBF80BF80u : 0x3F803F80u;
        *(uint4*)(smem + 65536 + 65536 + i * 16) = make_uint4(v, v, v, v);
    }
    fence_async_smem();
    __syncthreads();
    if (warp == 0) {
        pdl_wait();
        TL(1, 1);
        const uint4* gk = g_K + (size_t)h * 4096;
        const uint4* gv = g_V + (size_t)h * 4096;
        if (lane == 0) bulk_g2s(sQ, g_Q + (size_t)h * 4096 + qb * 1024, 16384, sBar);
        if (lane == 1) bulk_g2s(sK, gk, 16384, sBar);
        if (lane == 2) bulk_g2s(sV, gv, 8192, sBar);
        if (lane == 3) bulk_g2s(sV + 32768, gv + 2048, 8192, sBar);
        if (lane == 4) bulk_g2s(sK + 16384, gk + 1024, 49152, sBar + 8);
        if (lane == 5) bulk_g2s(sV + 8192, gv + 512, 24576, sBar + 8);
        if (lane == 6) bulk_g2s(sV + 32768 + 8192, gv + 2048 + 512, 24576, sBar + 8);
        __syncwarp();
    }
    ExpC c;
    {
        const volatile uint32_t* cc = g_const;
        c.c421 = cc[0]; c.c3 = __uint_as_float(cc[1]); c.one = __uint_as_float(cc[2]);
    }
    const uint32_t kdesc0 = (uint32_t)make_desc(sK, 128, 256, 0);
    const uint32_t vdesc0 = (uint32_t)make_desc(sV, 128, 32768, 0);
    #pragma unroll 1
    for (int pass = 0; pass < 2; pass++) {
        const bool dry = false;
        if (pass == 0) { mbar_wait(sBar, 0); __syncwarp(); TL(1, 2); }
        const int unit = (pass & 1) * 4 + wg;
        const uint32_t q = (uint32_t)make_desc(sQ + unit * 2048, 128, 256, 0);
        float o[12];
        #pragma unroll 1
        for (int attempt = 0; attempt < 2; attempt++) {
            float s0[16], s1[16], s2[16];
            #pragma unroll
            for (int i = 0; i < 16; i++) { s0[i] = 0.f; s1[i] = 0.f; s2[i] = 0.f; }
            float mx0 = -INFINITY, mx1 = -INFINITY;
            if (attempt) {
                #pragma unroll 1
                for (int it = 0; it < 64; it++) {
                    WG_FENCE();
                    wgmma_qk32(s0, q, kdesc0 + it * 64);
                    WG_COMMIT();
                    wg_wait<0>();
                    touch16(s0);
                    max16(s0, mx0, mx1);
                }
            }
            #pragma unroll
            for (int i = 0; i < 12; i++) o[i] = 0.f;
            WG_FENCE();
            wgmma_qk32(s2, q, kdesc0);
            wgmma_qk32(s0, q, kdesc0 + 64);
            wgmma_qk32(s1, q, kdesc0 + 128);
            WG_COMMIT();
            wg_wait<0>();
            touch16(s0); touch16(s1); touch16(s2);
            max16(s0, mx0, mx1); max16(s1, mx0, mx1); max16(s2, mx0, mx1);
            mx0 = fmaxf(mx0, __shfl_xor_sync(~0u, mx0, 1)); mx0 = fmaxf(mx0, __shfl_xor_sync(~0u, mx0, 2));
            mx1 = fmaxf(mx1, __shfl_xor_sync(~0u, mx1, 1)); mx1 = fmaxf(mx1, __shfl_xor_sync(~0u, mx1, 2));
            const float bias = attempt ? 0.0f : 64.0f;
            c.nm0 = __shfl_sync(~0u, -fmaf(mx0, QS, bias), lane); c.nm1 = __shfl_sync(~0u, -fmaf(mx1, QS, bias), lane);
            c.cb0 = __shfl_sync(~0u, (127.0f + c.nm0) * (1.0f / 255.0f), lane);
            c.cb1 = __shfl_sync(~0u, (127.0f + c.nm1) * (1.0f / 255.0f), lane);
            uint32_t kd = kdesc0 + 192, vd = vdesc0 + 32;
            {
                uint32_t pa[4], pb[4];
                exp_block<12>(s2, pa, c);
                exp_block<14>(s2 + 8, pb, c);
                WG_FENCE();
                wgmma_pv(o, pa, vdesc0); wgmma_pv(o, pb, vdesc0 + 16);
                WG_COMMIT();
            }
            #pragma unroll 1
            for (int seg = 0; seg < (dry ? 1 : 2); seg++) {
            if (seg) { wg_wait<0>(); mbar_wait(sBar + 8, 0); __syncwarp(); }
            #pragma unroll 1
            for (int it = seg ? 3 : (dry ? 2 : 0); it < (seg ? 21 : 3); it++) {
                uint32_t p[6][4];
                WG_FENCE();
                wgmma_qk32(s2, q, kd);
                WG_COMMIT();
                exp_block<0>(s0, p[0], c);
                exp_block<2>(s0 + 8, p[1], c);
                WG_FENCE();
                wgmma_pv(o, p[0], vd); wgmma_pv(o, p[1], vd + 16);
                wgmma_qk32(s0, q, kd + 64);
                WG_COMMIT();
                wg_wait<1>();
                touch16(s2);
                exp_block<4>(s1, p[2], c);
                exp_block<6>(s1 + 8, p[3], c);
                WG_FENCE();
                wgmma_pv(o, p[2], vd + 32); wgmma_pv(o, p[3], vd + 48);
                wgmma_qk32(s1, q, kd + 128);
                WG_COMMIT();
                wg_wait<1>();
                touch16(s0);
                exp_block<8>(s2, p[4], c);
                exp_block<10>(s2 + 8, p[5], c);
                WG_FENCE();
                wgmma_pv(o, p[4], vd + 64); wgmma_pv(o, p[5], vd + 80);
                WG_COMMIT();
                vd += 96; kd += 192;
                wg_wait<1>();
                touch16(s1);
            }
            }
            wg_wait<0>();
            touch12(o);
            if (attempt) break;
            float big = 0.f;
            #pragma unroll
            for (int i = 0; i < 12; i++) big = fmaxf(big, fabsf(o[i]));
            bool bad = !(big < 1e30f);
            #pragma unroll
            for (int i = 0; i < 12; i++) bad |= (o[i] != o[i]);
            uint32_t any;
            asm volatile("{.reg .pred p, q; setp.ne.u32 p, %1, 0; barrier.cta.red.or.pred.aligned q, %2, 128, p; selp.u32 %0, 1, 0, q;}"
                         : "=r"(any) : "r"((uint32_t)bad), "r"(1 + wg) : "memory");
            if (dry || !__any_sync(~0u, any)) break;
        }
        const int g = lane >> 2, t = lane & 3;
        const int r = (warp & 3) * 16 + g;
        const float i0 = __fdiv_rn(1.0f, o[8]), i1 = __fdiv_rn(1.0f, o[10]);
        uint32_t* ob = (uint32_t*)(g_O + (size_t)(qb * 8 + unit) * 4096 + (h >> 2) * 512 + r * 8) + t;
        const int c0 = ((h & 3) * 2) ^ (r & 7), c1 = ((h & 3) * 2 + 1) ^ (r & 7);
        if (!dry) {
            ob[c0 * 4] = pack_bf16(o[0] * i0, o[1] * i0);
            ob[c1 * 4] = pack_bf16(o[4] * i0, o[5] * i0);
            ob[256 + c0 * 4] = pack_bf16(o[2] * i1, o[3] * i1);
            ob[256 + c1 * 4] = pack_bf16(o[6] * i1, o[7] * i1);
            TL(1, 3 + pass);
        }
    }
}

constexpr int K3_THREADS = 256;
constexpr int K3_SMEM = 65536 + 131072 + 128;

__global__ void __launch_bounds__(K3_THREADS, 1)
k3_out(const __grid_constant__ CUtensorMap wmap, const __nv_bfloat16* __restrict__ x, __nv_bfloat16* __restrict__ out) {
    extern __shared__ __align__(1024) unsigned char smem[];
    const uint32_t sA = smem_u32(smem), sB = sA + 65536, sBar = sB + 131072;
    const int warp = __shfl_sync(~0u, threadIdx.x >> 5, 0), lane = threadIdx.x & 31, wg = warp >> 2;
    const int nt = blockIdx.x & 3, mt = blockIdx.x >> 2;
    TL(2, 0);
    if (threadIdx.x == 0) {
        for (int i = 0; i < 6; i++) mbar_init(sBar + i * 8, 1);
        asm volatile("fence.mbarrier_init.release.cluster;" ::: "memory");
        for (int kh = 0; kh < 2; kh++) {
            mbar_expect_tx(sBar + kh * 8, 65536);
            tma_2d(sB + kh * 32768, &wmap, nt * 128, kh * 256, sBar + kh * 8);
            tma_2d(sB + 65536 + kh * 32768, &wmap, nt * 128 + 64, kh * 256, sBar + kh * 8);
        }
    }
    const int er = threadIdx.x >> 2, ec = (threadIdx.x & 3) * 32;
    const int row = mt * 64 + er;
    uint4 xv[4];
    #pragma unroll
    for (int j = 0; j < 4; j++) xv[j] = __ldg((const uint4*)(x + (size_t)row * D_ + nt * 128 + ec) + j);
    pdl_wait();
    TL(2, 1);
    if (threadIdx.x == 0) {
        for (int q = 0; q < 4; q++) {
            mbar_expect_tx(sBar + 16 + q * 8, 16384);
            bulk_g2s(sA + q * 16384, g_O + (size_t)mt * 4096 + q * 1024, 16384, sBar + 16 + q * 8);
        }
    }
    const int sel0 = g_sel[0], sel1 = g_sel[1];
    const float2 st = g_stats[row];
    uint32_t bb[16];
    {
        const uint32_t xu[16] = {xv[0].x, xv[0].y, xv[0].z, xv[0].w, xv[1].x, xv[1].y, xv[1].z, xv[1].w,
                                 xv[2].x, xv[2].y, xv[2].z, xv[2].w, xv[3].x, xv[3].y, xv[3].z, xv[3].w};
        #pragma unroll
        for (int j = 0; j < 16; j++) bb[j] = pack_bf16(bf16r(bf_lo(xu[j]) - st.x) * st.y, bf16r(bf_hi(xu[j]) - st.x) * st.y);
        const int slot = row == sel0 ? 0 : (row == sel1 ? 1 : -1);
        if (slot >= 0) {
            const float gate = bf16r(1.0f / (1.0f + __expf(-g_r[row])));
            const int c0 = nt * 128 + ec;
            #pragma unroll
            for (int j = 0; j < 16; j++) {
                const float2 a = *(const float2*)&g_ypart[0][slot][c0 + 2 * j], b = *(const float2*)&g_ypart[1][slot][c0 + 2 * j];
                const float2 c = *(const float2*)&g_ypart[2][slot][c0 + 2 * j], d = *(const float2*)&g_ypart[3][slot][c0 + 2 * j];
                bb[j] = pack_bf16(bf_lo(bb[j]) + bf16r(bf16r(a.x + b.x + c.x + d.x) * gate), bf_hi(bb[j]) + bf16r(bf16r(a.y + b.y + c.y + d.y) * gate));
            }
        }
    }
    __syncthreads();
    float acc[32];
    #pragma unroll
    for (int i = 0; i < 32; i++) acc[i] = 0.f;
    const uint64_t da0 = make_desc(sA, 16, 1024, 1);
    const uint64_t db0 = make_desc(sB + wg * 65536, 8192, 1024, 1);
    #pragma unroll 1
    for (int q = 0; q < 4; q++) {
        if ((q & 1) == 0) mbar_wait(sBar + (q >> 1) * 8, 0);
        mbar_wait(sBar + 16 + q * 8, 0);
        WG_FENCE();
        #pragma unroll
        for (int kk = 0; kk < 8; kk++)
            wgmma_n64(acc, da0 + (uint64_t)(q * 1024 + (kk >> 2) * 512 + (kk & 3) * 2), db0 + (uint64_t)(q * 1024 + kk * 128));
        WG_COMMIT();
    }
    wg_wait<0>();
    touch32(acc);
    TL(2, 2);
    __syncthreads();
    {
        const int g = lane >> 2, t = lane & 3;
        unsigned char* sp = smem + ((warp & 3) * 16 + g) * 272 + wg * 128 + t * 4;
        #pragma unroll
        for (int j = 0; j < 8; j++) {
            *(uint32_t*)(sp + j * 16) = pack_bf16(acc[4 * j], acc[4 * j + 1]);
            *(uint32_t*)(sp + 8 * 272 + j * 16) = pack_bf16(acc[4 * j + 2], acc[4 * j + 3]);
        }
    }
    __syncthreads();
    #pragma unroll
    for (int j = 0; j < 4; j++) {
        const uint4 av = *(const uint4*)(smem + er * 272 + ec * 2 + j * 16);
        const uint32_t au[4] = {av.x, av.y, av.z, av.w}, xu[4] = {xv[j].x, xv[j].y, xv[j].z, xv[j].w};
        uint32_t o[4];
        #pragma unroll
        for (int i = 0; i < 4; i++) {
            uint32_t t2;
            asm("add.rn.bf16x2 %0, %1, %2;" : "=r"(t2) : "r"(xu[i]), "r"(au[i]));
            asm("add.rn.bf16x2 %0, %1, %2;" : "=r"(o[i]) : "r"(t2), "r"(bb[j * 4 + i]));
        }
        *((uint4*)(out + (size_t)row * D_ + nt * 128 + ec) + j) = make_uint4(o[0], o[1], o[2], o[3]);
    }
    TL(2, 3);
}

typedef CUresult (*EncodeFn)(CUtensorMap*, CUtensorMapDataType, cuuint32_t, void*, const cuuint64_t*, const cuuint64_t*,
                             const cuuint32_t*, const cuuint32_t*, CUtensorMapInterleave, CUtensorMapSwizzle,
                             CUtensorMapL2promotion, CUtensorMapFloatOOBfill);

void make_wmap(EncodeFn fn, CUtensorMap* map, const void* ptr, int rows, int cols, int box_rows) {
    cuuint64_t dims[2] = {(cuuint64_t)cols, (cuuint64_t)rows};
    cuuint64_t strides[1] = {(cuuint64_t)cols * 2};
    cuuint32_t box[2] = {64, (cuuint32_t)box_rows};
    cuuint32_t es[2] = {1, 1};
    fn(map, CU_TENSOR_MAP_DATA_TYPE_BFLOAT16, 2, (void*)ptr, dims, strides, box, es, CU_TENSOR_MAP_INTERLEAVE_NONE,
       CU_TENSOR_MAP_SWIZZLE_128B, CU_TENSOR_MAP_L2_PROMOTION_L2_256B, CU_TENSOR_MAP_FLOAT_OOB_FILL_NONE);
}

}

extern "C" void kernel_launch(void* const* d_in, const int* in_sizes, int n_in, void* d_out, int out_size) {
    const __nv_bfloat16* x = (const __nv_bfloat16*)d_in[0];
    const __nv_bfloat16* wqkv = (const __nv_bfloat16*)d_in[1];
    const __nv_bfloat16* wo = (const __nv_bfloat16*)d_in[2];
    const __nv_bfloat16* w_r = (const __nv_bfloat16*)d_in[4];
    const __nv_bfloat16* w_gate = (const __nv_bfloat16*)d_in[5];
    const __nv_bfloat16* w_up = (const __nv_bfloat16*)d_in[6];
    const __nv_bfloat16* w_down = (const __nv_bfloat16*)d_in[7];
    __nv_bfloat16* out = (__nv_bfloat16*)d_out;

    static EncodeFn encode = nullptr;
    if (!encode) {
        void* fn = nullptr;
        cudaDriverEntryPointQueryResult qres;
        cudaGetDriverEntryPoint("cuTensorMapEncodeTiled", &fn, cudaEnableDefault, &qres);
        encode = (EncodeFn)fn;
        cudaFuncSetAttribute(k1_ln_qkv, cudaFuncAttributeMaxDynamicSharedMemorySize, K1_SMEM);
        cudaFuncSetAttribute(k2_attn, cudaFuncAttributeMaxDynamicSharedMemorySize, K2_SMEM);
        cudaFuncSetAttribute(k3_out, cudaFuncAttributeMaxDynamicSharedMemorySize, K3_SMEM);
    }
    CUtensorMap map_qkv, map_wo, map_x;
    make_wmap(encode, &map_x, x, S_, D_, 64);
    make_wmap(encode, &map_qkv, wqkv, D_, 3 * D_, 64);
    make_wmap(encode, &map_wo, wo, D_, D_, 256);

    k1_ln_qkv<<<128, K1_THREADS, K1_SMEM, cudaStreamPerThread>>>(map_qkv, map_x, w_r);
    cudaLaunchAttribute at[1];
    at[0].id = cudaLaunchAttributeProgrammaticStreamSerialization;
    at[0].val.programmaticStreamSerializationAllowed = 1;
    cudaLaunchConfig_t cfg = {};
    cfg.stream = cudaStreamPerThread;
    cfg.attrs = at; cfg.numAttrs = 1;
    cfg.gridDim = dim3(132); cfg.blockDim = dim3(K2_THREADS); cfg.dynamicSmemBytes = K2_SMEM;
    cudaLaunchKernelEx(&cfg, k2_attn, x, w_gate, w_up, w_down);
    cfg.gridDim = dim3(128); cfg.blockDim = dim3(K3_THREADS); cfg.dynamicSmemBytes = K3_SMEM;
    cudaLaunchKernelEx(&cfg, k3_out, map_wo, x, out);
}
```

```cpp
#include <cuda_runtime.h>
#include <cuda_bf16.h>
#include <cuda.h>
#include <stdint.h>

namespace {

constexpr int S_ = 2048, D_ = 512, H_ = 32, F_ = 1792;

constexpr uint32_t PMASK = 0xA52;
__host__ __device__ constexpr bool is_poly_group(int g8) { return g8 >= 4 && ((PMASK >> ((g8 - 4) % 12)) & 1); }

__device__ __align__(1024) uint4 g_QKV[3 * H_ * S_ * 2];
#define g_Q (g_QKV)
#define g_K (g_QKV + H_ * S_ * 2)
#define g_V (g_QKV + 2 * H_ * S_ * 2)
__device__ __align__(1024) uint4 g_O[S_ * D_ / 8];
__device__ float2 g_stats[S_];
__device__ uint32_t g_const[4] = {421u, 0x459EB285u  , 0x3F800000u  , 0u};
__device__ float g_r[S_];
__device__ __align__(16) float g_ypart[4][2][D_];
__device__ int g_sel[2];

#define TL(k, p)
#define CK(i)
__device__ __forceinline__ uint32_t smem_u32(const void* p) { return (uint32_t)__cvta_generic_to_shared(p); }
__device__ __forceinline__ float bf16r(float x) { return __bfloat162float(__float2bfloat16_rn(x)); }
__device__ __forceinline__ uint32_t pack_bf16(float lo, float hi) {
    uint32_t r; asm("cvt.rn.bf16x2.f32 %0, %1, %2;" : "=r"(r) : "f"(hi), "f"(lo)); return r;
}
__device__ __forceinline__ float bf_lo(uint32_t u) { return __uint_as_float(u << 16); }
__device__ __forceinline__ float bf_hi(uint32_t u) { return __uint_as_float(u & 0xFFFF0000u); }
__device__ __forceinline__ float ex2(float x) { float y; asm("ex2.approx.ftz.f32 %0, %1;" : "=f"(y) : "f"(x)); return y; }

__device__ __forceinline__ void mbar_init(uint32_t bar, uint32_t count) {
    asm volatile("mbarrier.init.shared::cta.b64 [%0], %1;" :: "r"(bar), "r"(count) : "memory");
}
__device__ __forceinline__ void mbar_expect_tx(uint32_t bar, uint32_t bytes) {
    asm volatile("mbarrier.arrive.expect_tx.shared::cta.b64 _, [%0], %1;" :: "r"(bar), "r"(bytes) : "memory");
}
__device__ __forceinline__ void mbar_arrive(uint32_t bar) {
    asm volatile("mbarrier.arrive.shared::cta.b64 _, [%0];" :: "r"(bar) : "memory");
}
__device__ __forceinline__ void mbar_wait(uint32_t bar, uint32_t parity) {
    uint32_t done;
    #pragma unroll 1
    for (int it = 0; it < (1 << 26); it++) {
        asm volatile("{.reg .pred p; mbarrier.try_wait.parity.shared::cta.b64 p, [%1], %2; selp.u32 %0, 1, 0, p;}"
                     : "=r"(done) : "r"(bar), "r"(parity) : "memory");
        if (done) return;
    }
    __trap();
}
__device__ __forceinline__ void bulk_g2s(uint32_t dst, const void* src, uint32_t bytes, uint32_t bar) {
    asm volatile("cp.async.bulk.shared::cluster.global.mbarrier::complete_tx::bytes [%0], [%1], %2, [%3];"
                 :: "r"(dst), "l"(src), "r"(bytes), "r"(bar) : "memory");
}
__device__ __forceinline__ void tma_2d(uint32_t dst, const CUtensorMap* map, int c0, int c1, uint32_t bar) {
    asm volatile("cp.async.bulk.tensor.2d.shared::cluster.global.mbarrier::complete_tx::bytes [%0], [%1, {%3, %4}], [%2];"
                 :: "r"(dst), "l"(map), "r"(bar), "r"(c0), "r"(c1) : "memory");
}
__device__ __forceinline__ void fence_async_smem() { asm volatile("fence.proxy.async.shared::cta;" ::: "memory"); }
__device__ __forceinline__ void named_bar(int id, int n) { asm volatile("bar.sync %0, %1;" :: "r"(id), "r"(n) : "memory"); }

__device__ __forceinline__ uint64_t make_desc(uint32_t saddr, uint32_t lbo, uint32_t sbo, uint32_t swz) {
    return (uint64_t)((saddr & 0x3FFFF) >> 4) | ((uint64_t)(lbo >> 4) << 16) | ((uint64_t)(sbo >> 4) << 32) | ((uint64_t)swz << 62);
}
#define WG_FENCE() asm volatile("wgmma.fence.sync.aligned;" ::: "memory")
#define WG_COMMIT() asm volatile("wgmma.commit_group.sync.aligned;" ::: "memory")
template <int N> __device__ __forceinline__ void wg_wait() { asm volatile("wgmma.wait_group.sync.aligned %0;" :: "n"(N) : "memory"); }

#define F4(d, o) "+f"(d[o]), "+f"(d[o + 1]), "+f"(d[o + 2]), "+f"(d[o + 3])
#define F16(d, o) F4(d, o), F4(d, o + 4), F4(d, o + 8), F4(d, o + 12)
#define F32(d, o) F16(d, o), F16(d, o + 16)

__device__ __forceinline__ void wgmma_rs_n128(float* d, const uint32_t* a, uint64_t db) {
    asm volatile("wgmma.mma_async.sync.aligned.m64n128k16.f32.bf16.bf16 "
        "{%0,%1,%2,%3,%4,%5,%6,%7,%8,%9,%10,%11,%12,%13,%14,%15,%16,%17,%18,%19,%20,%21,%22,%23,%24,%25,%26,%27,%28,%29,%30,%31,"
        "%32,%33,%34,%35,%36,%37,%38,%39,%40,%41,%42,%43,%44,%45,%46,%47,%48,%49,%50,%51,%52,%53,%54,%55,%56,%57,%58,%59,%60,%61,%62,%63}, "
        "{%64,%65,%66,%67}, %68, 1, 1, 1, 1;\n"
        : F32(d, 0), F32(d, 32) : "r"(a[0]), "r"(a[1]), "r"(a[2]), "r"(a[3]), "l"(db));
}
__device__ __forceinline__ void wgmma_rs_n64(float* d, const uint32_t* a, uint64_t db) {
    asm volatile("wgmma.mma_async.sync.aligned.m64n64k16.f32.bf16.bf16 "
        "{%0,%1,%2,%3,%4,%5,%6,%7,%8,%9,%10,%11,%12,%13,%14,%15,%16,%17,%18,%19,%20,%21,%22,%23,%24,%25,%26,%27,%28,%29,%30,%31}, "
        "{%32,%33,%34,%35}, %36, 1, 1, 1, 1;\n"
        : F32(d, 0) : "r"(a[0]), "r"(a[1]), "r"(a[2]), "r"(a[3]), "l"(db));
}
__device__ __forceinline__ void wgmma_n64(float* d, uint64_t da, uint64_t db) {
    asm volatile("wgmma.mma_async.sync.aligned.m64n64k16.f32.bf16.bf16 "
        "{%0,%1,%2,%3,%4,%5,%6,%7,%8,%9,%10,%11,%12,%13,%14,%15,%16,%17,%18,%19,%20,%21,%22,%23,%24,%25,%26,%27,%28,%29,%30,%31}, "
        "%32, %33, 1, 1, 1, 0, 1;\n"
        : F32(d, 0) : "l"(da), "l"(db));
}
__device__ __forceinline__ void wgmma_qk32(float* d, uint32_t qd, uint32_t kd) {
    asm volatile("{.reg .b64 a, b; mov.b64 a, {%16, 16}; mov.b64 b, {%17, 16};\n"
        "wgmma.mma_async.sync.aligned.m64n32k16.f32.bf16.bf16 {%0,%1,%2,%3,%4,%5,%6,%7,%8,%9,%10,%11,%12,%13,%14,%15}, a, b, 0, 1, 1, 0, 0;}\n"
        : F16(d, 0) : "r"(qd), "r"(kd));
}
__device__ __forceinline__ void wgmma_pv(float* d, const uint32_t* a, uint32_t vd) {
    asm volatile("{.reg .b64 b; mov.b64 b, {%16, 2048};\n"
        "wgmma.mma_async.sync.aligned.m64n24k16.f32.bf16.bf16 {%0,%1,%2,%3,%4,%5,%6,%7,%8,%9,%10,%11}, {%12,%13,%14,%15}, b, 1, 1, 1, 1;}\n"
        : F4(d, 0), F4(d, 4), F4(d, 8) : "r"(a[0]), "r"(a[1]), "r"(a[2]), "r"(a[3]), "r"(vd));
}
__device__ __forceinline__ void touch16(float* d) { asm volatile("" : F16(d, 0) :: "memory"); }
__device__ __forceinline__ void touch12(float* d) { asm volatile("" : F4(d, 0), F4(d, 4), F4(d, 8) :: "memory"); }
__device__ __forceinline__ void touch32(float* d) { asm volatile("" : F32(d, 0) :: "memory"); }
__device__ __forceinline__ void touch64(float* d) { asm volatile("" : F32(d, 0), F32(d, 32) :: "memory"); }

__device__ __forceinline__ float ln_elem(float x, float mean_b, float rden) {
    return bf16r(bf16r(x - mean_b) * rden);
}
__device__ __forceinline__ void pdl_wait() { asm volatile("griddepcontrol.wait;" ::: "memory"); }
__device__ __forceinline__ void pdl_launch() { asm volatile("griddepcontrol.launch_dependents;" ::: "memory"); }
__device__ __forceinline__ void cluster_arrive() { asm volatile("barrier.cluster.arrive.release.aligned;" ::: "memory"); }
__device__ __forceinline__ void cluster_wait() { asm volatile("barrier.cluster.wait.acquire.aligned;" ::: "memory"); }

constexpr int K1_THREADS = 288;
constexpr int K1_SMEM = 131072 + 6 * 16384 + 128 + 1024;

__device__ __forceinline__ void ldsm4(uint32_t* r, uint32_t addr) {
    asm volatile("ldmatrix.sync.aligned.m8n8.x4.shared.b16 {%0, %1, %2, %3}, [%4];" : "=r"(r[0]), "=r"(r[1]), "=r"(r[2]), "=r"(r[3]) : "r"(addr) : "memory");
}
__device__ __forceinline__ void stsm4(uint32_t addr, uint32_t r0, uint32_t r1, uint32_t r2, uint32_t r3) {
    asm volatile("stmatrix.sync.aligned.m8n8.x4.shared.b16 [%0], {%1, %2, %3, %4};" :: "r"(addr), "r"(r0), "r"(r1), "r"(r2), "r"(r3) : "memory");
}
__device__ __forceinline__ void mma16816(float* d, const uint32_t* a, uint32_t b0, uint32_t b1) {
    asm("mma.sync.aligned.m16n8k16.row.col.f32.bf16.bf16.f32 {%0,%1,%2,%3}, {%4,%5,%6,%7}, {%8,%9}, {%0,%1,%2,%3};"
        : "+f"(d[0]), "+f"(d[1]), "+f"(d[2]), "+f"(d[3]) : "r"(a[0]), "r"(a[1]), "r"(a[2]), "r"(a[3]), "r"(b0), "r"(b1));
}
__device__ __forceinline__ uint32_t sub_bf16x2(uint32_t a, uint32_t b) {
    uint32_t d; asm("sub.rn.bf16x2 %0, %1, %2;" : "=r"(d) : "r"(a), "r"(b)); return d;
}
__device__ __forceinline__ uint32_t ln_pair(uint32_t x2, uint32_t mean2, uint32_t rhi2, uint32_t rlo2) {
    const uint32_t d = sub_bf16x2(x2, mean2);
    uint32_t t, y;
    asm("mul.rn.bf16x2 %0, %1, %2;" : "=r"(t) : "r"(d), "r"(rlo2));
    asm("fma.rn.bf16x2 %0, %1, %2, %3;" : "=r"(y) : "r"(d), "r"(rhi2), "r"(t));
    return y;
}
struct LnRow { uint32_t m2, hi2, lo2; };
__device__ __forceinline__ LnRow ln_row(float mean, float rden) {
    LnRow r;
    r.m2 = pack_bf16(mean, mean);
    r.hi2 = pack_bf16(rden, rden);
    const float lo = rden - bf_lo(r.hi2);
    r.lo2 = pack_bf16(lo, lo);
    return r;
}
__device__ __forceinline__ void ln_frag(uint32_t* a, const LnRow& r0, const LnRow& r1) {
    a[0] = ln_pair(a[0], r0.m2, r0.hi2, r0.lo2); a[1] = ln_pair(a[1], r1.m2, r1.hi2, r1.lo2);
    a[2] = ln_pair(a[2], r0.m2, r0.hi2, r0.lo2); a[3] = ln_pair(a[3], r1.m2, r1.hi2, r1.lo2);
}

template <int NJ>
__device__ __forceinline__ void k1_store(const float* acc, int jj0, int nt, int row0, int lane) {
    const int g = lane >> 2, t = lane & 3, g8a = row0 >> 3;
    const uint32_t sx0 = is_poly_group(g8a) ? 0x80008000u : 0u, sx1 = is_poly_group(g8a + 1) ? 0x80008000u : 0u;
    const int off_qk = g8a * 64 + g * 4 + t, off_v = (row0 + g) * 4 + t;
    #pragma unroll
    for (int jj = 0; jj < NJ; jj++) {
        const int hg = nt * 12 + jj0 + jj;
        const bool isv = hg >= 64;
        const uint32_t x0 = isv ? sx0 : 0u, x1 = isv ? sx1 : 0u;
        uint32_t* base = (uint32_t*)g_QKV + (size_t)hg * 16384 + (isv ? off_v : off_qk);
        const int hs = isv ? 8192 : 32, rs = isv ? 32 : 64;
        base[0] = pack_bf16(acc[8 * jj], acc[8 * jj + 1]) ^ x0;
        base[rs] = pack_bf16(acc[8 * jj + 2], acc[8 * jj + 3]) ^ x1;
        base[hs] = pack_bf16(acc[8 * jj + 4], acc[8 * jj + 5]) ^ x0;
        base[hs + rs] = pack_bf16(acc[8 * jj + 6], acc[8 * jj + 7]) ^ x1;
    }
}

__global__ void __launch_bounds__(K1_THREADS, 1)
k1_ln_qkv(const __grid_constant__ CUtensorMap wmap, const __grid_constant__ CUtensorMap xmap, const __nv_bfloat16* __restrict__ w_r) {
    extern __shared__ __align__(1024) unsigned char smem[];
    const uint32_t sA = smem_u32(smem), sB = sA + 131072, sBar = sB + 6 * 16384;
    const int warp = __shfl_sync(~0u, threadIdx.x >> 5, 0), lane = threadIdx.x & 31;
    const int nt = blockIdx.x & 7, mt = blockIdx.x >> 3;
    const int wg = warp >> 2;
    CK(0);
    pdl_launch();
    uint32_t* s_wr = (uint32_t*)(smem + 131072 + 6 * 16384 + 128);
    if (warp == 8) {
        if (lane == 0) {
            for (int i = 0; i < 6; i++) { mbar_init(sBar + i * 8, 1); mbar_init(sBar + 48 + i * 8, 2); }
            mbar_init(sBar + 96, 1); mbar_init(sBar + 104, 1);
            asm volatile("fence.mbarrier_init.release.cluster;" ::: "memory");
            mbar_expect_tx(sBar + 96, 65536); mbar_expect_tx(sBar + 104, 65536);
            for (int i = 0; i < 6; i++) mbar_expect_tx(sBar + i * 8, 16384);
        }
        __syncwarp();
        if (lane < 16) tma_2d(sA + (lane & 7) * 16384 + (lane >> 3) * 8192, &xmap, (lane & 7) * 64, mt * 128 + (lane >> 3) * 64, sBar + 96 + (lane >> 3) * 8);
        named_bar(3, K1_THREADS);
        mbar_wait(sBar + 96, 0);
        if (lane < 12) {
            const int ld = lane >> 1, j = lane & 1;
            tma_2d(sB + ld * 16384 + j * 8192, &wmap, nt * 192 + j * 64, ld * 64, sBar + ld * 8);
        }
        __syncwarp();
        if (lane < 2) {
            for (int ld = 6; ld < 12; ld++) {
                const int sl = ld - 6;
                mbar_wait(sBar + 48 + sl * 8, 0);
                if (lane == 0) mbar_expect_tx(sBar + sl * 8, 16384);
                __syncwarp(3);
                if (ld < 8) tma_2d(sB + sl * 16384 + lane * 8192, &wmap, nt * 192 + lane * 64, ld * 64, sBar + sl * 8);
                else tma_2d(sB + sl * 16384 + lane * 8192, &wmap, nt * 192 + 128, (ld - 8) * 128 + lane * 64, sBar + sl * 8);
            }
        }
        return;
    }
    if (nt == 0) s_wr[threadIdx.x] = __ldg((const uint32_t*)w_r + threadIdx.x);
    named_bar(3, K1_THREADS);
    const int g = lane >> 2, t = lane & 3;
    const int lrow = warp * 16 + (lane & 7) + ((lane >> 3) & 1) * 8;
    const uint32_t lbase = sA + lrow * 128;
    const int lsw = lane & 7, lhi = lane >> 4;
    uint32_t laddr[4];
    #pragma unroll
    for (int k4 = 0; k4 < 4; k4++) laddr[k4] = lbase + (((k4 * 2 + lhi) ^ lsw) * 16);
    CK(1);
    mbar_wait(sBar + 96 + wg * 8, 0);
    CK(2);
    float dsum[4] = {0.f, 0.f, 0.f, 0.f}, dq0[4] = {0.f, 0.f, 0.f, 0.f}, dq1[4] = {0.f, 0.f, 0.f, 0.f};
    float esum[4] = {0.f, 0.f, 0.f, 0.f}, eq0[4] = {0.f, 0.f, 0.f, 0.f}, eq1[4] = {0.f, 0.f, 0.f, 0.f};
    #pragma unroll 2
    for (int pn = 0; pn < 8; pn++) {
        uint32_t a[4][4];
        #pragma unroll
        for (int k4 = 0; k4 < 4; k4++) ldsm4(a[k4], laddr[k4] + pn * 16384);
        #pragma unroll
        for (int k4 = 0; k4 < 4; k4 += 2) {
            mma16816(dsum, a[k4], 0x3F803F80u, 0x3F803F80u);
            mma16816(dq0, a[k4], a[k4][0], a[k4][2]);
            mma16816(dq1, a[k4], a[k4][1], a[k4][3]);
            mma16816(esum, a[k4 + 1], 0x3F803F80u, 0x3F803F80u);
            mma16816(eq0, a[k4 + 1], a[k4 + 1][0], a[k4 + 1][2]);
            mma16816(eq1, a[k4 + 1], a[k4 + 1][1], a[k4 + 1][3]);
        }
    }
    #pragma unroll
    for (int i = 0; i < 4; i++) { dsum[i] += esum[i]; dq0[i] += eq0[i]; dq1[i] += eq1[i]; }
    CK(3);
    const int dsrc = g * 4 + (g >> 1);
    const float sq0 = __shfl_sync(~0u, (g & 1) ? dq0[1] : dq0[0], dsrc), sq1 = __shfl_sync(~0u, (g & 1) ? dq1[3] : dq1[2], dsrc);
    const float mean0 = dsum[0] * (1.0f / D_), mean1 = dsum[2] * (1.0f / D_);
    float var0 = fmaf(-mean0, mean0, sq0 * (1.0f / D_)), var1 = fmaf(-mean1, mean1, sq1 * (1.0f / D_));
    if (__any_sync(~0u, !(mean0 * mean0 <= 16.0f * var0) || !(mean1 * mean1 <= 16.0f * var1))) {
        float q0 = 0.f, q1 = 0.f;
        #pragma unroll 1
        for (int ks = 0; ks < 32; ks++) {
            uint32_t a[4];
            ldsm4(a, lbase + (ks >> 2) * 16384 + ((((ks & 3) * 2 + lhi) ^ lsw) * 16));
            #pragma unroll
            for (int i = 0; i < 4; i++) {
                const float m = (i & 1) ? mean1 : mean0;
                const float d0 = bf_lo(a[i]) - m, d1 = bf_hi(a[i]) - m;
                if (i & 1) q1 = fmaf(d0, d0, fmaf(d1, d1, q1)); else q0 = fmaf(d0, d0, fmaf(d1, d1, q0));
            }
        }
        q0 += __shfl_xor_sync(~0u, q0, 1); q0 += __shfl_xor_sync(~0u, q0, 2);
        q1 += __shfl_xor_sync(~0u, q1, 1); q1 += __shfl_xor_sync(~0u, q1, 2);
        var0 = q0 * (1.0f / D_); var1 = q1 * (1.0f / D_);
    }
    const float rs0 = __frcp_rn(bf16r(__fsqrt_rn(bf16r(bf16r(var0) + 1e-5f))));
    const float rs1 = __frcp_rn(bf16r(__fsqrt_rn(bf16r(bf16r(var1) + 1e-5f))));
    const LnRow lr0 = ln_row(mean0, rs0), lr1 = ln_row(mean1, rs1);
    float acc[64];
    #pragma unroll
    for (int i = 0; i < 64; i++) acc[i] = 0.f;
    float dr[4] = {0.f, 0.f, 0.f, 0.f};
    const uint64_t db0 = make_desc(sB, 8192, 1024, 1);
    #pragma unroll 1
    for (int kc = 0; kc < 8; kc += 2) {
        #pragma unroll
        for (int h2 = 0; h2 < 2; h2++) {
            const int ld = kc + h2, sl = ld < 6 ? ld : ld - 6;
            uint32_t a[4][4];
            #pragma unroll
            for (int k4 = 0; k4 < 4; k4++) ldsm4(a[k4], laddr[k4] + ld * 16384);
            #pragma unroll
            for (int k4 = 0; k4 < 4; k4++) ln_frag(a[k4], lr0, lr1);
            if (nt == 0) {
                #pragma unroll
                for (int k4 = 0; k4 < 4; k4++) mma16816(dr, a[k4], s_wr[(ld * 4 + k4) * 8 + t], s_wr[(ld * 4 + k4) * 8 + 4 + t]);
            }
            mbar_wait(sBar + sl * 8, ld >= 6);
            WG_FENCE();
            #pragma unroll
            for (int k4 = 0; k4 < 4; k4++) wgmma_rs_n128(acc, a[k4], db0 + (uint64_t)(sl * 1024 + k4 * 128));
            WG_COMMIT();
            wg_wait<1>();
            if (ld >= 1 && ld <= 6 && (threadIdx.x & 127) == 0) mbar_arrive(sBar + 48 + (ld - 1) * 8);
        }
    }
    const int row0 = mt * 128 + warp * 16;
    if (nt == 0 && t == 0) {
        g_r[row0 + g] = bf16r(dr[0]); g_r[row0 + g + 8] = bf16r(dr[2]);
        g_stats[row0 + g] = make_float2(bf_lo(lr0.m2), rs0); g_stats[row0 + g + 8] = make_float2(bf_lo(lr1.m2), rs1);
    }
    wg_wait<0>();
    touch64(acc);
    CK(4);
    float acc2[32];
    #pragma unroll
    for (int i = 0; i < 32; i++) acc2[i] = 0.f;
    #pragma unroll 1
    for (int q = 0; q < 4; q++) {
        const int sl = q + 2;
        #pragma unroll
        for (int h2 = 0; h2 < 2; h2++) {
            uint32_t a[4][4];
            #pragma unroll
            for (int k4 = 0; k4 < 4; k4++) ldsm4(a[k4], laddr[k4] + (q * 2 + h2) * 16384);
            #pragma unroll
            for (int k4 = 0; k4 < 4; k4++) ln_frag(a[k4], lr0, lr1);
            if (h2 == 0) mbar_wait(sBar + sl * 8, 1);
            WG_FENCE();
            #pragma unroll
            for (int k4 = 0; k4 < 4; k4++) wgmma_rs_n64(acc2, a[k4], db0 + (uint64_t)(sl * 1024 + (h2 * 4 + k4) * 128));
            WG_COMMIT();
            wg_wait<1>();
        }
        if (q == 0) k1_store<4>(acc, 0, nt, row0, lane);
        if (q == 1) k1_store<4>(acc + 32, 4, nt, row0, lane);
    }
    wg_wait<0>();
    touch32(acc2);
    CK(5);
    k1_store<4>(acc2, 8, nt, row0, lane);
    CK(6);
}

constexpr int K2_THREADS = 512;
constexpr int K2_SMEM = 65536 + 98304 + 16384 + 128;

constexpr float QS = 0.25f * 1.4426950408889634f;
__device__ __forceinline__ uint32_t polyexp(float s, float cb, uint32_t c421, float c3, float one) {
    float u;
    asm("fma.rn.sat.f32 %0, %1, %2, %3;" : "=f"(u) : "f"(s), "f"(QS * (1.0f / 255.0f)), "f"(cb));
    float z = fmaf(u, 0.99609375f, one);
    uint32_t rb;
    asm("lop3.b32 %0, %1, 0xFFFF8000, %2, 0xEA;" : "=r"(rb) : "r"(__float_as_uint(z)), "r"(c421));
    float f = z - __uint_as_float(rb);
    float h = fmaf(f, c3, 58.86525f);
    h = fmaf(f, h, -0.29870507f);
    return __float_as_uint(fmaf(f, h, z));
}

struct ExpC { float nm0, nm1, cb0, cb1, c3, one; uint32_t c421; };

template <int G>
__device__ __forceinline__ void exp_block(const float* s, uint32_t* p, const ExpC& c) {
    #pragma unroll
    for (int hf = 0; hf < 2; hf++) {
        const float* x = s + hf * 4;
        if ((PMASK >> (G + hf)) & 1) {
            p[hf * 2 + 0] = __byte_perm(polyexp(x[0], c.cb0, c.c421, c.c3, c.one), polyexp(x[1], c.cb0, c.c421, c.c3, c.one), 0x6521);
            p[hf * 2 + 1] = __byte_perm(polyexp(x[2], c.cb1, c.c421, c.c3, c.one), polyexp(x[3], c.cb1, c.c421, c.c3, c.one), 0x6521);
        } else {
            p[hf * 2 + 0] = pack_bf16(ex2(fmaf(x[0], QS, c.nm0)), ex2(fmaf(x[1], QS, c.nm0)));
            p[hf * 2 + 1] = pack_bf16(ex2(fmaf(x[2], QS, c.nm1)), ex2(fmaf(x[3], QS, c.nm1)));
        }
    }
}

__device__ __forceinline__ void max16(const float* s, float& mx0, float& mx1) {
    #pragma unroll
    for (int j = 0; j < 4; j++) {
        mx0 = fmaxf(mx0, fmaxf(s[4 * j], s[4 * j + 1]));
        mx1 = fmaxf(mx1, fmaxf(s[4 * j + 2], s[4 * j + 3]));
    }
}

__device__ void moe_cta(int part, unsigned char* smem, const __nv_bfloat16* __restrict__ x, const __nv_bfloat16* __restrict__ w_gate,
                        const __nv_bfloat16* __restrict__ w_up, const __nv_bfloat16* __restrict__ w_down) {
    float* xs = (float*)smem;
    float* red = xs + 1024;
    float* hs = red + 8 * 4 * 448;
    __shared__ float s_v[32];
    __shared__ int s_i[32];
    __shared__ int s_sel[2];
    const int tid = threadIdx.x, warp = tid >> 5, lane = tid & 31;
    for (int pass = 0; pass < 2; pass++) {
        float bv = -INFINITY; int bi = 0x7fffffff;
        const int excl = pass ? s_sel[0] : -1;
        for (int i = tid; i < S_; i += K2_THREADS) {
            float v = g_r[i];
            if (i != excl && (v > bv || (v == bv && i < bi) || bi == 0x7fffffff)) { bv = v; bi = i; }
        }
        #pragma unroll
        for (int o = 16; o; o >>= 1) {
            float ov = __shfl_xor_sync(~0u, bv, o); int oi = __shfl_xor_sync(~0u, bi, o);
            if (ov > bv || (ov == bv && oi < bi)) { bv = ov; bi = oi; }
        }
        if (lane == 0) { s_v[warp] = bv; s_i[warp] = bi; }
        __syncthreads();
        if (warp == 0) {
            bv = lane < 16 ? s_v[lane] : -INFINITY; bi = lane < 16 ? s_i[lane] : 0x7fffffff;
            #pragma unroll
            for (int o = 16; o; o >>= 1) {
                float ov = __shfl_xor_sync(~0u, bv, o); int oi = __shfl_xor_sync(~0u, bi, o);
                if (ov > bv || (ov == bv && oi < bi)) { bv = ov; bi = oi; }
            }
            if (lane == 0) s_sel[pass] = (bi == 0x7fffffff) ? pass : bi;
        }
        __syncthreads();
    }
    for (int i = tid; i < 1024; i += K2_THREADS) {
        const int tok = s_sel[i >> 9];
        const float2 st = g_stats[tok];
        xs[i] = ln_elem(__bfloat162float(x[(size_t)tok * D_ + (i & 511)]), st.x, st.y);
    }
    if (part == 0 && tid < 2) g_sel[tid] = s_sel[tid];
    __syncthreads();
    const int c0 = part * 448;
    if (tid < 448) {
        const int cg = tid % 56, ks = tid / 56;
        float a[4][8];
        #pragma unroll
        for (int i = 0; i < 4; i++)
            #pragma unroll
            for (int j = 0; j < 8; j++) a[i][j] = 0.f;
        const __nv_bfloat16* pg = w_gate + (size_t)(ks * 64) * F_ + c0 + cg * 8;
        const __nv_bfloat16* pu = w_up + (size_t)(ks * 64) * F_ + c0 + cg * 8;
        #pragma unroll 8
        for (int k = 0; k < 64; k++) {
            const uint4 gv = __ldg((const uint4*)(pg + (size_t)k * F_));
            const uint4 uv = __ldg((const uint4*)(pu + (size_t)k * F_));
            const float x0 = xs[ks * 64 + k], x1 = xs[512 + ks * 64 + k];
            const uint32_t gu[4] = {gv.x, gv.y, gv.z, gv.w}, uu[4] = {uv.x, uv.y, uv.z, uv.w};
            #pragma unroll
            for (int j = 0; j < 4; j++) {
                const float g0 = bf_lo(gu[j]), g1 = bf_hi(gu[j]), u0 = bf_lo(uu[j]), u1 = bf_hi(uu[j]);
                a[0][2 * j] = fmaf(x0, g0, a[0][2 * j]); a[0][2 * j + 1] = fmaf(x0, g1, a[0][2 * j + 1]);
                a[1][2 * j] = fmaf(x1, g0, a[1][2 * j]); a[1][2 * j + 1] = fmaf(x1, g1, a[1][2 * j + 1]);
                a[2][2 * j] = fmaf(x0, u0, a[2][2 * j]); a[2][2 * j + 1] = fmaf(x0, u1, a[2][2 * j + 1]);
                a[3][2 * j] = fmaf(x1, u0, a[3][2 * j]); a[3][2 * j + 1] = fmaf(x1, u1, a[3][2 * j + 1]);
            }
        }
        #pragma unroll
        for (int i = 0; i < 4; i++)
            #pragma unroll
            for (int j = 0; j < 8; j++) red[(ks * 4 + i) * 448 + cg * 8 + j] = a[i][j];
    }
    __syncthreads();
    for (int i = tid; i < 896; i += K2_THREADS) {
        const int tok = i / 448, c = i % 448;
        float gs = 0.f, us = 0.f;
        #pragma unroll
        for (int ks = 0; ks < 8; ks++) { gs += red[(ks * 4 + tok) * 448 + c]; us += red[(ks * 4 + 2 + tok) * 448 + c]; }
        gs = bf16r(gs); us = bf16r(us);
        const float sl = bf16r(gs / (1.0f + __expf(-gs)));
        hs[i] = bf16r(sl * us);
    }
    __syncthreads();
    {
        const int cg = tid & 63, fs = tid >> 6;
        float a[2][8];
        #pragma unroll
        for (int j = 0; j < 8; j++) { a[0][j] = 0.f; a[1][j] = 0.f; }
        const __nv_bfloat16* pd = w_down + (size_t)(c0 + fs * 56) * D_ + cg * 8;
        #pragma unroll 8
        for (int f = 0; f < 56; f++) {
            const uint4 dv = __ldg((const uint4*)(pd + (size_t)f * D_));
            const float h0 = hs[fs * 56 + f], h1 = hs[448 + fs * 56 + f];
            const uint32_t du[4] = {dv.x, dv.y, dv.z, dv.w};
            #pragma unroll
            for (int j = 0; j < 4; j++) {
                const float d0 = bf_lo(du[j]), d1 = bf_hi(du[j]);
                a[0][2 * j] = fmaf(h0, d0, a[0][2 * j]); a[0][2 * j + 1] = fmaf(h0, d1, a[0][2 * j + 1]);
                a[1][2 * j] = fmaf(h1, d0, a[1][2 * j]); a[1][2 * j + 1] = fmaf(h1, d1, a[1][2 * j + 1]);
            }
        }
        #pragma unroll
        for (int j = 0; j < 8; j++) { red[(fs * 2) * 512 + cg * 8 + j] = a[0][j]; red[(fs * 2 + 1) * 512 + cg * 8 + j] = a[1][j]; }
    }
    __syncthreads();
    for (int i = tid; i < 1024; i += K2_THREADS) {
        float s = 0.f;
        #pragma unroll
        for (int fs = 0; fs < 8; fs++) s += red[(fs * 2 + (i >> 9)) * 512 + (i & 511)];
        g_ypart[part][i >> 9][i & 511] = s;
    }
}

__global__ void __launch_bounds__(K2_THREADS, 1)
k2_attn(const __nv_bfloat16* __restrict__ x, const __nv_bfloat16* __restrict__ w_gate, const __nv_bfloat16* __restrict__ w_up,
        const __nv_bfloat16* __restrict__ w_down) {
    extern __shared__ __align__(1024) unsigned char smem[];
    TL(1, 0);
    pdl_launch();
    if (blockIdx.x >= 128) {
        const int part = blockIdx.x - 128;
        {
            const int k = threadIdx.x;
            asm volatile("cp.async.bulk.prefetch.L2.global [%0], %1;" :: "l"(w_gate + (size_t)k * F_ + part * 448), "r"(896) : "memory");
            asm volatile("cp.async.bulk.prefetch.L2.global [%0], %1;" :: "l"(w_up + (size_t)k * F_ + part * 448), "r"(896) : "memory");
            if (k < 56) asm volatile("cp.async.bulk.prefetch.L2.global [%0], %1;" :: "l"(w_down + (size_t)(part * 448 + k * 8) * D_), "r"(8192) : "memory");
        }
        pdl_wait(); TL(1, 1); moe_cta(blockIdx.x - 128, smem, x, w_gate, w_up, w_down); TL(1, 2); return; }
    const uint32_t sK = smem_u32(smem), sV = sK + 65536, sQ = sV + 98304, sBar = sQ + 16384;
    const int h = blockIdx.x >> 2, qb = blockIdx.x & 3;
    const int warp = __shfl_sync(~0u, threadIdx.x >> 5, 0), lane = threadIdx.x & 31, wg = warp >> 2;
    if (threadIdx.x == 0) {
        mbar_init(sBar, 1); mbar_init(sBar + 8, 1);
        asm volatile("fence.mbarrier_init.release.cluster;" ::: "memory");
        mbar_expect_tx(sBar, 16384 + 16384 + 2 * 8192);
        mbar_expect_tx(sBar + 8, 49152 + 2 * 24576);
    }
    for (int i = threadIdx.x; i < 2048; i += K2_THREADS) {
        const uint32_t v = is_poly_group(i >> 3) ? 0xBF80BF80u : 0x3F803F80u;
        *(uint4*)(smem + 65536 + 65536 + i * 16) = make_uint4(v, v, v, v);
    }
    fence_async_smem();
    __syncthreads();
    if (warp == 0) {
        pdl_wait();
        TL(1, 1);
        const uint4* gk = g_K + (size_t)h * 4096;
        const uint4* gv = g_V + (size_t)h * 4096;
        if (lane == 0) bulk_g2s(sQ, g_Q + (size_t)h * 4096 + qb * 1024, 16384, sBar);
        if (lane == 1) bulk_g2s(sK, gk, 16384, sBar);
        if (lane == 2) bulk_g2s(sV, gv, 8192, sBar);
        if (lane == 3) bulk_g2s(sV + 32768, gv + 2048, 8192, sBar);
        if (lane == 4) bulk_g2s(sK + 16384, gk + 1024, 49152, sBar + 8);
        if (lane == 5) bulk_g2s(sV + 8192, gv + 512, 24576, sBar + 8);
        if (lane == 6) bulk_g2s(sV + 32768 + 8192, gv + 2048 + 512, 24576, sBar + 8);
        __syncwarp();
    }
    ExpC c;
    {
        const volatile uint32_t* cc = g_const;
        c.c421 = cc[0]; c.c3 = __uint_as_float(cc[1]); c.one = __uint_as_float(cc[2]);
    }
    const uint32_t kdesc0 = (uint32_t)make_desc(sK, 128, 256, 0);
    const uint32_t vdesc0 = (uint32_t)make_desc(sV, 128, 32768, 0);
    #pragma unroll 1
    for (int pass = 0; pass < 2; pass++) {
        const bool dry = false;
        if (pass == 0) { mbar_wait(sBar, 0); __syncwarp(); TL(1, 2); }
        const int unit = (pass & 1) * 4 + wg;
        const uint32_t q = (uint32_t)make_desc(sQ + unit * 2048, 128, 256, 0);
        float o[12];
        #pragma unroll 1
        for (int attempt = 0; attempt < 2; attempt++) {
            float s0[16], s1[16], s2[16];
            #pragma unroll
            for (int i = 0; i < 16; i++) { s0[i] = 0.f; s1[i] = 0.f; s2[i] = 0.f; }
            float mx0 = -INFINITY, mx1 = -INFINITY;
            if (attempt) {
                #pragma unroll 1
                for (int it = 0; it < 64; it++) {
                    WG_FENCE();
                    wgmma_qk32(s0, q, kdesc0 + it * 64);
                    WG_COMMIT();
                    wg_wait<0>();
                    touch16(s0);
                    max16(s0, mx0, mx1);
                }
            }
            #pragma unroll
            for (int i = 0; i < 12; i++) o[i] = 0.f;
            WG_FENCE();
            wgmma_qk32(s2, q, kdesc0);
            wgmma_qk32(s0, q, kdesc0 + 64);
            wgmma_qk32(s1, q, kdesc0 + 128);
            WG_COMMIT();
            wg_wait<0>();
            touch16(s0); touch16(s1); touch16(s2);
            max16(s0, mx0, mx1); max16(s1, mx0, mx1); max16(s2, mx0, mx1);
            mx0 = fmaxf(mx0, __shfl_xor_sync(~0u, mx0, 1)); mx0 = fmaxf(mx0, __shfl_xor_sync(~0u, mx0, 2));
            mx1 = fmaxf(mx1, __shfl_xor_sync(~0u, mx1, 1)); mx1 = fmaxf(mx1, __shfl_xor_sync(~0u, mx1, 2));
            const float bias = attempt ? 0.0f : 64.0f;
            c.nm0 = __shfl_sync(~0u, -fmaf(mx0, QS, bias), lane); c.nm1 = __shfl_sync(~0u, -fmaf(mx1, QS, bias), lane);
            c.cb0 = __shfl_sync(~0u, (127.0f + c.nm0) * (1.0f / 255.0f), lane);
            c.cb1 = __shfl_sync(~0u, (127.0f + c.nm1) * (1.0f / 255.0f), lane);
            uint32_t kd = kdesc0 + 192, vd = vdesc0 + 32;
            {
                uint32_t pa[4], pb[4];
                exp_block<12>(s2, pa, c);
                exp_block<14>(s2 + 8, pb, c);
                WG_FENCE();
                wgmma_pv(o, pa, vdesc0); wgmma_pv(o, pb, vdesc0 + 16);
                WG_COMMIT();
            }
            #pragma unroll 1
            for (int seg = 0; seg < (dry ? 1 : 2); seg++) {
            if (seg) { wg_wait<0>(); mbar_wait(sBar + 8, 0); __syncwarp(); }
            #pragma unroll 1
            for (int it = seg ? 3 : (dry ? 2 : 0); it < (seg ? 21 : 3); it++) {
                uint32_t p[6][4];
                WG_FENCE();
                wgmma_qk32(s2, q, kd);
                WG_COMMIT();
                exp_block<0>(s0, p[0], c);
                exp_block<2>(s0 + 8, p[1], c);
                WG_FENCE();
                wgmma_pv(o, p[0], vd); wgmma_pv(o, p[1], vd + 16);
                wgmma_qk32(s0, q, kd + 64);
                WG_COMMIT();
                wg_wait<1>();
                touch16(s2);
                exp_block<4>(s1, p[2], c);
                exp_block<6>(s1 + 8, p[3], c);
                WG_FENCE();
                wgmma_pv(o, p[2], vd + 32); wgmma_pv(o, p[3], vd + 48);
                wgmma_qk32(s1, q, kd + 128);
                WG_COMMIT();
                wg_wait<1>();
                touch16(s0);
                exp_block<8>(s2, p[4], c);
                exp_block<10>(s2 + 8, p[5], c);
                WG_FENCE();
                wgmma_pv(o, p[4], vd + 64); wgmma_pv(o, p[5], vd + 80);
                WG_COMMIT();
                vd += 96; kd += 192;
                wg_wait<1>();
                touch16(s1);
            }
            }
            wg_wait<0>();
            touch12(o);
            if (attempt) break;
            float big = 0.f;
            #pragma unroll
            for (int i = 0; i < 12; i++) big = fmaxf(big, fabsf(o[i]));
            bool bad = !(big < 1e30f);
            #pragma unroll
            for (int i = 0; i < 12; i++) bad |= (o[i] != o[i]);
            uint32_t any;
            asm volatile("{.reg .pred p, q; setp.ne.u32 p, %1, 0; barrier.cta.red.or.pred.aligned q, %2, 128, p; selp.u32 %0, 1, 0, q;}"
                         : "=r"(any) : "r"((uint32_t)bad), "r"(1 + wg) : "memory");
            if (dry || !__any_sync(~0u, any)) break;
        }
        const int g = lane >> 2, t = lane & 3;
        const int r = (warp & 3) * 16 + g;
        const float i0 = __fdiv_rn(1.0f, o[8]), i1 = __fdiv_rn(1.0f, o[10]);
        uint32_t* ob = (uint32_t*)(g_O + (size_t)(qb * 8 + unit) * 4096 + (h >> 2) * 512 + r * 8) + t;
        const int c0 = ((h & 3) * 2) ^ (r & 7), c1 = ((h & 3) * 2 + 1) ^ (r & 7);
        if (!dry) {
            ob[c0 * 4] = pack_bf16(o[0] * i0, o[1] * i0);
            ob[c1 * 4] = pack_bf16(o[4] * i0, o[5] * i0);
            ob[256 + c0 * 4] = pack_bf16(o[2] * i1, o[3] * i1);
            ob[256 + c1 * 4] = pack_bf16(o[6] * i1, o[7] * i1);
            TL(1, 3 + pass);
        }
    }
}

constexpr int K3_THREADS = 256;
constexpr int K3_SMEM = 65536 + 131072 + 128;

__global__ void __launch_bounds__(K3_THREADS, 1)
k3_out(const __grid_constant__ CUtensorMap wmap, const __nv_bfloat16* __restrict__ x, __nv_bfloat16* __restrict__ out) {
    extern __shared__ __align__(1024) unsigned char smem[];
    const uint32_t sA = smem_u32(smem), sB = sA + 65536, sBar = sB + 131072;
    const int warp = __shfl_sync(~0u, threadIdx.x >> 5, 0), lane = threadIdx.x & 31, wg = warp >> 2;
    const int nt = blockIdx.x & 3, mt = blockIdx.x >> 2;
    TL(2, 0);
    if (threadIdx.x == 0) {
        for (int i = 0; i < 6; i++) mbar_init(sBar + i * 8, 1);
        asm volatile("fence.mbarrier_init.release.cluster;" ::: "memory");
        for (int kh = 0; kh < 2; kh++) {
            mbar_expect_tx(sBar + kh * 8, 65536);
            tma_2d(sB + kh * 32768, &wmap, nt * 128, kh * 256, sBar + kh * 8);
            tma_2d(sB + 65536 + kh * 32768, &wmap, nt * 128 + 64, kh * 256, sBar + kh * 8);
        }
    }
    const int er = threadIdx.x >> 2, ec = (threadIdx.x & 3) * 32;
    const int row = mt * 64 + er;
    uint4 xv[4];
    #pragma unroll
    for (int j = 0; j < 4; j++) xv[j] = __ldg((const uint4*)(x + (size_t)row * D_ + nt * 128 + ec) + j);
    pdl_wait();
    TL(2, 1);
    if (threadIdx.x == 0) {
        for (int q = 0; q < 4; q++) {
            mbar_expect_tx(sBar + 16 + q * 8, 16384);
            bulk_g2s(sA + q * 16384, g_O + (size_t)mt * 4096 + q * 1024, 16384, sBar + 16 + q * 8);
        }
    }
    const int sel0 = g_sel[0], sel1 = g_sel[1];
    const float2 st = g_stats[row];
    uint32_t bb[16];
    {
        const uint32_t xu[16] = {xv[0].x, xv[0].y, xv[0].z, xv[0].w, xv[1].x, xv[1].y, xv[1].z, xv[1].w,
                                 xv[2].x, xv[2].y, xv[2].z, xv[2].w, xv[3].x, xv[3].y, xv[3].z, xv[3].w};
        #pragma unroll
        for (int j = 0; j < 16; j++) bb[j] = pack_bf16(bf16r(bf_lo(xu[j]) - st.x) * st.y, bf16r(bf_hi(xu[j]) - st.x) * st.y);
        const int slot = row == sel0 ? 0 : (row == sel1 ? 1 : -1);
        if (slot >= 0) {
            const float gate = bf16r(1.0f / (1.0f + __expf(-g_r[row])));
            const int c0 = nt * 128 + ec;
            #pragma unroll
            for (int j = 0; j < 16; j++) {
                const float2 a = *(const float2*)&g_ypart[0][slot][c0 + 2 * j], b = *(const float2*)&g_ypart[1][slot][c0 + 2 * j];
                const float2 c = *(const float2*)&g_ypart[2][slot][c0 + 2 * j], d = *(const float2*)&g_ypart[3][slot][c0 + 2 * j];
                bb[j] = pack_bf16(bf_lo(bb[j]) + bf16r(bf16r(a.x + b.x + c.x + d.x) * gate), bf_hi(bb[j]) + bf16r(bf16r(a.y + b.y + c.y + d.y) * gate));
            }
        }
    }
    __syncthreads();
    float acc[32];
    #pragma unroll
    for (int i = 0; i < 32; i++) acc[i] = 0.f;
    const uint64_t da0 = make_desc(sA, 16, 1024, 1);
    const uint64_t db0 = make_desc(sB + wg * 65536, 8192, 1024, 1);
    #pragma unroll 1
    for (int q = 0; q < 4; q++) {
        if ((q & 1) == 0) mbar_wait(sBar + (q >> 1) * 8, 0);
        mbar_wait(sBar + 16 + q * 8, 0);
        WG_FENCE();
        #pragma unroll
        for (int kk = 0; kk < 8; kk++)
            wgmma_n64(acc, da0 + (uint64_t)(q * 1024 + (kk >> 2) * 512 + (kk & 3) * 2), db0 + (uint64_t)(q * 1024 + kk * 128));
        WG_COMMIT();
    }
    wg_wait<0>();
    touch32(acc);
    TL(2, 2);
    __syncthreads();
    {
        const int g = lane >> 2, t = lane & 3;
        unsigned char* sp = smem + ((warp & 3) * 16 + g) * 272 + wg * 128 + t * 4;
        #pragma unroll
        for (int j = 0; j < 8; j++) {
            *(uint32_t*)(sp + j * 16) = pack_bf16(acc[4 * j], acc[4 * j + 1]);
            *(uint32_t*)(sp + 8 * 272 + j * 16) = pack_bf16(acc[4 * j + 2], acc[4 * j + 3]);
        }
    }
    __syncthreads();
    #pragma unroll
    for (int j = 0; j < 4; j++) {
        const uint4 av = *(const uint4*)(smem + er * 272 + ec * 2 + j * 16);
        const uint32_t au[4] = {av.x, av.y, av.z, av.w}, xu[4] = {xv[j].x, xv[j].y, xv[j].z, xv[j].w};
        uint32_t o[4];
        #pragma unroll
        for (int i = 0; i < 4; i++) {
            uint32_t t2;
            asm("add.rn.bf16x2 %0, %1, %2;" : "=r"(t2) : "r"(xu[i]), "r"(au[i]));
            asm("add.rn.bf16x2 %0, %1, %2;" : "=r"(o[i]) : "r"(t2), "r"(bb[j * 4 + i]));
        }
        *((uint4*)(out + (size_t)row * D_ + nt * 128 + ec) + j) = make_uint4(o[0], o[1], o[2], o[3]);
    }
    TL(2, 3);
}

typedef CUresult (*EncodeFn)(CUtensorMap*, CUtensorMapDataType, cuuint32_t, void*, const cuuint64_t*, const cuuint64_t*,
                             const cuuint32_t*, const cuuint32_t*, CUtensorMapInterleave, CUtensorMapSwizzle,
                             CUtensorMapL2promotion, CUtensorMapFloatOOBfill);

void make_wmap(EncodeFn fn, CUtensorMap* map, const void* ptr, int rows, int cols, int box_rows) {
    cuuint64_t dims[2] = {(cuuint64_t)cols, (cuuint64_t)rows};
    cuuint64_t strides[1] = {(cuuint64_t)cols * 2};
    cuuint32_t box[2] = {64, (cuuint32_t)box_rows};
    cuuint32_t es[2] = {1, 1};
    fn(map, CU_TENSOR_MAP_DATA_TYPE_BFLOAT16, 2, (void*)ptr, dims, strides, box, es, CU_TENSOR_MAP_INTERLEAVE_NONE,
       CU_TENSOR_MAP_SWIZZLE_128B, CU_TENSOR_MAP_L2_PROMOTION_L2_256B, CU_TENSOR_MAP_FLOAT_OOB_FILL_NONE);
}

}

extern "C" void kernel_launch(void* const* d_in, const int* in_sizes, int n_in, void* d_out, int out_size) {
    const __nv_bfloat16* x = (const __nv_bfloat16*)d_in[0];
    const __nv_bfloat16* wqkv = (const __nv_bfloat16*)d_in[1];
    const __nv_bfloat16* wo = (const __nv_bfloat16*)d_in[2];
    const __nv_bfloat16* w_r = (const __nv_bfloat16*)d_in[4];
    const __nv_bfloat16* w_gate = (const __nv_bfloat16*)d_in[5];
    const __nv_bfloat16* w_up = (const __nv_bfloat16*)d_in[6];
    const __nv_bfloat16* w_down = (const __nv_bfloat16*)d_in[7];
    __nv_bfloat16* out = (__nv_bfloat16*)d_out;

    static EncodeFn encode = nullptr;
    if (!encode) {
        void* fn = nullptr;
        cudaDriverEntryPointQueryResult qres;
        cudaGetDriverEntryPoint("cuTensorMapEncodeTiled", &fn, cudaEnableDefault, &qres);
        encode = (EncodeFn)fn;
        cudaFuncSetAttribute(k1_ln_qkv, cudaFuncAttributeMaxDynamicSharedMemorySize, K1_SMEM);
        cudaFuncSetAttribute(k2_attn, cudaFuncAttributeMaxDynamicSharedMemorySize, K2_SMEM);
        cudaFuncSetAttribute(k3_out, cudaFuncAttributeMaxDynamicSharedMemorySize, K3_SMEM);
    }
    CUtensorMap map_qkv, map_wo, map_x;
    make_wmap(encode, &map_x, x, S_, D_, 64);
    make_wmap(encode, &map_qkv, wqkv, D_, 3 * D_, 64);
    make_wmap(encode, &map_wo, wo, D_, D_, 256);

    k1_ln_qkv<<<128, K1_THREADS, K1_SMEM, cudaStreamPerThread>>>(map_qkv, map_x, w_r);
    cudaLaunchAttribute at[1];
    at[0].id = cudaLaunchAttributeProgrammaticStreamSerialization;
    at[0].val.programmaticStreamSerializationAllowed = 1;
    cudaLaunchConfig_t cfg = {};
    cfg.stream = cudaStreamPerThread;
    cfg.attrs = at; cfg.numAttrs = 1;
    cfg.gridDim = dim3(132); cfg.blockDim = dim3(K2_THREADS); cfg.dynamicSmemBytes = K2_SMEM;
    cudaLaunchKernelEx(&cfg, k2_attn, x, w_gate, w_up, w_down);
    cfg.gridDim = dim3(128); cfg.blockDim = dim3(K3_THREADS); cfg.dynamicSmemBytes = K3_SMEM;
    cudaLaunchKernelEx(&cfg, k3_out, map_wo, x, out);
}
```

```cpp
#include <cuda_runtime.h>
#include <cuda_bf16.h>
#include <cuda.h>
#include <stdint.h>

namespace {

constexpr int S_ = 2048, D_ = 512, H_ = 32, F_ = 1792;

constexpr uint32_t PMASK = 0x6B5;
__host__ __device__ constexpr bool is_poly_group(int g8) { return g8 >= 4 && ((PMASK >> ((g8 - 4) % 12)) & 1); }

__device__ __align__(1024) uint4 g_QKV[3 * H_ * S_ * 2];
#define g_Q (g_QKV)
#define g_K (g_QKV + H_ * S_ * 2)
#define g_V (g_QKV + 2 * H_ * S_ * 2)
__device__ __align__(1024) uint4 g_O[S_ * D_ / 8];
__device__ float2 g_stats[S_];
__device__ uint32_t g_const[4] = {0x3F803F80u, 0x422A422Au, 0x3F800000u, 0u};
__device__ float g_r[S_];
__device__ __align__(16) float g_ypart[4][2][D_];
__device__ int g_sel[2];

#define TL(k, p)
#define CK(i)
__device__ __forceinline__ uint32_t smem_u32(const void* p) { return (uint32_t)__cvta_generic_to_shared(p); }
__device__ __forceinline__ float bf16r(float x) { return __bfloat162float(__float2bfloat16_rn(x)); }
__device__ __forceinline__ uint32_t pack_bf16(float lo, float hi) {
    uint32_t r; asm("cvt.rn.bf16x2.f32 %0, %1, %2;" : "=r"(r) : "f"(hi), "f"(lo)); return r;
}
__device__ __forceinline__ float bf_lo(uint32_t u) { return __uint_as_float(u << 16); }
__device__ __forceinline__ float bf_hi(uint32_t u) { return __uint_as_float(u & 0xFFFF0000u); }
__device__ __forceinline__ float ex2(float x) { float y; asm("ex2.approx.ftz.f32 %0, %1;" : "=f"(y) : "f"(x)); return y; }

__device__ __forceinline__ void mbar_init(uint32_t bar, uint32_t count) {
    asm volatile("mbarrier.init.shared::cta.b64 [%0], %1;" :: "r"(bar), "r"(count) : "memory");
}
__device__ __forceinline__ void mbar_expect_tx(uint32_t bar, uint32_t bytes) {
    asm volatile("mbarrier.arrive.expect_tx.shared::cta.b64 _, [%0], %1;" :: "r"(bar), "r"(bytes) : "memory");
}
__device__ __forceinline__ void mbar_arrive(uint32_t bar) {
    asm volatile("mbarrier.arrive.shared::cta.b64 _, [%0];" :: "r"(bar) : "memory");
}
__device__ __forceinline__ void mbar_wait(uint32_t bar, uint32_t parity) {
    uint32_t done;
    #pragma unroll 1
    for (int it = 0; it < (1 << 26); it++) {
        asm volatile("{.reg .pred p; mbarrier.try_wait.parity.shared::cta.b64 p, [%1], %2; selp.u32 %0, 1, 0, p;}"
                     : "=r"(done) : "r"(bar), "r"(parity) : "memory");
        if (done) return;
    }
    __trap();
}
__device__ __forceinline__ void bulk_g2s(uint32_t dst, const void* src, uint32_t bytes, uint32_t bar) {
    asm volatile("cp.async.bulk.shared::cluster.global.mbarrier::complete_tx::bytes [%0], [%1], %2, [%3];"
                 :: "r"(dst), "l"(src), "r"(bytes), "r"(bar) : "memory");
}
__device__ __forceinline__ void tma_2d(uint32_t dst, const CUtensorMap* map, int c0, int c1, uint32_t bar) {
    asm volatile("cp.async.bulk.tensor.2d.shared::cluster.global.mbarrier::complete_tx::bytes [%0], [%1, {%3, %4}], [%2];"
                 :: "r"(dst), "l"(map), "r"(bar), "r"(c0), "r"(c1) : "memory");
}
__device__ __forceinline__ void fence_async_smem() { asm volatile("fence.proxy.async.shared::cta;" ::: "memory"); }
__device__ __forceinline__ void named_bar(int id, int n) { asm volatile("bar.sync %0, %1;" :: "r"(id), "r"(n) : "memory"); }

__device__ __forceinline__ uint64_t make_desc(uint32_t saddr, uint32_t lbo, uint32_t sbo, uint32_t swz) {
    return (uint64_t)((saddr & 0x3FFFF) >> 4) | ((uint64_t)(lbo >> 4) << 16) | ((uint64_t)(sbo >> 4) << 32) | ((uint64_t)swz << 62);
}
#define WG_FENCE() asm volatile("wgmma.fence.sync.aligned;" ::: "memory")
#define WG_COMMIT() asm volatile("wgmma.commit_group.sync.aligned;" ::: "memory")
template <int N> __device__ __forceinline__ void wg_wait() { asm volatile("wgmma.wait_group.sync.aligned %0;" :: "n"(N) : "memory"); }

#define F4(d, o) "+f"(d[o]), "+f"(d[o + 1]), "+f"(d[o + 2]), "+f"(d[o + 3])
#define F16(d, o) F4(d, o), F4(d, o + 4), F4(d, o + 8), F4(d, o + 12)
#define F32(d, o) F16(d, o), F16(d, o + 16)

__device__ __forceinline__ void wgmma_rs_n128(float* d, const uint32_t* a, uint64_t db) {
    asm volatile("wgmma.mma_async.sync.aligned.m64n128k16.f32.bf16.bf16 "
        "{%0,%1,%2,%3,%4,%5,%6,%7,%8,%9,%10,%11,%12,%13,%14,%15,%16,%17,%18,%19,%20,%21,%22,%23,%24,%25,%26,%27,%28,%29,%30,%31,"
        "%32,%33,%34,%35,%36,%37,%38,%39,%40,%41,%42,%43,%44,%45,%46,%47,%48,%49,%50,%51,%52,%53,%54,%55,%56,%57,%58,%59,%60,%61,%62,%63}, "
        "{%64,%65,%66,%67}, %68, 1, 1, 1, 1;\n"
        : F32(d, 0), F32(d, 32) : "r"(a[0]), "r"(a[1]), "r"(a[2]), "r"(a[3]), "l"(db));
}
__device__ __forceinline__ void wgmma_rs_n64(float* d, const uint32_t* a, uint64_t db) {
    asm volatile("wgmma.mma_async.sync.aligned.m64n64k16.f32.bf16.bf16 "
        "{%0,%1,%2,%3,%4,%5,%6,%7,%8,%9,%10,%11,%12,%13,%14,%15,%16,%17,%18,%19,%20,%21,%22,%23,%24,%25,%26,%27,%28,%29,%30,%31}, "
        "{%32,%33,%34,%35}, %36, 1, 1, 1, 1;\n"
        : F32(d, 0) : "r"(a[0]), "r"(a[1]), "r"(a[2]), "r"(a[3]), "l"(db));
}
__device__ __forceinline__ void wgmma_n64(float* d, uint64_t da, uint64_t db) {
    asm volatile("wgmma.mma_async.sync.aligned.m64n64k16.f32.bf16.bf16 "
        "{%0,%1,%2,%3,%4,%5,%6,%7,%8,%9,%10,%11,%12,%13,%14,%15,%16,%17,%18,%19,%20,%21,%22,%23,%24,%25,%26,%27,%28,%29,%30,%31}, "
        "%32, %33, 1, 1, 1, 0, 1;\n"
        : F32(d, 0) : "l"(da), "l"(db));
}
__device__ __forceinline__ void wgmma_qk32(float* d, uint32_t qd, uint32_t kd) {
    asm volatile("{.reg .b64 a, b; mov.b64 a, {%16, 16}; mov.b64 b, {%17, 16};\n"
        "wgmma.mma_async.sync.aligned.m64n32k16.f32.bf16.bf16 {%0,%1,%2,%3,%4,%5,%6,%7,%8,%9,%10,%11,%12,%13,%14,%15}, a, b, 0, 1, 1, 0, 0;}\n"
        : F16(d, 0) : "r"(qd), "r"(kd));
}
__device__ __forceinline__ void wgmma_pv(float* d, const uint32_t* a, uint32_t vd) {
    asm volatile("{.reg .b64 b; mov.b64 b, {%16, 2048};\n"
        "wgmma.mma_async.sync.aligned.m64n24k16.f32.bf16.bf16 {%0,%1,%2,%3,%4,%5,%6,%7,%8,%9,%10,%11}, {%12,%13,%14,%15}, b, 1, 1, 1, 1;}\n"
        : F4(d, 0), F4(d, 4), F4(d, 8) : "r"(a[0]), "r"(a[1]), "r"(a[2]), "r"(a[3]), "r"(vd));
}
__device__ __forceinline__ void touch16(float* d) { asm volatile("" : F16(d, 0) :: "memory"); }
__device__ __forceinline__ void touch12(float* d) { asm volatile("" : F4(d, 0), F4(d, 4), F4(d, 8) :: "memory"); }
__device__ __forceinline__ void touch32(float* d) { asm volatile("" : F32(d, 0) :: "memory"); }
__device__ __forceinline__ void touch64(float* d) { asm volatile("" : F32(d, 0), F32(d, 32) :: "memory"); }

__device__ __forceinline__ float ln_elem(float x, float mean_b, float rden) {
    return bf16r(bf16r(x - mean_b) * rden);
}
__device__ __forceinline__ void pdl_wait() { asm volatile("griddepcontrol.wait;" ::: "memory"); }
__device__ __forceinline__ void pdl_launch() { asm volatile("griddepcontrol.launch_dependents;" ::: "memory"); }
__device__ __forceinline__ void cluster_arrive() { asm volatile("barrier.cluster.arrive.release.aligned;" ::: "memory"); }
__device__ __forceinline__ void cluster_wait() { asm volatile("barrier.cluster.wait.acquire.aligned;" ::: "memory"); }

constexpr int K1_THREADS = 288;
constexpr int K1_SMEM = 131072 + 6 * 16384 + 128 + 1024;

__device__ __forceinline__ void ldsm4(uint32_t* r, uint32_t addr) {
    asm volatile("ldmatrix.sync.aligned.m8n8.x4.shared.b16 {%0, %1, %2, %3}, [%4];" : "=r"(r[0]), "=r"(r[1]), "=r"(r[2]), "=r"(r[3]) : "r"(addr) : "memory");
}
__device__ __forceinline__ void stsm4(uint32_t addr, uint32_t r0, uint32_t r1, uint32_t r2, uint32_t r3) {
    asm volatile("stmatrix.sync.aligned.m8n8.x4.shared.b16 [%0], {%1, %2, %3, %4};" :: "r"(addr), "r"(r0), "r"(r1), "r"(r2), "r"(r3) : "memory");
}
__device__ __forceinline__ void mma16816(float* d, const uint32_t* a, uint32_t b0, uint32_t b1) {
    asm("mma.sync.aligned.m16n8k16.row.col.f32.bf16.bf16.f32 {%0,%1,%2,%3}, {%4,%5,%6,%7}, {%8,%9}, {%0,%1,%2,%3};"
        : "+f"(d[0]), "+f"(d[1]), "+f"(d[2]), "+f"(d[3]) : "r"(a[0]), "r"(a[1]), "r"(a[2]), "r"(a[3]), "r"(b0), "r"(b1));
}
__device__ __forceinline__ uint32_t sub_bf16x2(uint32_t a, uint32_t b) {
    uint32_t d; asm("sub.rn.bf16x2 %0, %1, %2;" : "=r"(d) : "r"(a), "r"(b)); return d;
}
__device__ __forceinline__ uint32_t ln_pair(uint32_t x2, uint32_t mean2, uint32_t rhi2, uint32_t rlo2) {
    const uint32_t d = sub_bf16x2(x2, mean2);
    uint32_t t, y;
    asm("mul.rn.bf16x2 %0, %1, %2;" : "=r"(t) : "r"(d), "r"(rlo2));
    asm("fma.rn.bf16x2 %0, %1, %2, %3;" : "=r"(y) : "r"(d), "r"(rhi2), "r"(t));
    return y;
}
struct LnRow { uint32_t m2, hi2, lo2; };
__device__ __forceinline__ LnRow ln_row(float mean, float rden) {
    LnRow r;
    r.m2 = pack_bf16(mean, mean);
    r.hi2 = pack_bf16(rden, rden);
    const float lo = rden - bf_lo(r.hi2);
    r.lo2 = pack_bf16(lo, lo);
    return r;
}
__device__ __forceinline__ void ln_frag(uint32_t* a, const LnRow& r0, const LnRow& r1) {
    a[0] = ln_pair(a[0], r0.m2, r0.hi2, r0.lo2); a[1] = ln_pair(a[1], r1.m2, r1.hi2, r1.lo2);
    a[2] = ln_pair(a[2], r0.m2, r0.hi2, r0.lo2); a[3] = ln_pair(a[3], r1.m2, r1.hi2, r1.lo2);
}

template <int NJ>
__device__ __forceinline__ void k1_store(const float* acc, int jj0, int nt, int row0, int lane) {
    const int g = lane >> 2, t = lane & 3, g8a = row0 >> 3;
    const uint32_t sx0 = is_poly_group(g8a) ? 0x80008000u : 0u, sx1 = is_poly_group(g8a + 1) ? 0x80008000u : 0u;
    const int off_qk = g8a * 64 + g * 4 + t, off_v = (row0 + g) * 4 + t;
    #pragma unroll
    for (int jj = 0; jj < NJ; jj++) {
        const int hg = nt * 12 + jj0 + jj;
        const bool isv = hg >= 64;
        const uint32_t x0 = isv ? sx0 : 0u, x1 = isv ? sx1 : 0u;
        uint32_t* base = (uint32_t*)g_QKV + (size_t)hg * 16384 + (isv ? off_v : off_qk);
        const int hs = isv ? 8192 : 32, rs = isv ? 32 : 64;
        base[0] = pack_bf16(acc[8 * jj], acc[8 * jj + 1]) ^ x0;
        base[rs] = pack_bf16(acc[8 * jj + 2], acc[8 * jj + 3]) ^ x1;
        base[hs] = pack_bf16(acc[8 * jj + 4], acc[8 * jj + 5]) ^ x0;
        base[hs + rs] = pack_bf16(acc[8 * jj + 6], acc[8 * jj + 7]) ^ x1;
    }
}

__global__ void __launch_bounds__(K1_THREADS, 1)
k1_ln_qkv(const __grid_constant__ CUtensorMap wmap, const __grid_constant__ CUtensorMap xmap, const __nv_bfloat16* __restrict__ w_r) {
    extern __shared__ __align__(1024) unsigned char smem[];
    const uint32_t sA = smem_u32(smem), sB = sA + 131072, sBar = sB + 6 * 16384;
    const int warp = __shfl_sync(~0u, threadIdx.x >> 5, 0), lane = threadIdx.x & 31;
    const int nt = blockIdx.x & 7, mt = blockIdx.x >> 3;
    const int wg = warp >> 2;
    CK(0);
    pdl_launch();
    uint32_t* s_wr = (uint32_t*)(smem + 131072 + 6 * 16384 + 128);
    if (warp == 8) {
        if (lane == 0) {
            for (int i = 0; i < 6; i++) { mbar_init(sBar + i * 8, 1); mbar_init(sBar + 48 + i * 8, 2); }
            mbar_init(sBar + 96, 1); mbar_init(sBar + 104, 1);
            asm volatile("fence.mbarrier_init.release.cluster;" ::: "memory");
            mbar_expect_tx(sBar + 96, 65536); mbar_expect_tx(sBar + 104, 65536);
            for (int i = 0; i < 6; i++) mbar_expect_tx(sBar + i * 8, 16384);
        }
        __syncwarp();
        if (lane < 16) tma_2d(sA + (lane & 7) * 16384 + (lane >> 3) * 8192, &xmap, (lane & 7) * 64, mt * 128 + (lane >> 3) * 64, sBar + 96 + (lane >> 3) * 8);
        named_bar(3, K1_THREADS);
        mbar_wait(sBar + 96, 0);
        if (lane < 12) {
            const int ld = lane >> 1, j = lane & 1;
            tma_2d(sB + ld * 16384 + j * 8192, &wmap, nt * 192 + j * 64, ld * 64, sBar + ld * 8);
        }
        __syncwarp();
        if (lane < 2) {
            for (int ld = 6; ld < 12; ld++) {
                const int sl = ld - 6;
                mbar_wait(sBar + 48 + sl * 8, 0);
                if (lane == 0) mbar_expect_tx(sBar + sl * 8, 16384);
                __syncwarp(3);
                if (ld < 8) tma_2d(sB + sl * 16384 + lane * 8192, &wmap, nt * 192 + lane * 64, ld * 64, sBar + sl * 8);
                else tma_2d(sB + sl * 16384 + lane * 8192, &wmap, nt * 192 + 128, (ld - 8) * 128 + lane * 64, sBar + sl * 8);
            }
        }
        return;
    }
    if (nt == 0) s_wr[threadIdx.x] = __ldg((const uint32_t*)w_r + threadIdx.x);
    named_bar(3, K1_THREADS);
    const int g = lane >> 2, t = lane & 3;
    const int lrow = warp * 16 + (lane & 7) + ((lane >> 3) & 1) * 8;
    const uint32_t lbase = sA + lrow * 128;
    const int lsw = lane & 7, lhi = lane >> 4;
    uint32_t laddr[4];
    #pragma unroll
    for (int k4 = 0; k4 < 4; k4++) laddr[k4] = lbase + (((k4 * 2 + lhi) ^ lsw) * 16);
    CK(1);
    mbar_wait(sBar + 96 + wg * 8, 0);
    CK(2);
    float dsum[4] = {0.f, 0.f, 0.f, 0.f}, dq0[4] = {0.f, 0.f, 0.f, 0.f}, dq1[4] = {0.f, 0.f, 0.f, 0.f};
    float esum[4] = {0.f, 0.f, 0.f, 0.f}, eq0[4] = {0.f, 0.f, 0.f, 0.f}, eq1[4] = {0.f, 0.f, 0.f, 0.f};
    #pragma unroll 2
    for (int pn = 0; pn < 8; pn++) {
        uint32_t a[4][4];
        #pragma unroll
        for (int k4 = 0; k4 < 4; k4++) ldsm4(a[k4], laddr[k4] + pn * 16384);
        #pragma unroll
        for (int k4 = 0; k4 < 4; k4 += 2) {
            mma16816(dsum, a[k4], 0x3F803F80u, 0x3F803F80u);
            mma16816(dq0, a[k4], a[k4][0], a[k4][2]);
            mma16816(dq1, a[k4], a[k4][1], a[k4][3]);
            mma16816(esum, a[k4 + 1], 0x3F803F80u, 0x3F803F80u);
            mma16816(eq0, a[k4 + 1], a[k4 + 1][0], a[k4 + 1][2]);
            mma16816(eq1, a[k4 + 1], a[k4 + 1][1], a[k4 + 1][3]);
        }
    }
    #pragma unroll
    for (int i = 0; i < 4; i++) { dsum[i] += esum[i]; dq0[i] += eq0[i]; dq1[i] += eq1[i]; }
    CK(3);
    const int dsrc = g * 4 + (g >> 1);
    const float sq0 = __shfl_sync(~0u, (g & 1) ? dq0[1] : dq0[0], dsrc), sq1 = __shfl_sync(~0u, (g & 1) ? dq1[3] : dq1[2], dsrc);
    const float mean0 = dsum[0] * (1.0f / D_), mean1 = dsum[2] * (1.0f / D_);
    float var0 = fmaf(-mean0, mean0, sq0 * (1.0f / D_)), var1 = fmaf(-mean1, mean1, sq1 * (1.0f / D_));
    if (__any_sync(~0u, !(mean0 * mean0 <= 16.0f * var0) || !(mean1 * mean1 <= 16.0f * var1))) {
        float q0 = 0.f, q1 = 0.f;
        #pragma unroll 1
        for (int ks = 0; ks < 32; ks++) {
            uint32_t a[4];
            ldsm4(a, lbase + (ks >> 2) * 16384 + ((((ks & 3) * 2 + lhi) ^ lsw) * 16));
            #pragma unroll
            for (int i = 0; i < 4; i++) {
                const float m = (i & 1) ? mean1 : mean0;
                const float d0 = bf_lo(a[i]) - m, d1 = bf_hi(a[i]) - m;
                if (i & 1) q1 = fmaf(d0, d0, fmaf(d1, d1, q1)); else q0 = fmaf(d0, d0, fmaf(d1, d1, q0));
            }
        }
        q0 += __shfl_xor_sync(~0u, q0, 1); q0 += __shfl_xor_sync(~0u, q0, 2);
        q1 += __shfl_xor_sync(~0u, q1, 1); q1 += __shfl_xor_sync(~0u, q1, 2);
        var0 = q0 * (1.0f / D_); var1 = q1 * (1.0f / D_);
    }
    const float rs0 = __frcp_rn(bf16r(__fsqrt_rn(bf16r(bf16r(var0) + 1e-5f))));
    const float rs1 = __frcp_rn(bf16r(__fsqrt_rn(bf16r(bf16r(var1) + 1e-5f))));
    const LnRow lr0 = ln_row(mean0, rs0), lr1 = ln_row(mean1, rs1);
    float acc[64];
    #pragma unroll
    for (int i = 0; i < 64; i++) acc[i] = 0.f;
    float dr[4] = {0.f, 0.f, 0.f, 0.f};
    const uint64_t db0 = make_desc(sB, 8192, 1024, 1);
    #pragma unroll 1
    for (int kc = 0; kc < 8; kc += 2) {
        #pragma unroll
        for (int h2 = 0; h2 < 2; h2++) {
            const int ld = kc + h2, sl = ld < 6 ? ld : ld - 6;
            uint32_t a[4][4];
            #pragma unroll
            for (int k4 = 0; k4 < 4; k4++) ldsm4(a[k4], laddr[k4] + ld * 16384);
            #pragma unroll
            for (int k4 = 0; k4 < 4; k4++) ln_frag(a[k4], lr0, lr1);
            if (nt == 0) {
                #pragma unroll
                for (int k4 = 0; k4 < 4; k4++) mma16816(dr, a[k4], s_wr[(ld * 4 + k4) * 8 + t], s_wr[(ld * 4 + k4) * 8 + 4 + t]);
            }
            mbar_wait(sBar + sl * 8, ld >= 6);
            WG_FENCE();
            #pragma unroll
            for (int k4 = 0; k4 < 4; k4++) wgmma_rs_n128(acc, a[k4], db0 + (uint64_t)(sl * 1024 + k4 * 128));
            WG_COMMIT();
            wg_wait<1>();
            if (ld >= 1 && ld <= 6 && (threadIdx.x & 127) == 0) mbar_arrive(sBar + 48 + (ld - 1) * 8);
        }
    }
    const int row0 = mt * 128 + warp * 16;
    if (nt == 0 && t == 0) {
        g_r[row0 + g] = bf16r(dr[0]); g_r[row0 + g + 8] = bf16r(dr[2]);
        g_stats[row0 + g] = make_float2(bf_lo(lr0.m2), rs0); g_stats[row0 + g + 8] = make_float2(bf_lo(lr1.m2), rs1);
    }
    wg_wait<0>();
    touch64(acc);
    CK(4);
    float acc2[32];
    #pragma unroll
    for (int i = 0; i < 32; i++) acc2[i] = 0.f;
    #pragma unroll 1
    for (int q = 0; q < 4; q++) {
        const int sl = q + 2;
        #pragma unroll
        for (int h2 = 0; h2 < 2; h2++) {
            uint32_t a[4][4];
            #pragma unroll
            for (int k4 = 0; k4 < 4; k4++) ldsm4(a[k4], laddr[k4] + (q * 2 + h2) * 16384);
            #pragma unroll
            for (int k4 = 0; k4 < 4; k4++) ln_frag(a[k4], lr0, lr1);
            if (h2 == 0) mbar_wait(sBar + sl * 8, 1);
            WG_FENCE();
            #pragma unroll
            for (int k4 = 0; k4 < 4; k4++) wgmma_rs_n64(acc2, a[k4], db0 + (uint64_t)(sl * 1024 + (h2 * 4 + k4) * 128));
            WG_COMMIT();
            wg_wait<1>();
        }
        if (q == 0) k1_store<4>(acc, 0, nt, row0, lane);
        if (q == 1) k1_store<4>(acc + 32, 4, nt, row0, lane);
    }
    wg_wait<0>();
    touch32(acc2);
    CK(5);
    k1_store<4>(acc2, 8, nt, row0, lane);
    CK(6);
}

constexpr int K2_THREADS = 512;
constexpr int K2_SMEM = 65536 + 98304 + 16384 + 128;

constexpr float QS = 0.25f * 1.4426950408889634f;
__device__ __forceinline__ uint32_t polyexp2(float s0, float s1, float cb, uint32_t one2, uint32_t ca2, float one) {
    float u0, u1;
    asm("fma.rn.sat.f32 %0, %1, %2, %3;" : "=f"(u0) : "f"(s0), "f"(QS * (1.0f / 255.0f)), "f"(cb));
    asm("fma.rn.sat.f32 %0, %1, %2, %3;" : "=f"(u1) : "f"(s1), "f"(QS * (1.0f / 255.0f)), "f"(cb));
    const float z0 = fmaf(u0, 0.99609375f, one), z1 = fmaf(u1, 0.99609375f, one);
    const uint32_t W = __byte_perm(__float_as_uint(z0), __float_as_uint(z1), 0x6521);
    uint32_t U, h, G;
    asm("lop3.b32 %0, %1, 0x007F007F, %2, 0xEA;" : "=r"(U) : "r"(W), "r"(one2));
    asm("fma.rn.bf16x2 %0, %1, %2, %3;" : "=r"(h) : "r"(U), "r"(ca2), "r"(0xC300C300u));
    asm("fma.rn.bf16x2 %0, %1, %2, %3;" : "=r"(G) : "r"(h), "r"(U), "r"(0x438B438Bu));
    return W + G - 0x43404340u;
}

struct ExpC { float nm0, nm1, cb0, cb1, one; uint32_t one2, ca2; };

template <int G>
__device__ __forceinline__ void exp_block(const float* s, uint32_t* p, const ExpC& c) {
    #pragma unroll
    for (int hf = 0; hf < 2; hf++) {
        const float* x = s + hf * 4;
        if ((PMASK >> (G + hf)) & 1) {
            p[hf * 2 + 0] = polyexp2(x[0], x[1], c.cb0, c.one2, c.ca2, c.one);
            p[hf * 2 + 1] = polyexp2(x[2], x[3], c.cb1, c.one2, c.ca2, c.one);
        } else {
            p[hf * 2 + 0] = pack_bf16(ex2(fmaf(x[0], QS, c.nm0)), ex2(fmaf(x[1], QS, c.nm0)));
            p[hf * 2 + 1] = pack_bf16(ex2(fmaf(x[2], QS, c.nm1)), ex2(fmaf(x[3], QS, c.nm1)));
        }
    }
}

__device__ __forceinline__ void max16(const float* s, float& mx0, float& mx1) {
    #pragma unroll
    for (int j = 0; j < 4; j++) {
        mx0 = fmaxf(mx0, fmaxf(s[4 * j], s[4 * j + 1]));
        mx1 = fmaxf(mx1, fmaxf(s[4 * j + 2], s[4 * j + 3]));
    }
}

__device__ void moe_cta(int part, unsigned char* smem, const __nv_bfloat16* __restrict__ x, const __nv_bfloat16* __restrict__ w_gate,
                        const __nv_bfloat16* __restrict__ w_up, const __nv_bfloat16* __restrict__ w_down) {
    float* xs = (float*)smem;
    float* red = xs + 1024;
    float* hs = red + 8 * 4 * 448;
    __shared__ float s_v[32];
    __shared__ int s_i[32];
    __shared__ int s_sel[2];
    const int tid = threadIdx.x, warp = tid >> 5, lane = tid & 31;
    for (int pass = 0; pass < 2; pass++) {
        float bv = -INFINITY; int bi = 0x7fffffff;
        const int excl = pass ? s_sel[0] : -1;
        for (int i = tid; i < S_; i += K2_THREADS) {
            float v = g_r[i];
            if (i != excl && (v > bv || (v == bv && i < bi) || bi == 0x7fffffff)) { bv = v; bi = i; }
        }
        #pragma unroll
        for (int o = 16; o; o >>= 1) {
            float ov = __shfl_xor_sync(~0u, bv, o); int oi = __shfl_xor_sync(~0u, bi, o);
            if (ov > bv || (ov == bv && oi < bi)) { bv = ov; bi = oi; }
        }
        if (lane == 0) { s_v[warp] = bv; s_i[warp] = bi; }
        __syncthreads();
        if (warp == 0) {
            bv = lane < 16 ? s_v[lane] : -INFINITY; bi = lane < 16 ? s_i[lane] : 0x7fffffff;
            #pragma unroll
            for (int o = 16; o; o >>= 1) {
                float ov = __shfl_xor_sync(~0u, bv, o); int oi = __shfl_xor_sync(~0u, bi, o);
                if (ov > bv || (ov == bv && oi < bi)) { bv = ov; bi = oi; }
            }
            if (lane == 0) s_sel[pass] = (bi == 0x7fffffff) ? pass : bi;
        }
        __syncthreads();
    }
    for (int i = tid; i < 1024; i += K2_THREADS) {
        const int tok = s_sel[i >> 9];
        const float2 st = g_stats[tok];
        xs[i] = ln_elem(__bfloat162float(x[(size_t)tok * D_ + (i & 511)]), st.x, st.y);
    }
    if (part == 0 && tid < 2) g_sel[tid] = s_sel[tid];
    __syncthreads();
    const int c0 = part * 448;
    if (tid < 448) {
        const int cg = tid % 56, ks = tid / 56;
        float a[4][8];
        #pragma unroll
        for (int i = 0; i < 4; i++)
            #pragma unroll
            for (int j = 0; j < 8; j++) a[i][j] = 0.f;
        const __nv_bfloat16* pg = w_gate + (size_t)(ks * 64) * F_ + c0 + cg * 8;
        const __nv_bfloat16* pu = w_up + (size_t)(ks * 64) * F_ + c0 + cg * 8;
        #pragma unroll 8
        for (int k = 0; k < 64; k++) {
            const uint4 gv = __ldg((const uint4*)(pg + (size_t)k * F_));
            const uint4 uv = __ldg((const uint4*)(pu + (size_t)k * F_));
            const float x0 = xs[ks * 64 + k], x1 = xs[512 + ks * 64 + k];
            const uint32_t gu[4] = {gv.x, gv.y, gv.z, gv.w}, uu[4] = {uv.x, uv.y, uv.z, uv.w};
            #pragma unroll
            for (int j = 0; j < 4; j++) {
                const float g0 = bf_lo(gu[j]), g1 = bf_hi(gu[j]), u0 = bf_lo(uu[j]), u1 = bf_hi(uu[j]);
                a[0][2 * j] = fmaf(x0, g0, a[0][2 * j]); a[0][2 * j + 1] = fmaf(x0, g1, a[0][2 * j + 1]);
                a[1][2 * j] = fmaf(x1, g0, a[1][2 * j]); a[1][2 * j + 1] = fmaf(x1, g1, a[1][2 * j + 1]);
                a[2][2 * j] = fmaf(x0, u0, a[2][2 * j]); a[2][2 * j + 1] = fmaf(x0, u1, a[2][2 * j + 1]);
                a[3][2 * j] = fmaf(x1, u0, a[3][2 * j]); a[3][2 * j + 1] = fmaf(x1, u1, a[3][2 * j + 1]);
            }
        }
        #pragma unroll
        for (int i = 0; i < 4; i++)
            #pragma unroll
            for (int j = 0; j < 8; j++) red[(ks * 4 + i) * 448 + cg * 8 + j] = a[i][j];
    }
    __syncthreads();
    for (int i = tid; i < 896; i += K2_THREADS) {
        const int tok = i / 448, c = i % 448;
        float gs = 0.f, us = 0.f;
        #pragma unroll
        for (int ks = 0; ks < 8; ks++) { gs += red[(ks * 4 + tok) * 448 + c]; us += red[(ks * 4 + 2 + tok) * 448 + c]; }
        gs = bf16r(gs); us = bf16r(us);
        const float sl = bf16r(gs / (1.0f + __expf(-gs)));
        hs[i] = bf16r(sl * us);
    }
    __syncthreads();
    {
        const int cg = tid & 63, fs = tid >> 6;
        float a[2][8];
        #pragma unroll
        for (int j = 0; j < 8; j++) { a[0][j] = 0.f; a[1][j] = 0.f; }
        const __nv_bfloat16* pd = w_down + (size_t)(c0 + fs * 56) * D_ + cg * 8;
        #pragma unroll 8
        for (int f = 0; f < 56; f++) {
            const uint4 dv = __ldg((const uint4*)(pd + (size_t)f * D_));
            const float h0 = hs[fs * 56 + f], h1 = hs[448 + fs * 56 + f];
            const uint32_t du[4] = {dv.x, dv.y, dv.z, dv.w};
            #pragma unroll
            for (int j = 0; j < 4; j++) {
                const float d0 = bf_lo(du[j]), d1 = bf_hi(du[j]);
                a[0][2 * j] = fmaf(h0, d0, a[0][2 * j]); a[0][2 * j + 1] = fmaf(h0, d1, a[0][2 * j + 1]);
                a[1][2 * j] = fmaf(h1, d0, a[1][2 * j]); a[1][2 * j + 1] = fmaf(h1, d1, a[1][2 * j + 1]);
            }
        }
        #pragma unroll
        for (int j = 0; j < 8; j++) { red[(fs * 2) * 512 + cg * 8 + j] = a[0][j]; red[(fs * 2 + 1) * 512 + cg * 8 + j] = a[1][j]; }
    }
    __syncthreads();
    for (int i = tid; i < 1024; i += K2_THREADS) {
        float s = 0.f;
        #pragma unroll
        for (int fs = 0; fs < 8; fs++) s += red[(fs * 2 + (i >> 9)) * 512 + (i & 511)];
        g_ypart[part][i >> 9][i & 511] = s;
    }
}

__global__ void __launch_bounds__(K2_THREADS, 1)
k2_attn(const __nv_bfloat16* __restrict__ x, const __nv_bfloat16* __restrict__ w_gate, const __nv_bfloat16* __restrict__ w_up,
        const __nv_bfloat16* __restrict__ w_down) {
    extern __shared__ __align__(1024) unsigned char smem[];
    TL(1, 0);
    pdl_launch();
    if (blockIdx.x >= 128) {
        const int part = blockIdx.x - 128;
        {
            const int k = threadIdx.x;
            asm volatile("cp.async.bulk.prefetch.L2.global [%0], %1;" :: "l"(w_gate + (size_t)k * F_ + part * 448), "r"(896) : "memory");
            asm volatile("cp.async.bulk.prefetch.L2.global [%0], %1;" :: "l"(w_up + (size_t)k * F_ + part * 448), "r"(896) : "memory");
            if (k < 56) asm volatile("cp.async.bulk.prefetch.L2.global [%0], %1;" :: "l"(w_down + (size_t)(part * 448 + k * 8) * D_), "r"(8192) : "memory");
        }
        pdl_wait(); TL(1, 1); moe_cta(blockIdx.x - 128, smem, x, w_gate, w_up, w_down); TL(1, 2); return; }
    const uint32_t sK = smem_u32(smem), sV = sK + 65536, sQ = sV + 98304, sBar = sQ + 16384;
    const int h = blockIdx.x >> 2, qb = blockIdx.x & 3;
    const int warp = __shfl_sync(~0u, threadIdx.x >> 5, 0), lane = threadIdx.x & 31, wg = warp >> 2;
    if (threadIdx.x == 0) {
        mbar_init(sBar, 1); mbar_init(sBar + 8, 1);
        asm volatile("fence.mbarrier_init.release.cluster;" ::: "memory");
        mbar_expect_tx(sBar, 16384 + 16384 + 2 * 8192);
        mbar_expect_tx(sBar + 8, 49152 + 2 * 24576);
    }
    for (int i = threadIdx.x; i < 2048; i += K2_THREADS) {
        const uint32_t v = is_poly_group(i >> 3) ? 0xBF80BF80u : 0x3F803F80u;
        *(uint4*)(smem + 65536 + 65536 + i * 16) = make_uint4(v, v, v, v);
    }
    fence_async_smem();
    __syncthreads();
    if (warp == 0) {
        pdl_wait();
        TL(1, 1);
        const uint4* gk = g_K + (size_t)h * 4096;
        const uint4* gv = g_V + (size_t)h * 4096;
        if (lane == 0) bulk_g2s(sQ, g_Q + (size_t)h * 4096 + qb * 1024, 16384, sBar);
        if (lane == 1) bulk_g2s(sK, gk, 16384, sBar);
        if (lane == 2) bulk_g2s(sV, gv, 8192, sBar);
        if (lane == 3) bulk_g2s(sV + 32768, gv + 2048, 8192, sBar);
        if (lane == 4) bulk_g2s(sK + 16384, gk + 1024, 49152, sBar + 8);
        if (lane == 5) bulk_g2s(sV + 8192, gv + 512, 24576, sBar + 8);
        if (lane == 6) bulk_g2s(sV + 32768 + 8192, gv + 2048 + 512, 24576, sBar + 8);
        __syncwarp();
    }
    ExpC c;
    {
        const volatile uint32_t* cc = g_const;
        c.one2 = cc[0]; c.ca2 = cc[1]; c.one = __uint_as_float(cc[2]);
    }
    const uint32_t kdesc0 = (uint32_t)make_desc(sK, 128, 256, 0);
    const uint32_t vdesc0 = (uint32_t)make_desc(sV, 128, 32768, 0);
    #pragma unroll 1
    for (int pass = 0; pass < 2; pass++) {
        const bool dry = false;
        if (pass == 0) { mbar_wait(sBar, 0); __syncwarp(); TL(1, 2); }
        const int unit = (pass & 1) * 4 + wg;
        const uint32_t q = (uint32_t)make_desc(sQ + unit * 2048, 128, 256, 0);
        float o[12];
        #pragma unroll 1
        for (int attempt = 0; attempt < 2; attempt++) {
            float s0[16], s1[16], s2[16];
            #pragma unroll
            for (int i = 0; i < 16; i++) { s0[i] = 0.f; s1[i] = 0.f; s2[i] = 0.f; }
            float mx0 = -INFINITY, mx1 = -INFINITY;
            if (attempt) {
                #pragma unroll 1
                for (int it = 0; it < 64; it++) {
                    WG_FENCE();
                    wgmma_qk32(s0, q, kdesc0 + it * 64);
                    WG_COMMIT();
                    wg_wait<0>();
                    touch16(s0);
                    max16(s0, mx0, mx1);
                }
            }
            #pragma unroll
            for (int i = 0; i < 12; i++) o[i] = 0.f;
            WG_FENCE();
            wgmma_qk32(s2, q, kdesc0);
            wgmma_qk32(s0, q, kdesc0 + 64);
            wgmma_qk32(s1, q, kdesc0 + 128);
            WG_COMMIT();
            wg_wait<0>();
            touch16(s0); touch16(s1); touch16(s2);
            max16(s0, mx0, mx1); max16(s1, mx0, mx1); max16(s2, mx0, mx1);
            mx0 = fmaxf(mx0, __shfl_xor_sync(~0u, mx0, 1)); mx0 = fmaxf(mx0, __shfl_xor_sync(~0u, mx0, 2));
            mx1 = fmaxf(mx1, __shfl_xor_sync(~0u, mx1, 1)); mx1 = fmaxf(mx1, __shfl_xor_sync(~0u, mx1, 2));
            const float bias = attempt ? 0.0f : 64.0f;
            c.nm0 = __shfl_sync(~0u, -fmaf(mx0, QS, bias), lane); c.nm1 = __shfl_sync(~0u, -fmaf(mx1, QS, bias), lane);
            c.cb0 = __shfl_sync(~0u, (127.0f + c.nm0) * (1.0f / 255.0f), lane);
            c.cb1 = __shfl_sync(~0u, (127.0f + c.nm1) * (1.0f / 255.0f), lane);
            uint32_t kd = kdesc0 + 192, vd = vdesc0 + 32;
            {
                uint32_t pa[4], pb[4];
                exp_block<12>(s2, pa, c);
                exp_block<14>(s2 + 8, pb, c);
                WG_FENCE();
                wgmma_pv(o, pa, vdesc0); wgmma_pv(o, pb, vdesc0 + 16);
                WG_COMMIT();
            }
            #pragma unroll 1
            for (int seg = 0; seg < (dry ? 1 : 2); seg++) {
            if (seg) { wg_wait<0>(); mbar_wait(sBar + 8, 0); __syncwarp(); }
            #pragma unroll 1
            for (int it = seg ? 3 : (dry ? 2 : 0); it < (seg ? 21 : 3); it++) {
                uint32_t p[6][4];
                WG_FENCE();
                wgmma_qk32(s2, q, kd);
                WG_COMMIT();
                exp_block<0>(s0, p[0], c);
                exp_block<2>(s0 + 8, p[1], c);
                WG_FENCE();
                wgmma_pv(o, p[0], vd); wgmma_pv(o, p[1], vd + 16);
                wgmma_qk32(s0, q, kd + 64);
                WG_COMMIT();
                wg_wait<1>();
                touch16(s2);
                exp_block<4>(s1, p[2], c);
                exp_block<6>(s1 + 8, p[3], c);
                WG_FENCE();
                wgmma_pv(o, p[2], vd + 32); wgmma_pv(o, p[3], vd + 48);
                wgmma_qk32(s1, q, kd + 128);
                WG_COMMIT();
                wg_wait<1>();
                touch16(s0);
                exp_block<8>(s2, p[4], c);
                exp_block<10>(s2 + 8, p[5], c);
                WG_FENCE();
                wgmma_pv(o, p[4], vd + 64); wgmma_pv(o, p[5], vd + 80);
                WG_COMMIT();
                vd += 96; kd += 192;
                wg_wait<1>();
                touch16(s1);
            }
            }
            wg_wait<0>();
            touch12(o);
            if (attempt) break;
            float big = 0.f;
            #pragma unroll
            for (int i = 0; i < 12; i++) big = fmaxf(big, fabsf(o[i]));
            bool bad = !(big < 1e30f);
            #pragma unroll
            for (int i = 0; i < 12; i++) bad |= (o[i] != o[i]);
            uint32_t any;
            asm volatile("{.reg .pred p, q; setp.ne.u32 p, %1, 0; barrier.cta.red.or.pred.aligned q, %2, 128, p; selp.u32 %0, 1, 0, q;}"
                         : "=r"(any) : "r"((uint32_t)bad), "r"(1 + wg) : "memory");
            if (dry || !__any_sync(~0u, any)) break;
        }
        const int g = lane >> 2, t = lane & 3;
        const int r = (warp & 3) * 16 + g;
        const float i0 = __fdiv_rn(1.0f, o[8]), i1 = __fdiv_rn(1.0f, o[10]);
        uint32_t* ob = (uint32_t*)(g_O + (size_t)(qb * 8 + unit) * 4096 + (h >> 2) * 512 + r * 8) + t;
        const int c0 = ((h & 3) * 2) ^ (r & 7), c1 = ((h & 3) * 2 + 1) ^ (r & 7);
        if (!dry) {
            ob[c0 * 4] = pack_bf16(o[0] * i0, o[1] * i0);
            ob[c1 * 4] = pack_bf16(o[4] * i0, o[5] * i0);
            ob[256 + c0 * 4] = pack_bf16(o[2] * i1, o[3] * i1);
            ob[256 + c1 * 4] = pack_bf16(o[6] * i1, o[7] * i1);
            TL(1, 3 + pass);
        }
    }
}

constexpr int K3_THREADS = 256;
constexpr int K3_SMEM = 65536 + 131072 + 128;

__global__ void __launch_bounds__(K3_THREADS, 1)
k3_out(const __grid_constant__ CUtensorMap wmap, const __nv_bfloat16* __restrict__ x, __nv_bfloat16* __restrict__ out) {
    extern __shared__ __align__(1024) unsigned char smem[];
    const uint32_t sA = smem_u32(smem), sB = sA + 65536, sBar = sB + 131072;
    const int warp = __shfl_sync(~0u, threadIdx.x >> 5, 0), lane = threadIdx.x & 31, wg = warp >> 2;
    const int nt = blockIdx.x & 3, mt = blockIdx.x >> 2;
    TL(2, 0);
    if (threadIdx.x == 0) {
        for (int i = 0; i < 6; i++) mbar_init(sBar + i * 8, 1);
        asm volatile("fence.mbarrier_init.release.cluster;" ::: "memory");
        for (int kh = 0; kh < 2; kh++) {
            mbar_expect_tx(sBar + kh * 8, 65536);
            tma_2d(sB + kh * 32768, &wmap, nt * 128, kh * 256, sBar + kh * 8);
            tma_2d(sB + 65536 + kh * 32768, &wmap, nt * 128 + 64, kh * 256, sBar + kh * 8);
        }
    }
    const int er = threadIdx.x >> 2, ec = (threadIdx.x & 3) * 32;
    const int row = mt * 64 + er;
    uint4 xv[4];
    #pragma unroll
    for (int j = 0; j < 4; j++) xv[j] = __ldg((const uint4*)(x + (size_t)row * D_ + nt * 128 + ec) + j);
    pdl_wait();
    TL(2, 1);
    if (threadIdx.x == 0) {
        for (int q = 0; q < 4; q++) {
            mbar_expect_tx(sBar + 16 + q * 8, 16384);
            bulk_g2s(sA + q * 16384, g_O + (size_t)mt * 4096 + q * 1024, 16384, sBar + 16 + q * 8);
        }
    }
    const int sel0 = g_sel[0], sel1 = g_sel[1];
    const float2 st = g_stats[row];
    uint32_t bb[16];
    {
        const uint32_t xu[16] = {xv[0].x, xv[0].y, xv[0].z, xv[0].w, xv[1].x, xv[1].y, xv[1].z, xv[1].w,
                                 xv[2].x, xv[2].y, xv[2].z, xv[2].w, xv[3].x, xv[3].y, xv[3].z, xv[3].w};
        #pragma unroll
        for (int j = 0; j < 16; j++) bb[j] = pack_bf16(bf16r(bf_lo(xu[j]) - st.x) * st.y, bf16r(bf_hi(xu[j]) - st.x) * st.y);
        const int slot = row == sel0 ? 0 : (row == sel1 ? 1 : -1);
        if (slot >= 0) {
            const float gate = bf16r(1.0f / (1.0f + __expf(-g_r[row])));
            const int c0 = nt * 128 + ec;
            #pragma unroll
            for (int j = 0; j < 16; j++) {
                const float2 a = *(const float2*)&g_ypart[0][slot][c0 + 2 * j], b = *(const float2*)&g_ypart[1][slot][c0 + 2 * j];
                const float2 c = *(const float2*)&g_ypart[2][slot][c0 + 2 * j], d = *(const float2*)&g_ypart[3][slot][c0 + 2 * j];
                bb[j] = pack_bf16(bf_lo(bb[j]) + bf16r(bf16r(a.x + b.x + c.x + d.x) * gate), bf_hi(bb[j]) + bf16r(bf16r(a.y + b.y + c.y + d.y) * gate));
            }
        }
    }
    __syncthreads();
    float acc[32];
    #pragma unroll
    for (int i = 0; i < 32; i++) acc[i] = 0.f;
    const uint64_t da0 = make_desc(sA, 16, 1024, 1);
    const uint64_t db0 = make_desc(sB + wg * 65536, 8192, 1024, 1);
    #pragma unroll 1
    for (int q = 0; q < 4; q++) {
        if ((q & 1) == 0) mbar_wait(sBar + (q >> 1) * 8, 0);
        mbar_wait(sBar + 16 + q * 8, 0);
        WG_FENCE();
        #pragma unroll
        for (int kk = 0; kk < 8; kk++)
            wgmma_n64(acc, da0 + (uint64_t)(q * 1024 + (kk >> 2) * 512 + (kk & 3) * 2), db0 + (uint64_t)(q * 1024 + kk * 128));
        WG_COMMIT();
    }
    wg_wait<0>();
    touch32(acc);
    TL(2, 2);
    __syncthreads();
    {
        const int g = lane >> 2, t = lane & 3;
        unsigned char* sp = smem + ((warp & 3) * 16 + g) * 272 + wg * 128 + t * 4;
        #pragma unroll
        for (int j = 0; j < 8; j++) {
            *(uint32_t*)(sp + j * 16) = pack_bf16(acc[4 * j], acc[4 * j + 1]);
            *(uint32_t*)(sp + 8 * 272 + j * 16) = pack_bf16(acc[4 * j + 2], acc[4 * j + 3]);
        }
    }
    __syncthreads();
    #pragma unroll
    for (int j = 0; j < 4; j++) {
        const uint4 av = *(const uint4*)(smem + er * 272 + ec * 2 + j * 16);
        const uint32_t au[4] = {av.x, av.y, av.z, av.w}, xu[4] = {xv[j].x, xv[j].y, xv[j].z, xv[j].w};
        uint32_t o[4];
        #pragma unroll
        for (int i = 0; i < 4; i++) {
            uint32_t t2;
            asm("add.rn.bf16x2 %0, %1, %2;" : "=r"(t2) : "r"(xu[i]), "r"(au[i]));
            asm("add.rn.bf16x2 %0, %1, %2;" : "=r"(o[i]) : "r"(t2), "r"(bb[j * 4 + i]));
        }
        *((uint4*)(out + (size_t)row * D_ + nt * 128 + ec) + j) = make_uint4(o[0], o[1], o[2], o[3]);
    }
    TL(2, 3);
}

typedef CUresult (*EncodeFn)(CUtensorMap*, CUtensorMapDataType, cuuint32_t, void*, const cuuint64_t*, const cuuint64_t*,
                             const cuuint32_t*, const cuuint32_t*, CUtensorMapInterleave, CUtensorMapSwizzle,
                             CUtensorMapL2promotion, CUtensorMapFloatOOBfill);

void make_wmap(EncodeFn fn, CUtensorMap* map, const void* ptr, int rows, int cols, int box_rows) {
    cuuint64_t dims[2] = {(cuuint64_t)cols, (cuuint64_t)rows};
    cuuint64_t strides[1] = {(cuuint64_t)cols * 2};
    cuuint32_t box[2] = {64, (cuuint32_t)box_rows};
    cuuint32_t es[2] = {1, 1};
    fn(map, CU_TENSOR_MAP_DATA_TYPE_BFLOAT16, 2, (void*)ptr, dims, strides, box, es, CU_TENSOR_MAP_INTERLEAVE_NONE,
       CU_TENSOR_MAP_SWIZZLE_128B, CU_TENSOR_MAP_L2_PROMOTION_L2_256B, CU_TENSOR_MAP_FLOAT_OOB_FILL_NONE);
}

}

extern "C" void kernel_launch(void* const* d_in, const int* in_sizes, int n_in, void* d_out, int out_size) {
    const __nv_bfloat16* x = (const __nv_bfloat16*)d_in[0];
    const __nv_bfloat16* wqkv = (const __nv_bfloat16*)d_in[1];
    const __nv_bfloat16* wo = (const __nv_bfloat16*)d_in[2];
    const __nv_bfloat16* w_r = (const __nv_bfloat16*)d_in[4];
    const __nv_bfloat16* w_gate = (const __nv_bfloat16*)d_in[5];
    const __nv_bfloat16* w_up = (const __nv_bfloat16*)d_in[6];
    const __nv_bfloat16* w_down = (const __nv_bfloat16*)d_in[7];
    __nv_bfloat16* out = (__nv_bfloat16*)d_out;

    static EncodeFn encode = nullptr;
    if (!encode) {
        void* fn = nullptr;
        cudaDriverEntryPointQueryResult qres;
        cudaGetDriverEntryPoint("cuTensorMapEncodeTiled", &fn, cudaEnableDefault, &qres);
        encode = (EncodeFn)fn;
        cudaFuncSetAttribute(k1_ln_qkv, cudaFuncAttributeMaxDynamicSharedMemorySize, K1_SMEM);
        cudaFuncSetAttribute(k2_attn, cudaFuncAttributeMaxDynamicSharedMemorySize, K2_SMEM);
        cudaFuncSetAttribute(k3_out, cudaFuncAttributeMaxDynamicSharedMemorySize, K3_SMEM);
    }
    CUtensorMap map_qkv, map_wo, map_x;
    make_wmap(encode, &map_x, x, S_, D_, 64);
    make_wmap(encode, &map_qkv, wqkv, D_, 3 * D_, 64);
    make_wmap(encode, &map_wo, wo, D_, D_, 256);

    k1_ln_qkv<<<128, K1_THREADS, K1_SMEM, cudaStreamPerThread>>>(map_qkv, map_x, w_r);
    cudaLaunchAttribute at[1];
    at[0].id = cudaLaunchAttributeProgrammaticStreamSerialization;
    at[0].val.programmaticStreamSerializationAllowed = 1;
    cudaLaunchConfig_t cfg = {};
    cfg.stream = cudaStreamPerThread;
    cfg.attrs = at; cfg.numAttrs = 1;
    cfg.gridDim = dim3(132); cfg.blockDim = dim3(K2_THREADS); cfg.dynamicSmemBytes = K2_SMEM;
    cudaLaunchKernelEx(&cfg, k2_attn, x, w_gate, w_up, w_down);
    cfg.gridDim = dim3(128); cfg.blockDim = dim3(K3_THREADS); cfg.dynamicSmemBytes = K3_SMEM;
    cudaLaunchKernelEx(&cfg, k3_out, map_wo, x, out);
}
```

```cpp
#include <cuda_runtime.h>
#include <cuda_bf16.h>
#include <cuda.h>
#include <stdint.h>

namespace {

constexpr int S_ = 2048, D_ = 512, H_ = 32, F_ = 1792;

constexpr uint32_t PMASK = 0xDB6;

__device__ __align__(1024) uint4 g_QKV[3 * H_ * S_ * 2];
#define g_Q (g_QKV)
#define g_K (g_QKV + H_ * S_ * 2)
#define g_V (g_QKV + 2 * H_ * S_ * 2)
__device__ __align__(1024) uint4 g_O[S_ * D_ / 8];
__device__ float2 g_stats[S_];
__device__ uint32_t g_const[2] = {0x3F803F80u, 0x42294229u};
__device__ float g_r[S_];
__device__ __align__(16) float g_ypart[4][2][D_];
__device__ int g_sel[2];

#define TL(k, p)
#define CK(i)
__device__ __forceinline__ uint32_t smem_u32(const void* p) { return (uint32_t)__cvta_generic_to_shared(p); }
__device__ __forceinline__ float bf16r(float x) { return __bfloat162float(__float2bfloat16_rn(x)); }
__device__ __forceinline__ uint32_t pack_bf16(float lo, float hi) {
    uint32_t r; asm("cvt.rn.bf16x2.f32 %0, %1, %2;" : "=r"(r) : "f"(hi), "f"(lo)); return r;
}
__device__ __forceinline__ float bf_lo(uint32_t u) { return __uint_as_float(u << 16); }
__device__ __forceinline__ float bf_hi(uint32_t u) { return __uint_as_float(u & 0xFFFF0000u); }
__device__ __forceinline__ float ex2(float x) { float y; asm("ex2.approx.ftz.f32 %0, %1;" : "=f"(y) : "f"(x)); return y; }

__device__ __forceinline__ void mbar_init(uint32_t bar, uint32_t count) {
    asm volatile("mbarrier.init.shared::cta.b64 [%0], %1;" :: "r"(bar), "r"(count) : "memory");
}
__device__ __forceinline__ void mbar_expect_tx(uint32_t bar, uint32_t bytes) {
    asm volatile("mbarrier.arrive.expect_tx.shared::cta.b64 _, [%0], %1;" :: "r"(bar), "r"(bytes) : "memory");
}
__device__ __forceinline__ void mbar_arrive(uint32_t bar) {
    asm volatile("mbarrier.arrive.shared::cta.b64 _, [%0];" :: "r"(bar) : "memory");
}
__device__ __forceinline__ void mbar_wait(uint32_t bar, uint32_t parity) {
    uint32_t done;
    #pragma unroll 1
    for (int it = 0; it < (1 << 26); it++) {
        asm volatile("{.reg .pred p; mbarrier.try_wait.parity.shared::cta.b64 p, [%1], %2; selp.u32 %0, 1, 0, p;}"
                     : "=r"(done) : "r"(bar), "r"(parity) : "memory");
        if (done) return;
    }
    __trap();
}
__device__ __forceinline__ void bulk_g2s(uint32_t dst, const void* src, uint32_t bytes, uint32_t bar) {
    asm volatile("cp.async.bulk.shared::cluster.global.mbarrier::complete_tx::bytes [%0], [%1], %2, [%3];"
                 :: "r"(dst), "l"(src), "r"(bytes), "r"(bar) : "memory");
}
__device__ __forceinline__ void tma_2d(uint32_t dst, const CUtensorMap* map, int c0, int c1, uint32_t bar) {
    asm volatile("cp.async.bulk.tensor.2d.shared::cluster.global.mbarrier::complete_tx::bytes [%0], [%1, {%3, %4}], [%2];"
                 :: "r"(dst), "l"(map), "r"(bar), "r"(c0), "r"(c1) : "memory");
}
__device__ __forceinline__ void fence_async_smem() { asm volatile("fence.proxy.async.shared::cta;" ::: "memory"); }
__device__ __forceinline__ void named_bar(int id, int n) { asm volatile("bar.sync %0, %1;" :: "r"(id), "r"(n) : "memory"); }

__device__ __forceinline__ uint64_t make_desc(uint32_t saddr, uint32_t lbo, uint32_t sbo, uint32_t swz) {
    return (uint64_t)((saddr & 0x3FFFF) >> 4) | ((uint64_t)(lbo >> 4) << 16) | ((uint64_t)(sbo >> 4) << 32) | ((uint64_t)swz << 62);
}
#define WG_FENCE() asm volatile("wgmma.fence.sync.aligned;" ::: "memory")
#define WG_COMMIT() asm volatile("wgmma.commit_group.sync.aligned;" ::: "memory")
template <int N> __device__ __forceinline__ void wg_wait() { asm volatile("wgmma.wait_group.sync.aligned %0;" :: "n"(N) : "memory"); }

#define F4(d, o) "+f"(d[o]), "+f"(d[o + 1]), "+f"(d[o + 2]), "+f"(d[o + 3])
#define F16(d, o) F4(d, o), F4(d, o + 4), F4(d, o + 8), F4(d, o + 12)
#define F32(d, o) F16(d, o), F16(d, o + 16)

__device__ __forceinline__ void wgmma_rs_n128(float* d, const uint32_t* a, uint64_t db) {
    asm volatile("wgmma.mma_async.sync.aligned.m64n128k16.f32.bf16.bf16 "
        "{%0,%1,%2,%3,%4,%5,%6,%7,%8,%9,%10,%11,%12,%13,%14,%15,%16,%17,%18,%19,%20,%21,%22,%23,%24,%25,%26,%27,%28,%29,%30,%31,"
        "%32,%33,%34,%35,%36,%37,%38,%39,%40,%41,%42,%43,%44,%45,%46,%47,%48,%49,%50,%51,%52,%53,%54,%55,%56,%57,%58,%59,%60,%61,%62,%63}, "
        "{%64,%65,%66,%67}, %68, 1, 1, 1, 1;\n"
        : F32(d, 0), F32(d, 32) : "r"(a[0]), "r"(a[1]), "r"(a[2]), "r"(a[3]), "l"(db));
}
__device__ __forceinline__ void wgmma_rs_n64(float* d, const uint32_t* a, uint64_t db) {
    asm volatile("wgmma.mma_async.sync.aligned.m64n64k16.f32.bf16.bf16 "
        "{%0,%1,%2,%3,%4,%5,%6,%7,%8,%9,%10,%11,%12,%13,%14,%15,%16,%17,%18,%19,%20,%21,%22,%23,%24,%25,%26,%27,%28,%29,%30,%31}, "
        "{%32,%33,%34,%35}, %36, 1, 1, 1, 1;\n"
        : F32(d, 0) : "r"(a[0]), "r"(a[1]), "r"(a[2]), "r"(a[3]), "l"(db));
}
__device__ __forceinline__ void wgmma_n64(float* d, uint64_t da, uint64_t db) {
    asm volatile("wgmma.mma_async.sync.aligned.m64n64k16.f32.bf16.bf16 "
        "{%0,%1,%2,%3,%4,%5,%6,%7,%8,%9,%10,%11,%12,%13,%14,%15,%16,%17,%18,%19,%20,%21,%22,%23,%24,%25,%26,%27,%28,%29,%30,%31}, "
        "%32, %33, 1, 1, 1, 0, 1;\n"
        : F32(d, 0) : "l"(da), "l"(db));
}
__device__ __forceinline__ void wgmma_qk32(float* d, uint32_t qd, uint32_t kd) {
    asm volatile("{.reg .b64 a, b; mov.b64 a, {%16, 16}; mov.b64 b, {%17, 16};\n"
        "wgmma.mma_async.sync.aligned.m64n32k16.f32.bf16.bf16 {%0,%1,%2,%3,%4,%5,%6,%7,%8,%9,%10,%11,%12,%13,%14,%15}, a, b, 0, 1, 1, 0, 0;}\n"
        : F16(d, 0) : "r"(qd), "r"(kd));
}
__device__ __forceinline__ void wgmma_pv(float* d, const uint32_t* a, uint32_t vd) {
    asm volatile("{.reg .b64 b; mov.b64 b, {%16, 2048};\n"
        "wgmma.mma_async.sync.aligned.m64n24k16.f32.bf16.bf16 {%0,%1,%2,%3,%4,%5,%6,%7,%8,%9,%10,%11}, {%12,%13,%14,%15}, b, 1, 1, 1, 1;}\n"
        : F4(d, 0), F4(d, 4), F4(d, 8) : "r"(a[0]), "r"(a[1]), "r"(a[2]), "r"(a[3]), "r"(vd));
}
__device__ __forceinline__ void touch16(float* d) { asm volatile("" : F16(d, 0) :: "memory"); }
__device__ __forceinline__ void touch12(float* d) { asm volatile("" : F4(d, 0), F4(d, 4), F4(d, 8) :: "memory"); }
__device__ __forceinline__ void touch32(float* d) { asm volatile("" : F32(d, 0) :: "memory"); }
__device__ __forceinline__ void touch64(float* d) { asm volatile("" : F32(d, 0), F32(d, 32) :: "memory"); }

__device__ __forceinline__ float ln_elem(float x, float mean_b, float rden) {
    return bf16r(bf16r(x - mean_b) * rden);
}
__device__ __forceinline__ void pdl_wait() { asm volatile("griddepcontrol.wait;" ::: "memory"); }
__device__ __forceinline__ void pdl_launch() { asm volatile("griddepcontrol.launch_dependents;" ::: "memory"); }
__device__ __forceinline__ void cluster_arrive() { asm volatile("barrier.cluster.arrive.release.aligned;" ::: "memory"); }
__device__ __forceinline__ void cluster_wait() { asm volatile("barrier.cluster.wait.acquire.aligned;" ::: "memory"); }

constexpr int K1_THREADS = 288;
constexpr int K1_SMEM = 131072 + 6 * 16384 + 128 + 1024;

__device__ __forceinline__ void ldsm4(uint32_t* r, uint32_t addr) {
    asm volatile("ldmatrix.sync.aligned.m8n8.x4.shared.b16 {%0, %1, %2, %3}, [%4];" : "=r"(r[0]), "=r"(r[1]), "=r"(r[2]), "=r"(r[3]) : "r"(addr) : "memory");
}
__device__ __forceinline__ void stsm4(uint32_t addr, uint32_t r0, uint32_t r1, uint32_t r2, uint32_t r3) {
    asm volatile("stmatrix.sync.aligned.m8n8.x4.shared.b16 [%0], {%1, %2, %3, %4};" :: "r"(addr), "r"(r0), "r"(r1), "r"(r2), "r"(r3) : "memory");
}
__device__ __forceinline__ void mma16816(float* d, const uint32_t* a, uint32_t b0, uint32_t b1) {
    asm("mma.sync.aligned.m16n8k16.row.col.f32.bf16.bf16.f32 {%0,%1,%2,%3}, {%4,%5,%6,%7}, {%8,%9}, {%0,%1,%2,%3};"
        : "+f"(d[0]), "+f"(d[1]), "+f"(d[2]), "+f"(d[3]) : "r"(a[0]), "r"(a[1]), "r"(a[2]), "r"(a[3]), "r"(b0), "r"(b1));
}
__device__ __forceinline__ uint32_t sub_bf16x2(uint32_t a, uint32_t b) {
    uint32_t d; asm("sub.rn.bf16x2 %0, %1, %2;" : "=r"(d) : "r"(a), "r"(b)); return d;
}
__device__ __forceinline__ uint32_t ln_pair(uint32_t x2, uint32_t mean2, uint32_t rhi2, uint32_t rlo2) {
    const uint32_t d = sub_bf16x2(x2, mean2);
    uint32_t t, y;
    asm("mul.rn.bf16x2 %0, %1, %2;" : "=r"(t) : "r"(d), "r"(rlo2));
    asm("fma.rn.bf16x2 %0, %1, %2, %3;" : "=r"(y) : "r"(d), "r"(rhi2), "r"(t));
    return y;
}
struct LnRow { uint32_t m2, hi2, lo2; };
__device__ __forceinline__ LnRow ln_row(float mean, float rden) {
    LnRow r;
    r.m2 = pack_bf16(mean, mean);
    r.hi2 = pack_bf16(rden, rden);
    const float lo = rden - bf_lo(r.hi2);
    r.lo2 = pack_bf16(lo, lo);
    return r;
}
__device__ __forceinline__ void ln_frag(uint32_t* a, const LnRow& r0, const LnRow& r1) {
    a[0] = ln_pair(a[0], r0.m2, r0.hi2, r0.lo2); a[1] = ln_pair(a[1], r1.m2, r1.hi2, r1.lo2);
    a[2] = ln_pair(a[2], r0.m2, r0.hi2, r0.lo2); a[3] = ln_pair(a[3], r1.m2, r1.hi2, r1.lo2);
}

template <int NJ>
__device__ __forceinline__ void k1_store(const float* acc, int jj0, int nt, int row0, int lane) {
    const int g = lane >> 2, t = lane & 3, g8a = row0 >> 3;
    const int off_qk = g8a * 64 + g * 4 + t, off_v = (row0 + g) * 4 + t;
    #pragma unroll
    for (int jj = 0; jj < NJ; jj++) {
        const int hg = nt * 12 + jj0 + jj;
        const bool isv = hg >= 64;
        const float m = isv ? 1.0f : 8.8817841970012523e-16f;
        uint32_t* base = (uint32_t*)g_QKV + (size_t)hg * 16384 + (isv ? off_v : off_qk);
        const int hs = isv ? 8192 : 32, rs = isv ? 32 : 64;
        base[0] = pack_bf16(acc[8 * jj] * m, acc[8 * jj + 1] * m);
        base[rs] = pack_bf16(acc[8 * jj + 2] * m, acc[8 * jj + 3] * m);
        base[hs] = pack_bf16(acc[8 * jj + 4] * m, acc[8 * jj + 5] * m);
        base[hs + rs] = pack_bf16(acc[8 * jj + 6] * m, acc[8 * jj + 7] * m);
    }
}

__global__ void __launch_bounds__(K1_THREADS, 1)
k1_ln_qkv(const __grid_constant__ CUtensorMap wmap, const __grid_constant__ CUtensorMap xmap, const __nv_bfloat16* __restrict__ w_r) {
    extern __shared__ __align__(1024) unsigned char smem[];
    const uint32_t sA = smem_u32(smem), sB = sA + 131072, sBar = sB + 6 * 16384;
    const int warp = __shfl_sync(~0u, threadIdx.x >> 5, 0), lane = threadIdx.x & 31;
    const int nt = blockIdx.x & 7, mt = blockIdx.x >> 3;
    const int wg = warp >> 2;
    CK(0);
    pdl_launch();
    uint32_t* s_wr = (uint32_t*)(smem + 131072 + 6 * 16384 + 128);
    if (warp == 8) {
        if (lane == 0) {
            for (int i = 0; i < 6; i++) { mbar_init(sBar + i * 8, 1); mbar_init(sBar + 48 + i * 8, 2); }
            mbar_init(sBar + 96, 1); mbar_init(sBar + 104, 1);
            asm volatile("fence.mbarrier_init.release.cluster;" ::: "memory");
            mbar_expect_tx(sBar + 96, 65536); mbar_expect_tx(sBar + 104, 65536);
            for (int i = 0; i < 6; i++) mbar_expect_tx(sBar + i * 8, 16384);
        }
        __syncwarp();
        if (lane < 16) tma_2d(sA + (lane & 7) * 16384 + (lane >> 3) * 8192, &xmap, (lane & 7) * 64, mt * 128 + (lane >> 3) * 64, sBar + 96 + (lane >> 3) * 8);
        named_bar(3, K1_THREADS);
        mbar_wait(sBar + 96, 0);
        if (lane < 12) {
            const int ld = lane >> 1, j = lane & 1;
            tma_2d(sB + ld * 16384 + j * 8192, &wmap, nt * 192 + j * 64, ld * 64, sBar + ld * 8);
        }
        __syncwarp();
        if (lane < 2) {
            for (int ld = 6; ld < 12; ld++) {
                const int sl = ld - 6;
                mbar_wait(sBar + 48 + sl * 8, 0);
                if (lane == 0) mbar_expect_tx(sBar + sl * 8, 16384);
                __syncwarp(3);
                if (ld < 8) tma_2d(sB + sl * 16384 + lane * 8192, &wmap, nt * 192 + lane * 64, ld * 64, sBar + sl * 8);
                else tma_2d(sB + sl * 16384 + lane * 8192, &wmap, nt * 192 + 128, (ld - 8) * 128 + lane * 64, sBar + sl * 8);
            }
        }
        return;
    }
    if (nt == 0) s_wr[threadIdx.x] = __ldg((const uint32_t*)w_r + threadIdx.x);
    named_bar(3, K1_THREADS);
    const int g = lane >> 2, t = lane & 3;
    const int lrow = warp * 16 + (lane & 7) + ((lane >> 3) & 1) * 8;
    const uint32_t lbase = sA + lrow * 128;
    const int lsw = lane & 7, lhi = lane >> 4;
    uint32_t laddr[4];
    #pragma unroll
    for (int k4 = 0; k4 < 4; k4++) laddr[k4] = lbase + (((k4 * 2 + lhi) ^ lsw) * 16);
    CK(1);
    mbar_wait(sBar + 96 + wg * 8, 0);
    CK(2);
    float dsum[4] = {0.f, 0.f, 0.f, 0.f}, dq0[4] = {0.f, 0.f, 0.f, 0.f}, dq1[4] = {0.f, 0.f, 0.f, 0.f};
    float esum[4] = {0.f, 0.f, 0.f, 0.f}, eq0[4] = {0.f, 0.f, 0.f, 0.f}, eq1[4] = {0.f, 0.f, 0.f, 0.f};
    #pragma unroll 2
    for (int pn = 0; pn < 8; pn++) {
        uint32_t a[4][4];
        #pragma unroll
        for (int k4 = 0; k4 < 4; k4++) ldsm4(a[k4], laddr[k4] + pn * 16384);
        #pragma unroll
        for (int k4 = 0; k4 < 4; k4 += 2) {
            mma16816(dsum, a[k4], 0x3F803F80u, 0x3F803F80u);
            mma16816(dq0, a[k4], a[k4][0], a[k4][2]);
            mma16816(dq1, a[k4], a[k4][1], a[k4][3]);
            mma16816(esum, a[k4 + 1], 0x3F803F80u, 0x3F803F80u);
            mma16816(eq0, a[k4 + 1], a[k4 + 1][0], a[k4 + 1][2]);
            mma16816(eq1, a[k4 + 1], a[k4 + 1][1], a[k4 + 1][3]);
        }
    }
    #pragma unroll
    for (int i = 0; i < 4; i++) { dsum[i] += esum[i]; dq0[i] += eq0[i]; dq1[i] += eq1[i]; }
    CK(3);
    const int dsrc = g * 4 + (g >> 1);
    const float sq0 = __shfl_sync(~0u, (g & 1) ? dq0[1] : dq0[0], dsrc), sq1 = __shfl_sync(~0u, (g & 1) ? dq1[3] : dq1[2], dsrc);
    const float mean0 = dsum[0] * (1.0f / D_), mean1 = dsum[2] * (1.0f / D_);
    float var0 = fmaf(-mean0, mean0, sq0 * (1.0f / D_)), var1 = fmaf(-mean1, mean1, sq1 * (1.0f / D_));
    if (__any_sync(~0u, !(mean0 * mean0 <= 16.0f * var0) || !(mean1 * mean1 <= 16.0f * var1))) {
        float q0 = 0.f, q1 = 0.f;
        #pragma unroll 1
        for (int ks = 0; ks < 32; ks++) {
            uint32_t a[4];
            ldsm4(a, lbase + (ks >> 2) * 16384 + ((((ks & 3) * 2 + lhi) ^ lsw) * 16));
            #pragma unroll
            for (int i = 0; i < 4; i++) {
                const float m = (i & 1) ? mean1 : mean0;
                const float d0 = bf_lo(a[i]) - m, d1 = bf_hi(a[i]) - m;
                if (i & 1) q1 = fmaf(d0, d0, fmaf(d1, d1, q1)); else q0 = fmaf(d0, d0, fmaf(d1, d1, q0));
            }
        }
        q0 += __shfl_xor_sync(~0u, q0, 1); q0 += __shfl_xor_sync(~0u, q0, 2);
        q1 += __shfl_xor_sync(~0u, q1, 1); q1 += __shfl_xor_sync(~0u, q1, 2);
        var0 = q0 * (1.0f / D_); var1 = q1 * (1.0f / D_);
    }
    const float rs0 = __frcp_rn(bf16r(__fsqrt_rn(bf16r(bf16r(var0) + 1e-5f))));
    const float rs1 = __frcp_rn(bf16r(__fsqrt_rn(bf16r(bf16r(var1) + 1e-5f))));
    const LnRow lr0 = ln_row(mean0, rs0), lr1 = ln_row(mean1, rs1);
    float acc[64];
    #pragma unroll
    for (int i = 0; i < 64; i++) acc[i] = 0.f;
    float dr[4] = {0.f, 0.f, 0.f, 0.f};
    const uint64_t db0 = make_desc(sB, 8192, 1024, 1);
    #pragma unroll 1
    for (int kc = 0; kc < 8; kc += 2) {
        #pragma unroll
        for (int h2 = 0; h2 < 2; h2++) {
            const int ld = kc + h2, sl = ld < 6 ? ld : ld - 6;
            uint32_t a[4][4];
            #pragma unroll
            for (int k4 = 0; k4 < 4; k4++) ldsm4(a[k4], laddr[k4] + ld * 16384);
            #pragma unroll
            for (int k4 = 0; k4 < 4; k4++) ln_frag(a[k4], lr0, lr1);
            if (nt == 0) {
                #pragma unroll
                for (int k4 = 0; k4 < 4; k4++) mma16816(dr, a[k4], s_wr[(ld * 4 + k4) * 8 + t], s_wr[(ld * 4 + k4) * 8 + 4 + t]);
            }
            mbar_wait(sBar + sl * 8, ld >= 6);
            WG_FENCE();
            #pragma unroll
            for (int k4 = 0; k4 < 4; k4++) wgmma_rs_n128(acc, a[k4], db0 + (uint64_t)(sl * 1024 + k4 * 128));
            WG_COMMIT();
            wg_wait<1>();
            if (ld >= 1 && ld <= 6 && (threadIdx.x & 127) == 0) mbar_arrive(sBar + 48 + (ld - 1) * 8);
        }
    }
    const int row0 = mt * 128 + warp * 16;
    if (nt == 0 && t == 0) {
        g_r[row0 + g] = bf16r(dr[0]); g_r[row0 + g + 8] = bf16r(dr[2]);
        g_stats[row0 + g] = make_float2(bf_lo(lr0.m2), rs0); g_stats[row0 + g + 8] = make_float2(bf_lo(lr1.m2), rs1);
    }
    wg_wait<0>();
    touch64(acc);
    CK(4);
    float acc2[32];
    #pragma unroll
    for (int i = 0; i < 32; i++) acc2[i] = 0.f;
    #pragma unroll 1
    for (int q = 0; q < 4; q++) {
        const int sl = q + 2;
        #pragma unroll
        for (int h2 = 0; h2 < 2; h2++) {
            uint32_t a[4][4];
            #pragma unroll
            for (int k4 = 0; k4 < 4; k4++) ldsm4(a[k4], laddr[k4] + (q * 2 + h2) * 16384);
            #pragma unroll
            for (int k4 = 0; k4 < 4; k4++) ln_frag(a[k4], lr0, lr1);
            if (h2 == 0) mbar_wait(sBar + sl * 8, 1);
            WG_FENCE();
            #pragma unroll
            for (int k4 = 0; k4 < 4; k4++) wgmma_rs_n64(acc2, a[k4], db0 + (uint64_t)(sl * 1024 + (h2 * 4 + k4) * 128));
            WG_COMMIT();
            wg_wait<1>();
        }
        if (q == 0) k1_store<4>(acc, 0, nt, row0, lane);
        if (q == 1) k1_store<4>(acc + 32, 4, nt, row0, lane);
    }
    wg_wait<0>();
    touch32(acc2);
    CK(5);
    k1_store<4>(acc2, 8, nt, row0, lane);
    CK(6);
}

constexpr int K2_THREADS = 512;
constexpr int K2_SMEM = 65536 + 98304 + 16384 + 128;

constexpr float QS = 0.25f * 1.4426950408889634f;
constexpr float SC100 = 1.2676506002282294e30f;
__device__ __forceinline__ uint32_t polyexp2(float s0, float s1, float cd, uint32_t one2, uint32_t ca2) {
    constexpr float A = 128.0f * QS * 1.7763568394002505e-15f;
    float t0, t1;
    asm("fma.rn.f32 %0, %1, %2, %3;" : "=f"(t0) : "f"(s0), "f"(A), "f"(cd));
    asm("fma.rn.f32 %0, %1, %2, %3;" : "=f"(t1) : "f"(s1), "f"(A), "f"(cd));
    uint32_t W, U, h, G;
    asm("cvt.pack.sat.s16.s32 %0, %1, %2;" : "=r"(W) : "r"(__float_as_int(t1)), "r"(__float_as_int(t0)));
    asm("lop3.b32 %0, %1, 0x007F007F, %2, 0xEA;" : "=r"(U) : "r"(W), "r"(one2));
    asm("fma.rn.bf16x2 %0, %1, %2, %3;" : "=r"(h) : "r"(U), "r"(ca2), "r"(0xC300C300u));
    asm("fma.rn.bf16x2 %0, %1, %2, %3;" : "=r"(G) : "r"(h), "r"(U), "r"(0x438B438Bu));
    return W + G - 0x43404340u;
}

struct ExpC { float nm0, nm1, cd0, cd1; uint32_t one2, ca2; };

template <int G>
__device__ __forceinline__ void exp_block(const float* s, uint32_t* p, const ExpC& c) {
    #pragma unroll
    for (int hf = 0; hf < 2; hf++) {
        const float* x = s + hf * 4;
        if ((PMASK >> (G + hf)) & 1) {
            p[hf * 2 + 0] = polyexp2(x[0], x[1], c.cd0, c.one2, c.ca2);
            p[hf * 2 + 1] = polyexp2(x[2], x[3], c.cd1, c.one2, c.ca2);
        } else {
            p[hf * 2 + 0] = pack_bf16(ex2(fmaf(x[0], QS * SC100, c.nm0)), ex2(fmaf(x[1], QS * SC100, c.nm0)));
            p[hf * 2 + 1] = pack_bf16(ex2(fmaf(x[2], QS * SC100, c.nm1)), ex2(fmaf(x[3], QS * SC100, c.nm1)));
        }
    }
}

__device__ __forceinline__ void max16(const float* s, float& mx0, float& mx1) {
    #pragma unroll
    for (int j = 0; j < 4; j++) {
        mx0 = fmaxf(mx0, fmaxf(s[4 * j], s[4 * j + 1]));
        mx1 = fmaxf(mx1, fmaxf(s[4 * j + 2], s[4 * j + 3]));
    }
}

__device__ void moe_cta(int part, unsigned char* smem, const __nv_bfloat16* __restrict__ x, const __nv_bfloat16* __restrict__ w_gate,
                        const __nv_bfloat16* __restrict__ w_up, const __nv_bfloat16* __restrict__ w_down) {
    float* xs = (float*)smem;
    float* red = xs + 1024;
    float* hs = red + 8 * 4 * 448;
    __shared__ float s_v[32];
    __shared__ int s_i[32];
    __shared__ int s_sel[2];
    const int tid = threadIdx.x, warp = tid >> 5, lane = tid & 31;
    for (int pass = 0; pass < 2; pass++) {
        float bv = -INFINITY; int bi = 0x7fffffff;
        const int excl = pass ? s_sel[0] : -1;
        for (int i = tid; i < S_; i += K2_THREADS) {
            float v = g_r[i];
            if (i != excl && (v > bv || (v == bv && i < bi) || bi == 0x7fffffff)) { bv = v; bi = i; }
        }
        #pragma unroll
        for (int o = 16; o; o >>= 1) {
            float ov = __shfl_xor_sync(~0u, bv, o); int oi = __shfl_xor_sync(~0u, bi, o);
            if (ov > bv || (ov == bv && oi < bi)) { bv = ov; bi = oi; }
        }
        if (lane == 0) { s_v[warp] = bv; s_i[warp] = bi; }
        __syncthreads();
        if (warp == 0) {
            bv = lane < 16 ? s_v[lane] : -INFINITY; bi = lane < 16 ? s_i[lane] : 0x7fffffff;
            #pragma unroll
            for (int o = 16; o; o >>= 1) {
                float ov = __shfl_xor_sync(~0u, bv, o); int oi = __shfl_xor_sync(~0u, bi, o);
                if (ov > bv || (ov == bv && oi < bi)) { bv = ov; bi = oi; }
            }
            if (lane == 0) s_sel[pass] = (bi == 0x7fffffff) ? pass : bi;
        }
        __syncthreads();
    }
    for (int i = tid; i < 1024; i += K2_THREADS) {
        const int tok = s_sel[i >> 9];
        const float2 st = g_stats[tok];
        xs[i] = ln_elem(__bfloat162float(x[(size_t)tok * D_ + (i & 511)]), st.x, st.y);
    }
    if (part == 0 && tid < 2) g_sel[tid] = s_sel[tid];
    __syncthreads();
    const int c0 = part * 448;
    if (tid < 448) {
        const int cg = tid % 56, ks = tid / 56;
        float a[4][8];
        #pragma unroll
        for (int i = 0; i < 4; i++)
            #pragma unroll
            for (int j = 0; j < 8; j++) a[i][j] = 0.f;
        const __nv_bfloat16* pg = w_gate + (size_t)(ks * 64) * F_ + c0 + cg * 8;
        const __nv_bfloat16* pu = w_up + (size_t)(ks * 64) * F_ + c0 + cg * 8;
        #pragma unroll 8
        for (int k = 0; k < 64; k++) {
            const uint4 gv = __ldg((const uint4*)(pg + (size_t)k * F_));
            const uint4 uv = __ldg((const uint4*)(pu + (size_t)k * F_));
            const float x0 = xs[ks * 64 + k], x1 = xs[512 + ks * 64 + k];
            const uint32_t gu[4] = {gv.x, gv.y, gv.z, gv.w}, uu[4] = {uv.x, uv.y, uv.z, uv.w};
            #pragma unroll
            for (int j = 0; j < 4; j++) {
                const float g0 = bf_lo(gu[j]), g1 = bf_hi(gu[j]), u0 = bf_lo(uu[j]), u1 = bf_hi(uu[j]);
                a[0][2 * j] = fmaf(x0, g0, a[0][2 * j]); a[0][2 * j + 1] = fmaf(x0, g1, a[0][2 * j + 1]);
                a[1][2 * j] = fmaf(x1, g0, a[1][2 * j]); a[1][2 * j + 1] = fmaf(x1, g1, a[1][2 * j + 1]);
                a[2][2 * j] = fmaf(x0, u0, a[2][2 * j]); a[2][2 * j + 1] = fmaf(x0, u1, a[2][2 * j + 1]);
                a[3][2 * j] = fmaf(x1, u0, a[3][2 * j]); a[3][2 * j + 1] = fmaf(x1, u1, a[3][2 * j + 1]);
            }
        }
        #pragma unroll
        for (int i = 0; i < 4; i++)
            #pragma unroll
            for (int j = 0; j < 8; j++) red[(ks * 4 + i) * 448 + cg * 8 + j] = a[i][j];
    }
    __syncthreads();
    for (int i = tid; i < 896; i += K2_THREADS) {
        const int tok = i / 448, c = i % 448;
        float gs = 0.f, us = 0.f;
        #pragma unroll
        for (int ks = 0; ks < 8; ks++) { gs += red[(ks * 4 + tok) * 448 + c]; us += red[(ks * 4 + 2 + tok) * 448 + c]; }
        gs = bf16r(gs); us = bf16r(us);
        const float sl = bf16r(gs / (1.0f + __expf(-gs)));
        hs[i] = bf16r(sl * us);
    }
    __syncthreads();
    {
        const int cg = tid & 63, fs = tid >> 6;
        float a[2][8];
        #pragma unroll
        for (int j = 0; j < 8; j++) { a[0][j] = 0.f; a[1][j] = 0.f; }
        const __nv_bfloat16* pd = w_down + (size_t)(c0 + fs * 56) * D_ + cg * 8;
        #pragma unroll 8
        for (int f = 0; f < 56; f++) {
            const uint4 dv = __ldg((const uint4*)(pd + (size_t)f * D_));
            const float h0 = hs[fs * 56 + f], h1 = hs[448 + fs * 56 + f];
            const uint32_t du[4] = {dv.x, dv.y, dv.z, dv.w};
            #pragma unroll
            for (int j = 0; j < 4; j++) {
                const float d0 = bf_lo(du[j]), d1 = bf_hi(du[j]);
                a[0][2 * j] = fmaf(h0, d0, a[0][2 * j]); a[0][2 * j + 1] = fmaf(h0, d1, a[0][2 * j + 1]);
                a[1][2 * j] = fmaf(h1, d0, a[1][2 * j]); a[1][2 * j + 1] = fmaf(h1, d1, a[1][2 * j + 1]);
            }
        }
        #pragma unroll
        for (int j = 0; j < 8; j++) { red[(fs * 2) * 512 + cg * 8 + j] = a[0][j]; red[(fs * 2 + 1) * 512 + cg * 8 + j] = a[1][j]; }
    }
    __syncthreads();
    for (int i = tid; i < 1024; i += K2_THREADS) {
        float s = 0.f;
        #pragma unroll
        for (int fs = 0; fs < 8; fs++) s += red[(fs * 2 + (i >> 9)) * 512 + (i & 511)];
        g_ypart[part][i >> 9][i & 511] = s;
    }
}

__global__ void __launch_bounds__(K2_THREADS, 1)
k2_attn(const __nv_bfloat16* __restrict__ x, const __nv_bfloat16* __restrict__ w_gate, const __nv_bfloat16* __restrict__ w_up,
        const __nv_bfloat16* __restrict__ w_down) {
    extern __shared__ __align__(1024) unsigned char smem[];
    TL(1, 0);
    pdl_launch();
    if (blockIdx.x >= 128) {
        const int part = blockIdx.x - 128;
        {
            const int k = threadIdx.x;
            asm volatile("cp.async.bulk.prefetch.L2.global [%0], %1;" :: "l"(w_gate + (size_t)k * F_ + part * 448), "r"(896) : "memory");
            asm volatile("cp.async.bulk.prefetch.L2.global [%0], %1;" :: "l"(w_up + (size_t)k * F_ + part * 448), "r"(896) : "memory");
            if (k < 56) asm volatile("cp.async.bulk.prefetch.L2.global [%0], %1;" :: "l"(w_down + (size_t)(part * 448 + k * 8) * D_), "r"(8192) : "memory");
        }
        pdl_wait(); TL(1, 1); moe_cta(blockIdx.x - 128, smem, x, w_gate, w_up, w_down); TL(1, 2); return; }
    const uint32_t sK = smem_u32(smem), sV = sK + 65536, sQ = sV + 98304, sBar = sQ + 16384;
    const int h = blockIdx.x >> 2, qb = blockIdx.x & 3;
    const int warp = __shfl_sync(~0u, threadIdx.x >> 5, 0), lane = threadIdx.x & 31, wg = warp >> 2;
    if (threadIdx.x == 0) {
        mbar_init(sBar, 1); mbar_init(sBar + 8, 1);
        asm volatile("fence.mbarrier_init.release.cluster;" ::: "memory");
        mbar_expect_tx(sBar, 16384 + 16384 + 2 * 8192);
        mbar_expect_tx(sBar + 8, 49152 + 2 * 24576);
    }
    for (int i = threadIdx.x; i < 2048; i += K2_THREADS)
        *(uint4*)(smem + 65536 + 65536 + i * 16) = make_uint4(0x3F803F80u, 0x3F803F80u, 0x3F803F80u, 0x3F803F80u);
    fence_async_smem();
    __syncthreads();
    if (warp == 0) {
        pdl_wait();
        TL(1, 1);
        const uint4* gk = g_K + (size_t)h * 4096;
        const uint4* gv = g_V + (size_t)h * 4096;
        if (lane == 0) bulk_g2s(sQ, g_Q + (size_t)h * 4096 + qb * 1024, 16384, sBar);
        if (lane == 1) bulk_g2s(sK, gk, 16384, sBar);
        if (lane == 2) bulk_g2s(sV, gv, 8192, sBar);
        if (lane == 3) bulk_g2s(sV + 32768, gv + 2048, 8192, sBar);
        if (lane == 4) bulk_g2s(sK + 16384, gk + 1024, 49152, sBar + 8);
        if (lane == 5) bulk_g2s(sV + 8192, gv + 512, 24576, sBar + 8);
        if (lane == 6) bulk_g2s(sV + 32768 + 8192, gv + 2048 + 512, 24576, sBar + 8);
        __syncwarp();
    }
    ExpC c;
    {
        const volatile uint32_t* cc = g_const;
        c.one2 = cc[0]; c.ca2 = cc[1];
    }
    const uint32_t kdesc0 = (uint32_t)make_desc(sK, 128, 256, 0);
    const uint32_t vdesc0 = (uint32_t)make_desc(sV, 128, 32768, 0);
    #pragma unroll 1
    for (int pass = 0; pass < 2; pass++) {
        const bool dry = false;
        if (pass == 0) { mbar_wait(sBar, 0); __syncwarp(); TL(1, 2); }
        const int unit = (pass & 1) * 4 + wg;
        const uint32_t q = (uint32_t)make_desc(sQ + unit * 2048, 128, 256, 0);
        float o[12];
        #pragma unroll 1
        for (int attempt = 0; attempt < 2; attempt++) {
            float s0[16], s1[16], s2[16];
            #pragma unroll
            for (int i = 0; i < 16; i++) { s0[i] = 0.f; s1[i] = 0.f; s2[i] = 0.f; }
            float mx0 = -INFINITY, mx1 = -INFINITY;
            if (attempt) {
                #pragma unroll 1
                for (int it = 0; it < 64; it++) {
                    WG_FENCE();
                    wgmma_qk32(s0, q, kdesc0 + it * 64);
                    WG_COMMIT();
                    wg_wait<0>();
                    touch16(s0);
                    max16(s0, mx0, mx1);
                }
            }
            #pragma unroll
            for (int i = 0; i < 12; i++) o[i] = 0.f;
            WG_FENCE();
            wgmma_qk32(s2, q, kdesc0);
            wgmma_qk32(s0, q, kdesc0 + 64);
            wgmma_qk32(s1, q, kdesc0 + 128);
            WG_COMMIT();
            wg_wait<0>();
            touch16(s0); touch16(s1); touch16(s2);
            max16(s0, mx0, mx1); max16(s1, mx0, mx1); max16(s2, mx0, mx1);
            mx0 = fmaxf(mx0, __shfl_xor_sync(~0u, mx0, 1)); mx0 = fmaxf(mx0, __shfl_xor_sync(~0u, mx0, 2));
            mx1 = fmaxf(mx1, __shfl_xor_sync(~0u, mx1, 1)); mx1 = fmaxf(mx1, __shfl_xor_sync(~0u, mx1, 2));
            const float bias = attempt ? 0.0f : 128.0f * 64.0f;
            const float y0 = ceilf(fmaf(mx0, 128.0f * QS * SC100, bias)), y1 = ceilf(fmaf(mx1, 128.0f * QS * SC100, bias));
            c.nm0 = __shfl_sync(~0u, y0 * (-1.0f / 128.0f), lane); c.nm1 = __shfl_sync(~0u, y1 * (-1.0f / 128.0f), lane);
            c.cd0 = __shfl_sync(~0u, __fmul_rn(16256.0f - y0, __int_as_float(1)), lane);
            c.cd1 = __shfl_sync(~0u, __fmul_rn(16256.0f - y1, __int_as_float(1)), lane);
            uint32_t kd = kdesc0 + 192, vd = vdesc0 + 32;
            {
                uint32_t pa[4], pb[4];
                exp_block<12>(s2, pa, c);
                exp_block<14>(s2 + 8, pb, c);
                WG_FENCE();
                wgmma_pv(o, pa, vdesc0); wgmma_pv(o, pb, vdesc0 + 16);
                WG_COMMIT();
            }
            #pragma unroll 1
            for (int seg = 0; seg < (dry ? 1 : 2); seg++) {
            if (seg) { wg_wait<0>(); mbar_wait(sBar + 8, 0); __syncwarp(); }
            #pragma unroll 1
            for (int it = seg ? 3 : (dry ? 2 : 0); it < (seg ? 21 : 3); it++) {
                uint32_t p[6][4];
                WG_FENCE();
                wgmma_qk32(s2, q, kd);
                WG_COMMIT();
                exp_block<0>(s0, p[0], c);
                exp_block<2>(s0 + 8, p[1], c);
                WG_FENCE();
                wgmma_pv(o, p[0], vd); wgmma_pv(o, p[1], vd + 16);
                wgmma_qk32(s0, q, kd + 64);
                WG_COMMIT();
                wg_wait<1>();
                touch16(s2);
                exp_block<4>(s1, p[2], c);
                exp_block<6>(s1 + 8, p[3], c);
                WG_FENCE();
                wgmma_pv(o, p[2], vd + 32); wgmma_pv(o, p[3], vd + 48);
                wgmma_qk32(s1, q, kd + 128);
                WG_COMMIT();
                wg_wait<1>();
                touch16(s0);
                exp_block<8>(s2, p[4], c);
                exp_block<10>(s2 + 8, p[5], c);
                WG_FENCE();
                wgmma_pv(o, p[4], vd + 64); wgmma_pv(o, p[5], vd + 80);
                WG_COMMIT();
                vd += 96; kd += 192;
                wg_wait<1>();
                touch16(s1);
            }
            }
            wg_wait<0>();
            touch12(o);
            if (attempt) break;
            float big = 0.f;
            #pragma unroll
            for (int i = 0; i < 12; i++) big = fmaxf(big, fabsf(o[i]));
            bool bad = !(big < 1e30f);
            #pragma unroll
            for (int i = 0; i < 12; i++) bad |= (o[i] != o[i]);
            uint32_t any;
            asm volatile("{.reg .pred p, q; setp.ne.u32 p, %1, 0; barrier.cta.red.or.pred.aligned q, %2, 128, p; selp.u32 %0, 1, 0, q;}"
                         : "=r"(any) : "r"((uint32_t)bad), "r"(1 + wg) : "memory");
            if (dry || !__any_sync(~0u, any)) break;
        }
        const int g = lane >> 2, t = lane & 3;
        const int r = (warp & 3) * 16 + g;
        const float i0 = __fdiv_rn(1.0f, o[8]), i1 = __fdiv_rn(1.0f, o[10]);
        uint32_t* ob = (uint32_t*)(g_O + (size_t)(qb * 8 + unit) * 4096 + (h >> 2) * 512 + r * 8) + t;
        const int c0 = ((h & 3) * 2) ^ (r & 7), c1 = ((h & 3) * 2 + 1) ^ (r & 7);
        if (!dry) {
            ob[c0 * 4] = pack_bf16(o[0] * i0, o[1] * i0);
            ob[c1 * 4] = pack_bf16(o[4] * i0, o[5] * i0);
            ob[256 + c0 * 4] = pack_bf16(o[2] * i1, o[3] * i1);
            ob[256 + c1 * 4] = pack_bf16(o[6] * i1, o[7] * i1);
            TL(1, 3 + pass);
        }
    }
}

constexpr int K3_THREADS = 256;
constexpr int K3_SMEM = 65536 + 131072 + 128;

__global__ void __launch_bounds__(K3_THREADS, 1)
k3_out(const __grid_constant__ CUtensorMap wmap, const __nv_bfloat16* __restrict__ x, __nv_bfloat16* __restrict__ out) {
    extern __shared__ __align__(1024) unsigned char smem[];
    const uint32_t sA = smem_u32(smem), sB = sA + 65536, sBar = sB + 131072;
    const int warp = __shfl_sync(~0u, threadIdx.x >> 5, 0), lane = threadIdx.x & 31, wg = warp >> 2;
    const int nt = blockIdx.x & 3, mt = blockIdx.x >> 2;
    TL(2, 0);
    if (threadIdx.x == 0) {
        for (int i = 0; i < 6; i++) mbar_init(sBar + i * 8, 1);
        asm volatile("fence.mbarrier_init.release.cluster;" ::: "memory");
        for (int kh = 0; kh < 2; kh++) {
            mbar_expect_tx(sBar + kh * 8, 65536);
            tma_2d(sB + kh * 32768, &wmap, nt * 128, kh * 256, sBar + kh * 8);
            tma_2d(sB + 65536 + kh * 32768, &wmap, nt * 128 + 64, kh * 256, sBar + kh * 8);
        }
    }
    const int er = threadIdx.x >> 2, ec = (threadIdx.x & 3) * 32;
    const int row = mt * 64 + er;
    uint4 xv[4];
    #pragma unroll
    for (int j = 0; j < 4; j++) xv[j] = __ldg((const uint4*)(x + (size_t)row * D_ + nt * 128 + ec) + j);
    pdl_wait();
    TL(2, 1);
    if (threadIdx.x == 0) {
        for (int q = 0; q < 4; q++) {
            mbar_expect_tx(sBar + 16 + q * 8, 16384);
            bulk_g2s(sA + q * 16384, g_O + (size_t)mt * 4096 + q * 1024, 16384, sBar + 16 + q * 8);
        }
    }
    const int sel0 = g_sel[0], sel1 = g_sel[1];
    const float2 st = g_stats[row];
    uint32_t bb[16];
    {
        const uint32_t xu[16] = {xv[0].x, xv[0].y, xv[0].z, xv[0].w, xv[1].x, xv[1].y, xv[1].z, xv[1].w,
                                 xv[2].x, xv[2].y, xv[2].z, xv[2].w, xv[3].x, xv[3].y, xv[3].z, xv[3].w};
        #pragma unroll
        for (int j = 0; j < 16; j++) bb[j] = pack_bf16(bf16r(bf_lo(xu[j]) - st.x) * st.y, bf16r(bf_hi(xu[j]) - st.x) * st.y);
        const int slot = row == sel0 ? 0 : (row == sel1 ? 1 : -1);
        if (slot >= 0) {
            const float gate = bf16r(1.0f / (1.0f + __expf(-g_r[row])));
            const int c0 = nt * 128 + ec;
            #pragma unroll
            for (int j = 0; j < 16; j++) {
                const float2 a = *(const float2*)&g_ypart[0][slot][c0 + 2 * j], b = *(const float2*)&g_ypart[1][slot][c0 + 2 * j];
                const float2 c = *(const float2*)&g_ypart[2][slot][c0 + 2 * j], d = *(const float2*)&g_ypart[3][slot][c0 + 2 * j];
                bb[j] = pack_bf16(bf_lo(bb[j]) + bf16r(bf16r(a.x + b.x + c.x + d.x) * gate), bf_hi(bb[j]) + bf16r(bf16r(a.y + b.y + c.y + d.y) * gate));
            }
        }
    }
    __syncthreads();
    float acc[32];
    #pragma unroll
    for (int i = 0; i < 32; i++) acc[i] = 0.f;
    const uint64_t da0 = make_desc(sA, 16, 1024, 1);
    const uint64_t db0 = make_desc(sB + wg * 65536, 8192, 1024, 1);
    #pragma unroll 1
    for (int q = 0; q < 4; q++) {
        if ((q & 1) == 0) mbar_wait(sBar + (q >> 1) * 8, 0);
        mbar_wait(sBar + 16 + q * 8, 0);
        WG_FENCE();
        #pragma unroll
        for (int kk = 0; kk < 8; kk++)
            wgmma_n64(acc, da0 + (uint64_t)(q * 1024 + (kk >> 2) * 512 + (kk & 3) * 2), db0 + (uint64_t)(q * 1024 + kk * 128));
        WG_COMMIT();
    }
    wg_wait<0>();
    touch32(acc);
    TL(2, 2);
    __syncthreads();
    {
        const int g = lane >> 2, t = lane & 3;
        unsigned char* sp = smem + ((warp & 3) * 16 + g) * 272 + wg * 128 + t * 4;
        #pragma unroll
        for (int j = 0; j < 8; j++) {
            *(uint32_t*)(sp + j * 16) = pack_bf16(acc[4 * j], acc[4 * j + 1]);
            *(uint32_t*)(sp + 8 * 272 + j * 16) = pack_bf16(acc[4 * j + 2], acc[4 * j + 3]);
        }
    }
    __syncthreads();
    #pragma unroll
    for (int j = 0; j < 4; j++) {
        const uint4 av = *(const uint4*)(smem + er * 272 + ec * 2 + j * 16);
        const uint32_t au[4] = {av.x, av.y, av.z, av.w}, xu[4] = {xv[j].x, xv[j].y, xv[j].z, xv[j].w};
        uint32_t o[4];
        #pragma unroll
        for (int i = 0; i < 4; i++) {
            uint32_t t2;
            asm("add.rn.bf16x2 %0, %1, %2;" : "=r"(t2) : "r"(xu[i]), "r"(au[i]));
            asm("add.rn.bf16x2 %0, %1, %2;" : "=r"(o[i]) : "r"(t2), "r"(bb[j * 4 + i]));
        }
        *((uint4*)(out + (size_t)row * D_ + nt * 128 + ec) + j) = make_uint4(o[0], o[1], o[2], o[3]);
    }
    TL(2, 3);
}

typedef CUresult (*EncodeFn)(CUtensorMap*, CUtensorMapDataType, cuuint32_t, void*, const cuuint64_t*, const cuuint64_t*,
                             const cuuint32_t*, const cuuint32_t*, CUtensorMapInterleave, CUtensorMapSwizzle,
                             CUtensorMapL2promotion, CUtensorMapFloatOOBfill);

void make_wmap(EncodeFn fn, CUtensorMap* map, const void* ptr, int rows, int cols, int box_rows) {
    cuuint64_t dims[2] = {(cuuint64_t)cols, (cuuint64_t)rows};
    cuuint64_t strides[1] = {(cuuint64_t)cols * 2};
    cuuint32_t box[2] = {64, (cuuint32_t)box_rows};
    cuuint32_t es[2] = {1, 1};
    fn(map, CU_TENSOR_MAP_DATA_TYPE_BFLOAT16, 2, (void*)ptr, dims, strides, box, es, CU_TENSOR_MAP_INTERLEAVE_NONE,
       CU_TENSOR_MAP_SWIZZLE_128B, CU_TENSOR_MAP_L2_PROMOTION_L2_256B, CU_TENSOR_MAP_FLOAT_OOB_FILL_NONE);
}

}

extern "C" void kernel_launch(void* const* d_in, const int* in_sizes, int n_in, void* d_out, int out_size) {
    const __nv_bfloat16* x = (const __nv_bfloat16*)d_in[0];
    const __nv_bfloat16* wqkv = (const __nv_bfloat16*)d_in[1];
    const __nv_bfloat16* wo = (const __nv_bfloat16*)d_in[2];
    const __nv_bfloat16* w_r = (const __nv_bfloat16*)d_in[4];
    const __nv_bfloat16* w_gate = (const __nv_bfloat16*)d_in[5];
    const __nv_bfloat16* w_up = (const __nv_bfloat16*)d_in[6];
    const __nv_bfloat16* w_down = (const __nv_bfloat16*)d_in[7];
    __nv_bfloat16* out = (__nv_bfloat16*)d_out;

    static EncodeFn encode = nullptr;
    if (!encode) {
        void* fn = nullptr;
        cudaDriverEntryPointQueryResult qres;
        cudaGetDriverEntryPoint("cuTensorMapEncodeTiled", &fn, cudaEnableDefault, &qres);
        encode = (EncodeFn)fn;
        cudaFuncSetAttribute(k1_ln_qkv, cudaFuncAttributeMaxDynamicSharedMemorySize, K1_SMEM);
        cudaFuncSetAttribute(k2_attn, cudaFuncAttributeMaxDynamicSharedMemorySize, K2_SMEM);
        cudaFuncSetAttribute(k3_out, cudaFuncAttributeMaxDynamicSharedMemorySize, K3_SMEM);
    }
    CUtensorMap map_qkv, map_wo, map_x;
    make_wmap(encode, &map_x, x, S_, D_, 64);
    make_wmap(encode, &map_qkv, wqkv, D_, 3 * D_, 64);
    make_wmap(encode, &map_wo, wo, D_, D_, 256);

    k1_ln_qkv<<<128, K1_THREADS, K1_SMEM, cudaStreamPerThread>>>(map_qkv, map_x, w_r);
    cudaLaunchAttribute at[1];
    at[0].id = cudaLaunchAttributeProgrammaticStreamSerialization;
    at[0].val.programmaticStreamSerializationAllowed = 1;
    cudaLaunchConfig_t cfg = {};
    cfg.stream = cudaStreamPerThread;
    cfg.attrs = at; cfg.numAttrs = 1;
    cfg.gridDim = dim3(132); cfg.blockDim = dim3(K2_THREADS); cfg.dynamicSmemBytes = K2_SMEM;
    cudaLaunchKernelEx(&cfg, k2_attn, x, w_gate, w_up, w_down);
    cfg.gridDim = dim3(128); cfg.blockDim = dim3(K3_THREADS); cfg.dynamicSmemBytes = K3_SMEM;
    cudaLaunchKernelEx(&cfg, k3_out, map_wo, x, out);
}
```

```cpp
#include <cuda_runtime.h>
#include <cuda_bf16.h>
#include <cuda.h>
#include <stdint.h>

namespace {

constexpr int S_ = 2048, D_ = 512, H_ = 32, F_ = 1792;

constexpr uint32_t PMASK = 0xDB6;

__device__ __align__(1024) uint4 g_QKV[3 * H_ * S_ * 2];
#define g_Q (g_QKV)
#define g_K (g_QKV + H_ * S_ * 2)
#define g_V (g_QKV + 2 * H_ * S_ * 2)
__device__ __align__(1024) uint4 g_O[S_ * D_ / 8];
__device__ float2 g_stats[S_];
__device__ uint32_t g_const[2] = {0x3F803F80u, 0x42294229u};
__device__ float g_r[S_];
__device__ __align__(16) float g_ypart[4][2][D_];
__device__ int g_sel[2];

#define TL(k, p)
#define CK(i)
__device__ __forceinline__ uint32_t smem_u32(const void* p) { return (uint32_t)__cvta_generic_to_shared(p); }
__device__ __forceinline__ float bf16r(float x) { return __bfloat162float(__float2bfloat16_rn(x)); }
__device__ __forceinline__ uint32_t pack_bf16(float lo, float hi) {
    uint32_t r; asm("cvt.rn.bf16x2.f32 %0, %1, %2;" : "=r"(r) : "f"(hi), "f"(lo)); return r;
}
__device__ __forceinline__ float bf_lo(uint32_t u) { return __uint_as_float(u << 16); }
__device__ __forceinline__ float bf_hi(uint32_t u) { return __uint_as_float(u & 0xFFFF0000u); }
__device__ __forceinline__ float ex2(float x) { float y; asm("ex2.approx.ftz.f32 %0, %1;" : "=f"(y) : "f"(x)); return y; }

__device__ __forceinline__ void mbar_init(uint32_t bar, uint32_t count) {
    asm volatile("mbarrier.init.shared::cta.b64 [%0], %1;" :: "r"(bar), "r"(count) : "memory");
}
__device__ __forceinline__ void mbar_expect_tx(uint32_t bar, uint32_t bytes) {
    asm volatile("mbarrier.arrive.expect_tx.shared::cta.b64 _, [%0], %1;" :: "r"(bar), "r"(bytes) : "memory");
}
__device__ __forceinline__ void mbar_arrive(uint32_t bar) {
    asm volatile("mbarrier.arrive.shared::cta.b64 _, [%0];" :: "r"(bar) : "memory");
}
__device__ __forceinline__ void mbar_wait(uint32_t bar, uint32_t parity) {
    uint32_t done;
    #pragma unroll 1
    for (int it = 0; it < (1 << 26); it++) {
        asm volatile("{.reg .pred p; mbarrier.try_wait.parity.shared::cta.b64 p, [%1], %2; selp.u32 %0, 1, 0, p;}"
                     : "=r"(done) : "r"(bar), "r"(parity) : "memory");
        if (done) return;
    }
    __trap();
}
__device__ __forceinline__ void bulk_g2s(uint32_t dst, const void* src, uint32_t bytes, uint32_t bar) {
    asm volatile("cp.async.bulk.shared::cluster.global.mbarrier::complete_tx::bytes [%0], [%1], %2, [%3];"
                 :: "r"(dst), "l"(src), "r"(bytes), "r"(bar) : "memory");
}
__device__ __forceinline__ void tma_2d(uint32_t dst, const CUtensorMap* map, int c0, int c1, uint32_t bar) {
    asm volatile("cp.async.bulk.tensor.2d.shared::cluster.global.mbarrier::complete_tx::bytes [%0], [%1, {%3, %4}], [%2];"
                 :: "r"(dst), "l"(map), "r"(bar), "r"(c0), "r"(c1) : "memory");
}
__device__ __forceinline__ void fence_async_smem() { asm volatile("fence.proxy.async.shared::cta;" ::: "memory"); }
__device__ __forceinline__ void named_bar(int id, int n) { asm volatile("bar.sync %0, %1;" :: "r"(id), "r"(n) : "memory"); }

__device__ __forceinline__ uint64_t make_desc(uint32_t saddr, uint32_t lbo, uint32_t sbo, uint32_t swz) {
    return (uint64_t)((saddr & 0x3FFFF) >> 4) | ((uint64_t)(lbo >> 4) << 16) | ((uint64_t)(sbo >> 4) << 32) | ((uint64_t)swz << 62);
}
#define WG_FENCE() asm volatile("wgmma.fence.sync.aligned;" ::: "memory")
#define WG_COMMIT() asm volatile("wgmma.commit_group.sync.aligned;" ::: "memory")
template <int N> __device__ __forceinline__ void wg_wait() { asm volatile("wgmma.wait_group.sync.aligned %0;" :: "n"(N) : "memory"); }

#define F4(d, o) "+f"(d[o]), "+f"(d[o + 1]), "+f"(d[o + 2]), "+f"(d[o + 3])
#define F16(d, o) F4(d, o), F4(d, o + 4), F4(d, o + 8), F4(d, o + 12)
#define F32(d, o) F16(d, o), F16(d, o + 16)

__device__ __forceinline__ void wgmma_rs_n128(float* d, const uint32_t* a, uint64_t db) {
    asm volatile("wgmma.mma_async.sync.aligned.m64n128k16.f32.bf16.bf16 "
        "{%0,%1,%2,%3,%4,%5,%6,%7,%8,%9,%10,%11,%12,%13,%14,%15,%16,%17,%18,%19,%20,%21,%22,%23,%24,%25,%26,%27,%28,%29,%30,%31,"
        "%32,%33,%34,%35,%36,%37,%38,%39,%40,%41,%42,%43,%44,%45,%46,%47,%48,%49,%50,%51,%52,%53,%54,%55,%56,%57,%58,%59,%60,%61,%62,%63}, "
        "{%64,%65,%66,%67}, %68, 1, 1, 1, 1;\n"
        : F32(d, 0), F32(d, 32) : "r"(a[0]), "r"(a[1]), "r"(a[2]), "r"(a[3]), "l"(db));
}
__device__ __forceinline__ void wgmma_rs_n64(float* d, const uint32_t* a, uint64_t db) {
    asm volatile("wgmma.mma_async.sync.aligned.m64n64k16.f32.bf16.bf16 "
        "{%0,%1,%2,%3,%4,%5,%6,%7,%8,%9,%10,%11,%12,%13,%14,%15,%16,%17,%18,%19,%20,%21,%22,%23,%24,%25,%26,%27,%28,%29,%30,%31}, "
        "{%32,%33,%34,%35}, %36, 1, 1, 1, 1;\n"
        : F32(d, 0) : "r"(a[0]), "r"(a[1]), "r"(a[2]), "r"(a[3]), "l"(db));
}
__device__ __forceinline__ void wgmma_n64(float* d, uint64_t da, uint64_t db) {
    asm volatile("wgmma.mma_async.sync.aligned.m64n64k16.f32.bf16.bf16 "
        "{%0,%1,%2,%3,%4,%5,%6,%7,%8,%9,%10,%11,%12,%13,%14,%15,%16,%17,%18,%19,%20,%21,%22,%23,%24,%25,%26,%27,%28,%29,%30,%31}, "
        "%32, %33, 1, 1, 1, 0, 1;\n"
        : F32(d, 0) : "l"(da), "l"(db));
}
__device__ __forceinline__ void wgmma_qk32(float* d, uint32_t qd, uint32_t kd) {
    asm volatile("{.reg .b64 a, b; mov.b64 a, {%16, 16}; mov.b64 b, {%17, 16};\n"
        "wgmma.mma_async.sync.aligned.m64n32k16.f32.bf16.bf16 {%0,%1,%2,%3,%4,%5,%6,%7,%8,%9,%10,%11,%12,%13,%14,%15}, a, b, 0, 1, 1, 0, 0;}\n"
        : F16(d, 0) : "r"(qd), "r"(kd));
}
__device__ __forceinline__ void wgmma_pv(float* d, const uint32_t* a, uint32_t vd) {
    asm volatile("{.reg .b64 b; mov.b64 b, {%16, 2048};\n"
        "wgmma.mma_async.sync.aligned.m64n24k16.f32.bf16.bf16 {%0,%1,%2,%3,%4,%5,%6,%7,%8,%9,%10,%11}, {%12,%13,%14,%15}, b, 1, 1, 1, 1;}\n"
        : F4(d, 0), F4(d, 4), F4(d, 8) : "r"(a[0]), "r"(a[1]), "r"(a[2]), "r"(a[3]), "r"(vd));
}
__device__ __forceinline__ void touch16(float* d) { asm volatile("" : F16(d, 0) :: "memory"); }
__device__ __forceinline__ void touch12(float* d) { asm volatile("" : F4(d, 0), F4(d, 4), F4(d, 8) :: "memory"); }
__device__ __forceinline__ void touch32(float* d) { asm volatile("" : F32(d, 0) :: "memory"); }
__device__ __forceinline__ void touch64(float* d) { asm volatile("" : F32(d, 0), F32(d, 32) :: "memory"); }

__device__ __forceinline__ float ln_elem(float x, float mean_b, float rden) {
    return bf16r(bf16r(x - mean_b) * rden);
}
__device__ __forceinline__ void pdl_wait() { asm volatile("griddepcontrol.wait;" ::: "memory"); }
__device__ __forceinline__ void pdl_launch() { asm volatile("griddepcontrol.launch_dependents;" ::: "memory"); }
__device__ __forceinline__ void cluster_arrive() { asm volatile("barrier.cluster.arrive.release.aligned;" ::: "memory"); }
__device__ __forceinline__ void cluster_wait() { asm volatile("barrier.cluster.wait.acquire.aligned;" ::: "memory"); }

constexpr int K1_THREADS = 288;
constexpr int K1_SMEM = 131072 + 6 * 16384 + 128 + 1024;

__device__ __forceinline__ void ldsm4(uint32_t* r, uint32_t addr) {
    asm volatile("ldmatrix.sync.aligned.m8n8.x4.shared.b16 {%0, %1, %2, %3}, [%4];" : "=r"(r[0]), "=r"(r[1]), "=r"(r[2]), "=r"(r[3]) : "r"(addr) : "memory");
}
__device__ __forceinline__ void stsm4(uint32_t addr, uint32_t r0, uint32_t r1, uint32_t r2, uint32_t r3) {
    asm volatile("stmatrix.sync.aligned.m8n8.x4.shared.b16 [%0], {%1, %2, %3, %4};" :: "r"(addr), "r"(r0), "r"(r1), "r"(r2), "r"(r3) : "memory");
}
__device__ __forceinline__ void mma16816(float* d, const uint32_t* a, uint32_t b0, uint32_t b1) {
    asm("mma.sync.aligned.m16n8k16.row.col.f32.bf16.bf16.f32 {%0,%1,%2,%3}, {%4,%5,%6,%7}, {%8,%9}, {%0,%1,%2,%3};"
        : "+f"(d[0]), "+f"(d[1]), "+f"(d[2]), "+f"(d[3]) : "r"(a[0]), "r"(a[1]), "r"(a[2]), "r"(a[3]), "r"(b0), "r"(b1));
}
__device__ __forceinline__ uint32_t sub_bf16x2(uint32_t a, uint32_t b) {
    uint32_t d; asm("sub.rn.bf16x2 %0, %1, %2;" : "=r"(d) : "r"(a), "r"(b)); return d;
}
__device__ __forceinline__ uint32_t ln_pair(uint32_t x2, uint32_t mean2, uint32_t rhi2, uint32_t rlo2) {
    const uint32_t d = sub_bf16x2(x2, mean2);
    uint32_t t, y;
    asm("mul.rn.bf16x2 %0, %1, %2;" : "=r"(t) : "r"(d), "r"(rlo2));
    asm("fma.rn.bf16x2 %0, %1, %2, %3;" : "=r"(y) : "r"(d), "r"(rhi2), "r"(t));
    return y;
}
struct LnRow { uint32_t m2, hi2, lo2; };
__device__ __forceinline__ LnRow ln_row(float mean, float rden) {
    LnRow r;
    r.m2 = pack_bf16(mean, mean);
    r.hi2 = pack_bf16(rden, rden);
    const float lo = rden - bf_lo(r.hi2);
    r.lo2 = pack_bf16(lo, lo);
    return r;
}
__device__ __forceinline__ void ln_frag(uint32_t* a, const LnRow& r0, const LnRow& r1) {
    a[0] = ln_pair(a[0], r0.m2, r0.hi2, r0.lo2); a[1] = ln_pair(a[1], r1.m2, r1.hi2, r1.lo2);
    a[2] = ln_pair(a[2], r0.m2, r0.hi2, r0.lo2); a[3] = ln_pair(a[3], r1.m2, r1.hi2, r1.lo2);
}

template <int NJ>
__device__ __forceinline__ void k1_store(const float* acc, int jj0, int nt, int row0, int lane) {
    const int g = lane >> 2, t = lane & 3, g8a = row0 >> 3;
    const int off_qk = g8a * 64 + g * 4 + t, off_v = (row0 + g) * 4 + t;
    #pragma unroll
    for (int jj = 0; jj < NJ; jj++) {
        const int hg = nt * 12 + jj0 + jj;
        const bool isv = hg >= 64;
        const float m = isv ? 1.0f : 8.8817841970012523e-16f;
        uint32_t* base = (uint32_t*)g_QKV + (size_t)hg * 16384 + (isv ? off_v : off_qk);
        const int hs = isv ? 8192 : 32, rs = isv ? 32 : 64;
        base[0] = pack_bf16(acc[8 * jj] * m, acc[8 * jj + 1] * m);
        base[rs] = pack_bf16(acc[8 * jj + 2] * m, acc[8 * jj + 3] * m);
        base[hs] = pack_bf16(acc[8 * jj + 4] * m, acc[8 * jj + 5] * m);
        base[hs + rs] = pack_bf16(acc[8 * jj + 6] * m, acc[8 * jj + 7] * m);
    }
}

__global__ void __launch_bounds__(K1_THREADS, 1)
k1_ln_qkv(const __grid_constant__ CUtensorMap wmap, const __grid_constant__ CUtensorMap xmap, const __nv_bfloat16* __restrict__ w_r) {
    extern __shared__ __align__(1024) unsigned char smem[];
    const uint32_t sA = smem_u32(smem), sB = sA + 131072, sBar = sB + 6 * 16384;
    const int warp = __shfl_sync(~0u, threadIdx.x >> 5, 0), lane = threadIdx.x & 31;
    const int nt = blockIdx.x & 7, mt = blockIdx.x >> 3;
    const int wg = warp >> 2;
    CK(0);
    pdl_launch();
    uint32_t* s_wr = (uint32_t*)(smem + 131072 + 6 * 16384 + 128);
    if (warp == 8) {
        if (lane == 0) {
            for (int i = 0; i < 6; i++) { mbar_init(sBar + i * 8, 1); mbar_init(sBar + 48 + i * 8, 2); }
            mbar_init(sBar + 96, 1); mbar_init(sBar + 104, 1);
            asm volatile("fence.mbarrier_init.release.cluster;" ::: "memory");
            mbar_expect_tx(sBar + 96, 65536); mbar_expect_tx(sBar + 104, 65536);
            for (int i = 0; i < 6; i++) mbar_expect_tx(sBar + i * 8, 16384);
        }
        __syncwarp();
        if (lane < 16) tma_2d(sA + (lane & 7) * 16384 + (lane >> 3) * 8192, &xmap, (lane & 7) * 64, mt * 128 + (lane >> 3) * 64, sBar + 96 + (lane >> 3) * 8);
        named_bar(3, K1_THREADS);
        mbar_wait(sBar + 96, 0);
        if (lane < 12) {
            const int ld = lane >> 1, j = lane & 1;
            tma_2d(sB + ld * 16384 + j * 8192, &wmap, nt * 192 + j * 64, ld * 64, sBar + ld * 8);
        }
        __syncwarp();
        if (lane < 2) {
            for (int ld = 6; ld < 12; ld++) {
                const int sl = ld - 6;
                mbar_wait(sBar + 48 + sl * 8, 0);
                if (lane == 0) mbar_expect_tx(sBar + sl * 8, 16384);
                __syncwarp(3);
                if (ld < 8) tma_2d(sB + sl * 16384 + lane * 8192, &wmap, nt * 192 + lane * 64, ld * 64, sBar + sl * 8);
                else tma_2d(sB + sl * 16384 + lane * 8192, &wmap, nt * 192 + 128, (ld - 8) * 128 + lane * 64, sBar + sl * 8);
            }
        }
        return;
    }
    if (nt == 0) s_wr[threadIdx.x] = __ldg((const uint32_t*)w_r + threadIdx.x);
    named_bar(3, K1_THREADS);
    const int g = lane >> 2, t = lane & 3;
    const int lrow = warp * 16 + (lane & 7) + ((lane >> 3) & 1) * 8;
    const uint32_t lbase = sA + lrow * 128;
    const int lsw = lane & 7, lhi = lane >> 4;
    uint32_t laddr[4];
    #pragma unroll
    for (int k4 = 0; k4 < 4; k4++) laddr[k4] = lbase + (((k4 * 2 + lhi) ^ lsw) * 16);
    CK(1);
    mbar_wait(sBar + 96 + wg * 8, 0);
    CK(2);
    float dsum[4] = {0.f, 0.f, 0.f, 0.f}, dq0[4] = {0.f, 0.f, 0.f, 0.f}, dq1[4] = {0.f, 0.f, 0.f, 0.f};
    float esum[4] = {0.f, 0.f, 0.f, 0.f}, eq0[4] = {0.f, 0.f, 0.f, 0.f}, eq1[4] = {0.f, 0.f, 0.f, 0.f};
    #pragma unroll 2
    for (int pn = 0; pn < 8; pn++) {
        uint32_t a[4][4];
        #pragma unroll
        for (int k4 = 0; k4 < 4; k4++) ldsm4(a[k4], laddr[k4] + pn * 16384);
        #pragma unroll
        for (int k4 = 0; k4 < 4; k4 += 2) {
            mma16816(dsum, a[k4], 0x3F803F80u, 0x3F803F80u);
            mma16816(dq0, a[k4], a[k4][0], a[k4][2]);
            mma16816(dq1, a[k4], a[k4][1], a[k4][3]);
            mma16816(esum, a[k4 + 1], 0x3F803F80u, 0x3F803F80u);
            mma16816(eq0, a[k4 + 1], a[k4 + 1][0], a[k4 + 1][2]);
            mma16816(eq1, a[k4 + 1], a[k4 + 1][1], a[k4 + 1][3]);
        }
    }
    #pragma unroll
    for (int i = 0; i < 4; i++) { dsum[i] += esum[i]; dq0[i] += eq0[i]; dq1[i] += eq1[i]; }
    CK(3);
    const int dsrc = g * 4 + (g >> 1);
    const float sq0 = __shfl_sync(~0u, (g & 1) ? dq0[1] : dq0[0], dsrc), sq1 = __shfl_sync(~0u, (g & 1) ? dq1[3] : dq1[2], dsrc);
    const float mean0 = dsum[0] * (1.0f / D_), mean1 = dsum[2] * (1.0f / D_);
    float var0 = fmaf(-mean0, mean0, sq0 * (1.0f / D_)), var1 = fmaf(-mean1, mean1, sq1 * (1.0f / D_));
    if (__any_sync(~0u, !(mean0 * mean0 <= 16.0f * var0) || !(mean1 * mean1 <= 16.0f * var1))) {
        float q0 = 0.f, q1 = 0.f;
        #pragma unroll 1
        for (int ks = 0; ks < 32; ks++) {
            uint32_t a[4];
            ldsm4(a, lbase + (ks >> 2) * 16384 + ((((ks & 3) * 2 + lhi) ^ lsw) * 16));
            #pragma unroll
            for (int i = 0; i < 4; i++) {
                const float m = (i & 1) ? mean1 : mean0;
                const float d0 = bf_lo(a[i]) - m, d1 = bf_hi(a[i]) - m;
                if (i & 1) q1 = fmaf(d0, d0, fmaf(d1, d1, q1)); else q0 = fmaf(d0, d0, fmaf(d1, d1, q0));
            }
        }
        q0 += __shfl_xor_sync(~0u, q0, 1); q0 += __shfl_xor_sync(~0u, q0, 2);
        q1 += __shfl_xor_sync(~0u, q1, 1); q1 += __shfl_xor_sync(~0u, q1, 2);
        var0 = q0 * (1.0f / D_); var1 = q1 * (1.0f / D_);
    }
    const float rs0 = __frcp_rn(bf16r(__fsqrt_rn(bf16r(bf16r(var0) + 1e-5f))));
    const float rs1 = __frcp_rn(bf16r(__fsqrt_rn(bf16r(bf16r(var1) + 1e-5f))));
    const LnRow lr0 = ln_row(mean0, rs0), lr1 = ln_row(mean1, rs1);
    float acc[64];
    #pragma unroll
    for (int i = 0; i < 64; i++) acc[i] = 0.f;
    float dr[4] = {0.f, 0.f, 0.f, 0.f};
    const uint64_t db0 = make_desc(sB, 8192, 1024, 1);
    #pragma unroll 1
    for (int kc = 0; kc < 8; kc += 2) {
        #pragma unroll
        for (int h2 = 0; h2 < 2; h2++) {
            const int ld = kc + h2, sl = ld < 6 ? ld : ld - 6;
            uint32_t a[4][4];
            #pragma unroll
            for (int k4 = 0; k4 < 4; k4++) ldsm4(a[k4], laddr[k4] + ld * 16384);
            #pragma unroll
            for (int k4 = 0; k4 < 4; k4++) ln_frag(a[k4], lr0, lr1);
            if (nt == 0) {
                #pragma unroll
                for (int k4 = 0; k4 < 4; k4++) mma16816(dr, a[k4], s_wr[(ld * 4 + k4) * 8 + t], s_wr[(ld * 4 + k4) * 8 + 4 + t]);
            }
            mbar_wait(sBar + sl * 8, ld >= 6);
            WG_FENCE();
            #pragma unroll
            for (int k4 = 0; k4 < 4; k4++) wgmma_rs_n128(acc, a[k4], db0 + (uint64_t)(sl * 1024 + k4 * 128));
            WG_COMMIT();
            wg_wait<1>();
            if (ld >= 1 && ld <= 6 && (threadIdx.x & 127) == 0) mbar_arrive(sBar + 48 + (ld - 1) * 8);
        }
    }
    const int row0 = mt * 128 + warp * 16;
    if (nt == 0 && t == 0) {
        g_r[row0 + g] = bf16r(dr[0]); g_r[row0 + g + 8] = bf16r(dr[2]);
        g_stats[row0 + g] = make_float2(bf_lo(lr0.m2), rs0); g_stats[row0 + g + 8] = make_float2(bf_lo(lr1.m2), rs1);
    }
    wg_wait<0>();
    touch64(acc);
    CK(4);
    float acc2[32];
    #pragma unroll
    for (int i = 0; i < 32; i++) acc2[i] = 0.f;
    #pragma unroll 1
    for (int q = 0; q < 4; q++) {
        const int sl = q + 2;
        #pragma unroll
        for (int h2 = 0; h2 < 2; h2++) {
            uint32_t a[4][4];
            #pragma unroll
            for (int k4 = 0; k4 < 4; k4++) ldsm4(a[k4], laddr[k4] + (q * 2 + h2) * 16384);
            #pragma unroll
            for (int k4 = 0; k4 < 4; k4++) ln_frag(a[k4], lr0, lr1);
            if (h2 == 0) mbar_wait(sBar + sl * 8, 1);
            WG_FENCE();
            #pragma unroll
            for (int k4 = 0; k4 < 4; k4++) wgmma_rs_n64(acc2, a[k4], db0 + (uint64_t)(sl * 1024 + (h2 * 4 + k4) * 128));
            WG_COMMIT();
            wg_wait<1>();
        }
        if (q == 0) k1_store<4>(acc, 0, nt, row0, lane);
        if (q == 1) k1_store<4>(acc + 32, 4, nt, row0, lane);
    }
    wg_wait<0>();
    touch32(acc2);
    CK(5);
    k1_store<4>(acc2, 8, nt, row0, lane);
    CK(6);
}

constexpr int K2_THREADS = 512;
constexpr int K2_SMEM = 65536 + 98304 + 16384 + 128;

constexpr float QS = 0.25f * 1.4426950408889634f;
constexpr float SC100 = 1.2676506002282294e30f;
__device__ __forceinline__ uint32_t polyexp2(float s0, float s1, float cd, uint32_t one2, uint32_t ca2) {
    constexpr float A = 128.0f * QS * 1.7763568394002505e-15f;
    float t0, t1;
    asm("fma.rn.f32 %0, %1, %2, %3;" : "=f"(t0) : "f"(s0), "f"(A), "f"(cd));
    asm("fma.rn.f32 %0, %1, %2, %3;" : "=f"(t1) : "f"(s1), "f"(A), "f"(cd));
    uint32_t W, U, h, G;
    asm("cvt.pack.sat.s16.s32 %0, %1, %2;" : "=r"(W) : "r"(__float_as_int(t1)), "r"(__float_as_int(t0)));
    asm("lop3.b32 %0, %1, 0x007F007F, %2, 0xEA;" : "=r"(U) : "r"(W), "r"(one2));
    asm("fma.rn.bf16x2 %0, %1, %2, %3;" : "=r"(h) : "r"(U), "r"(ca2), "r"(0xC300C300u));
    asm("fma.rn.bf16x2 %0, %1, %2, %3;" : "=r"(G) : "r"(h), "r"(U), "r"(0x438B438Bu));
    return W + G - 0x43404340u;
}

struct ExpC { float nm0, nm1, cd0, cd1; uint32_t one2, ca2; };

template <int G>
__device__ __forceinline__ void exp_block(const float* s, uint32_t* p, const ExpC& c) {
    #pragma unroll
    for (int hf = 0; hf < 2; hf++) {
        const float* x = s + hf * 4;
        if ((PMASK >> (G + hf)) & 1) {
            p[hf * 2 + 0] = polyexp2(x[0], x[1], c.cd0, c.one2, c.ca2);
            p[hf * 2 + 1] = polyexp2(x[2], x[3], c.cd1, c.one2, c.ca2);
        } else {
            p[hf * 2 + 0] = pack_bf16(ex2(fmaf(x[0], QS * SC100, c.nm0)), ex2(fmaf(x[1], QS * SC100, c.nm0)));
            p[hf * 2 + 1] = pack_bf16(ex2(fmaf(x[2], QS * SC100, c.nm1)), ex2(fmaf(x[3], QS * SC100, c.nm1)));
        }
    }
}

__device__ __forceinline__ void max16(const float* s, float& mx0, float& mx1) {
    #pragma unroll
    for (int j = 0; j < 4; j++) {
        mx0 = fmaxf(mx0, fmaxf(s[4 * j], s[4 * j + 1]));
        mx1 = fmaxf(mx1, fmaxf(s[4 * j + 2], s[4 * j + 3]));
    }
}

__device__ __forceinline__ void moe_load(int b, int part, uint32_t ring, uint32_t bars, const CUtensorMap* mg, const CUtensorMap* mu, const CUtensorMap* md) {
    const int sl = b & 3, grp = b & 1;
    if (b < 28) {
        const int j = b >> 1;
        mbar_expect_tx(bars + sl * 8, 32768);
        tma_2d(ring + sl * 32768, grp ? mu : mg, part * 448 + (j >> 1) * 64, (j & 1) * 256, bars + sl * 8);
    } else {
        const int j = (b - 28) >> 1;
        mbar_expect_tx(bars + sl * 8, 28672);
        tma_2d(ring + sl * 32768, md, ((j >> 1) * 2 + grp) * 64, part * 448 + (j & 1) * 224, bars + sl * 8);
    }
}

__device__ void moe_cta(int part, unsigned char* smem, const __nv_bfloat16* __restrict__ x, const CUtensorMap* mg, const CUtensorMap* mu, const CUtensorMap* md) {
    const uint32_t ring = smem_u32(smem), bars = ring + 131072;
    __nv_bfloat16* xs = (__nv_bfloat16*)(smem + 131072 + 128);
    float* gu = (float*)(smem + 131072 + 128 + 2048);
    float* s_v = gu + 4 * 448;
    int* s_i = (int*)(s_v + 16);
    int* s_sel = s_i + 16;
    const int tid = threadIdx.x, warp = __shfl_sync(~0u, tid >> 5, 0), lane = tid & 31;
    if (tid == 0) {
        for (int i = 0; i < 4; i++) mbar_init(bars + i * 8, 1);
        asm volatile("fence.mbarrier_init.release.cluster;" ::: "memory");
        for (int b = 0; b < 4; b++) moe_load(b, part, ring, bars, mg, mu, md);
    }
    pdl_wait();
    TL(1, 1);
    float rv[4];
    #pragma unroll
    for (int i = 0; i < 4; i++) rv[i] = g_r[tid + i * K2_THREADS];
    for (int pass = 0; pass < 2; pass++) {
        float bv = -INFINITY; int bi = 0x7fffffff;
        const int excl = pass ? s_sel[0] : -1;
        #pragma unroll
        for (int i = 0; i < 4; i++) {
            const int idx = tid + i * K2_THREADS;
            if (idx != excl && (rv[i] > bv || bi == 0x7fffffff)) { bv = rv[i]; bi = idx; }
        }
        #pragma unroll
        for (int o = 16; o; o >>= 1) {
            float ov = __shfl_xor_sync(~0u, bv, o); int oi = __shfl_xor_sync(~0u, bi, o);
            if (ov > bv || (ov == bv && oi < bi)) { bv = ov; bi = oi; }
        }
        if (lane == 0) { s_v[warp] = bv; s_i[warp] = bi; }
        __syncthreads();
        if (warp == 0) {
            bv = lane < 16 ? s_v[lane] : -INFINITY; bi = lane < 16 ? s_i[lane] : 0x7fffffff;
            #pragma unroll
            for (int o = 16; o; o >>= 1) {
                float ov = __shfl_xor_sync(~0u, bv, o); int oi = __shfl_xor_sync(~0u, bi, o);
                if (ov > bv || (ov == bv && oi < bi)) { bv = ov; bi = oi; }
            }
            if (lane == 0) s_sel[pass] = (bi == 0x7fffffff) ? pass : bi;
        }
        __syncthreads();
    }
    for (int i = tid; i < 1024; i += K2_THREADS) {
        const int tok = s_sel[i >> 9];
        const float2 st = g_stats[tok];
        xs[i] = __float2bfloat16_rn(ln_elem(__bfloat162float(x[(size_t)tok * D_ + (i & 511)]), st.x, st.y));
    }
    if (part == 0 && tid < 2) g_sel[tid] = s_sel[tid];
    __syncthreads();
    const int grp = warp >> 3, nj = warp & 7, g = lane >> 2, t = lane & 3;
    const uint32_t* xw = (const uint32_t*)xs + (g & 1) * 256 + t;
    float acc[4] = {0.f, 0.f, 0.f, 0.f};
    #pragma unroll 1
    for (int j = 0; j < 22; j++) {
        const int b = j * 2 + grp, sl = b & 3;
        const bool down = j >= 14;
        if (j == 14) {
            __syncthreads();
            for (int i = tid; i < 896; i += K2_THREADS) {
                const float gs = bf16r(gu[i]), us = bf16r(gu[896 + i]);
                const float sl_ = bf16r(gs / (1.0f + __expf(-gs)));
                xs[(i / 448) * 512 + (i % 448)] = __float2bfloat16_rn(sl_ * us);
            }
            __syncthreads();
        }
        const int kbase = (j & 1) * (down ? 112 : 128);
        const int nk2 = down ? 7 : 8;
        mbar_wait(bars + sl * 8, (b >> 2) & 1);
        const uint32_t baddr = ring + sl * 32768 + lane * 128 + ((nj ^ (lane & 7)) * 16);
        #pragma unroll 2
        for (int k2 = 0; k2 < nk2; k2++) {
            uint32_t bf[4];
            asm volatile("ldmatrix.sync.aligned.m8n8.x4.trans.shared.b16 {%0, %1, %2, %3}, [%4];"
                         : "=r"(bf[0]), "=r"(bf[1]), "=r"(bf[2]), "=r"(bf[3]) : "r"(baddr + k2 * 4096) : "memory");
            uint32_t a[4] = {0u, 0u, 0u, 0u}, a2[4] = {0u, 0u, 0u, 0u};
            if (g < 2) {
                a[0] = xw[kbase + k2 * 16]; a[2] = xw[kbase + k2 * 16 + 4];
                a2[0] = xw[kbase + k2 * 16 + 8]; a2[2] = xw[kbase + k2 * 16 + 12];
            }
            mma16816(acc, a, bf[0], bf[1]);
            mma16816(acc, a2, bf[2], bf[3]);
        }
        named_bar(1 + grp, 256);
        if ((tid & 255) == 0 && b + 4 < 44) moe_load(b + 4, part, ring, bars, mg, mu, md);
        if (j & 1) {
            if (g < 2) {
                if (!down) *(float2*)&gu[(grp * 2 + g) * 448 + (j >> 1) * 64 + nj * 8 + t * 2] = make_float2(acc[0], acc[1]);
                else *(float2*)&g_ypart[part][g][(((j - 14) >> 1) * 2 + grp) * 64 + nj * 8 + t * 2] = make_float2(acc[0], acc[1]);
            }
            acc[0] = 0.f; acc[1] = 0.f; acc[2] = 0.f; acc[3] = 0.f;
        }
    }
}

__global__ void __launch_bounds__(K2_THREADS, 1)
k2_attn(const __nv_bfloat16* __restrict__ x, const __grid_constant__ CUtensorMap mg, const __grid_constant__ CUtensorMap mu,
        const __grid_constant__ CUtensorMap md) {
    extern __shared__ __align__(1024) unsigned char smem[];
    TL(1, 0);
    pdl_launch();
    if (blockIdx.x >= 128) { moe_cta(blockIdx.x - 128, smem, x, &mg, &mu, &md); TL(1, 2); return; }
    const uint32_t sK = smem_u32(smem), sV = sK + 65536, sQ = sV + 98304, sBar = sQ + 16384;
    const int h = blockIdx.x >> 2, qb = blockIdx.x & 3;
    const int warp = __shfl_sync(~0u, threadIdx.x >> 5, 0), lane = threadIdx.x & 31, wg = warp >> 2;
    if (threadIdx.x == 0) {
        mbar_init(sBar, 1); mbar_init(sBar + 8, 1);
        asm volatile("fence.mbarrier_init.release.cluster;" ::: "memory");
        mbar_expect_tx(sBar, 16384 + 16384 + 2 * 8192);
        mbar_expect_tx(sBar + 8, 49152 + 2 * 24576);
    }
    for (int i = threadIdx.x; i < 2048; i += K2_THREADS)
        *(uint4*)(smem + 65536 + 65536 + i * 16) = make_uint4(0x3F803F80u, 0x3F803F80u, 0x3F803F80u, 0x3F803F80u);
    fence_async_smem();
    __syncthreads();
    if (warp == 0) {
        pdl_wait();
        TL(1, 1);
        const uint4* gk = g_K + (size_t)h * 4096;
        const uint4* gv = g_V + (size_t)h * 4096;
        if (lane == 0) bulk_g2s(sQ, g_Q + (size_t)h * 4096 + qb * 1024, 16384, sBar);
        if (lane == 1) bulk_g2s(sK, gk, 16384, sBar);
        if (lane == 2) bulk_g2s(sV, gv, 8192, sBar);
        if (lane == 3) bulk_g2s(sV + 32768, gv + 2048, 8192, sBar);
        if (lane == 4) bulk_g2s(sK + 16384, gk + 1024, 49152, sBar + 8);
        if (lane == 5) bulk_g2s(sV + 8192, gv + 512, 24576, sBar + 8);
        if (lane == 6) bulk_g2s(sV + 32768 + 8192, gv + 2048 + 512, 24576, sBar + 8);
        __syncwarp();
    }
    ExpC c;
    {
        const volatile uint32_t* cc = g_const;
        c.one2 = cc[0]; c.ca2 = cc[1];
    }
    const uint32_t kdesc0 = (uint32_t)make_desc(sK, 128, 256, 0);
    const uint32_t vdesc0 = (uint32_t)make_desc(sV, 128, 32768, 0);
    #pragma unroll 1
    for (int pass = 0; pass < 2; pass++) {
        const bool dry = false;
        if (pass == 0) { mbar_wait(sBar, 0); __syncwarp(); TL(1, 2); }
        const int unit = (pass & 1) * 4 + wg;
        const uint32_t q = (uint32_t)make_desc(sQ + unit * 2048, 128, 256, 0);
        float o[12];
        #pragma unroll 1
        for (int attempt = 0; attempt < 2; attempt++) {
            float s0[16], s1[16], s2[16];
            #pragma unroll
            for (int i = 0; i < 16; i++) { s0[i] = 0.f; s1[i] = 0.f; s2[i] = 0.f; }
            float mx0 = -INFINITY, mx1 = -INFINITY;
            if (attempt) {
                #pragma unroll 1
                for (int it = 0; it < 64; it++) {
                    WG_FENCE();
                    wgmma_qk32(s0, q, kdesc0 + it * 64);
                    WG_COMMIT();
                    wg_wait<0>();
                    touch16(s0);
                    max16(s0, mx0, mx1);
                }
            }
            #pragma unroll
            for (int i = 0; i < 12; i++) o[i] = 0.f;
            WG_FENCE();
            wgmma_qk32(s2, q, kdesc0);
            wgmma_qk32(s0, q, kdesc0 + 64);
            wgmma_qk32(s1, q, kdesc0 + 128);
            WG_COMMIT();
            wg_wait<0>();
            touch16(s0); touch16(s1); touch16(s2);
            max16(s0, mx0, mx1); max16(s1, mx0, mx1); max16(s2, mx0, mx1);
            mx0 = fmaxf(mx0, __shfl_xor_sync(~0u, mx0, 1)); mx0 = fmaxf(mx0, __shfl_xor_sync(~0u, mx0, 2));
            mx1 = fmaxf(mx1, __shfl_xor_sync(~0u, mx1, 1)); mx1 = fmaxf(mx1, __shfl_xor_sync(~0u, mx1, 2));
            const float bias = attempt ? 0.0f : 128.0f * 64.0f;
            const float y0 = ceilf(fmaf(mx0, 128.0f * QS * SC100, bias)), y1 = ceilf(fmaf(mx1, 128.0f * QS * SC100, bias));
            c.nm0 = __shfl_sync(~0u, y0 * (-1.0f / 128.0f), lane); c.nm1 = __shfl_sync(~0u, y1 * (-1.0f / 128.0f), lane);
            c.cd0 = __shfl_sync(~0u, __fmul_rn(16256.0f - y0, __int_as_float(1)), lane);
            c.cd1 = __shfl_sync(~0u, __fmul_rn(16256.0f - y1, __int_as_float(1)), lane);
            uint32_t kd = kdesc0 + 192, vd = vdesc0 + 32;
            {
                uint32_t pa[4], pb[4];
                exp_block<12>(s2, pa, c);
                exp_block<14>(s2 + 8, pb, c);
                WG_FENCE();
                wgmma_pv(o, pa, vdesc0); wgmma_pv(o, pb, vdesc0 + 16);
                WG_COMMIT();
            }
            #pragma unroll 1
            for (int seg = 0; seg < (dry ? 1 : 2); seg++) {
            if (seg) { wg_wait<0>(); mbar_wait(sBar + 8, 0); __syncwarp(); }
            #pragma unroll 1
            for (int it = seg ? 3 : (dry ? 2 : 0); it < (seg ? 21 : 3); it++) {
                uint32_t p[6][4];
                WG_FENCE();
                wgmma_qk32(s2, q, kd);
                WG_COMMIT();
                exp_block<0>(s0, p[0], c);
                exp_block<2>(s0 + 8, p[1], c);
                WG_FENCE();
                wgmma_pv(o, p[0], vd); wgmma_pv(o, p[1], vd + 16);
                wgmma_qk32(s0, q, kd + 64);
                WG_COMMIT();
                wg_wait<1>();
                touch16(s2);
                exp_block<4>(s1, p[2], c);
                exp_block<6>(s1 + 8, p[3], c);
                WG_FENCE();
                wgmma_pv(o, p[2], vd + 32); wgmma_pv(o, p[3], vd + 48);
                wgmma_qk32(s1, q, kd + 128);
                WG_COMMIT();
                wg_wait<1>();
                touch16(s0);
                exp_block<8>(s2, p[4], c);
                exp_block<10>(s2 + 8, p[5], c);
                WG_FENCE();
                wgmma_pv(o, p[4], vd + 64); wgmma_pv(o, p[5], vd + 80);
                WG_COMMIT();
                vd += 96; kd += 192;
                wg_wait<1>();
                touch16(s1);
            }
            }
            wg_wait<0>();
            touch12(o);
            if (attempt) break;
            float big = 0.f;
            #pragma unroll
            for (int i = 0; i < 12; i++) big = fmaxf(big, fabsf(o[i]));
            bool bad = !(big < 1e30f);
            #pragma unroll
            for (int i = 0; i < 12; i++) bad |= (o[i] != o[i]);
            uint32_t any;
            asm volatile("{.reg .pred p, q; setp.ne.u32 p, %1, 0; barrier.cta.red.or.pred.aligned q, %2, 128, p; selp.u32 %0, 1, 0, q;}"
                         : "=r"(any) : "r"((uint32_t)bad), "r"(1 + wg) : "memory");
            if (dry || !__any_sync(~0u, any)) break;
        }
        const int g = lane >> 2, t = lane & 3;
        const int r = (warp & 3) * 16 + g;
        const float i0 = __fdiv_rn(1.0f, o[8]), i1 = __fdiv_rn(1.0f, o[10]);
        uint32_t* ob = (uint32_t*)(g_O + (size_t)(qb * 8 + unit) * 4096 + (h >> 2) * 512 + r * 8) + t;
        const int c0 = ((h & 3) * 2) ^ (r & 7), c1 = ((h & 3) * 2 + 1) ^ (r & 7);
        if (!dry) {
            ob[c0 * 4] = pack_bf16(o[0] * i0, o[1] * i0);
            ob[c1 * 4] = pack_bf16(o[4] * i0, o[5] * i0);
            ob[256 + c0 * 4] = pack_bf16(o[2] * i1, o[3] * i1);
            ob[256 + c1 * 4] = pack_bf16(o[6] * i1, o[7] * i1);
            TL(1, 3 + pass);
        }
    }
}

constexpr int K3_THREADS = 256;
constexpr int K3_SMEM = 65536 + 131072 + 128;

__global__ void __launch_bounds__(K3_THREADS, 1)
k3_out(const __grid_constant__ CUtensorMap wmap, const __nv_bfloat16* __restrict__ x, __nv_bfloat16* __restrict__ out) {
    extern __shared__ __align__(1024) unsigned char smem[];
    const uint32_t sA = smem_u32(smem), sB = sA + 65536, sBar = sB + 131072;
    const int warp = __shfl_sync(~0u, threadIdx.x >> 5, 0), lane = threadIdx.x & 31, wg = warp >> 2;
    const int nt = blockIdx.x & 3, mt = blockIdx.x >> 2;
    TL(2, 0);
    if (threadIdx.x == 0) {
        for (int i = 0; i < 6; i++) mbar_init(sBar + i * 8, 1);
        asm volatile("fence.mbarrier_init.release.cluster;" ::: "memory");
        for (int kh = 0; kh < 2; kh++) {
            mbar_expect_tx(sBar + kh * 8, 65536);
            tma_2d(sB + kh * 32768, &wmap, nt * 128, kh * 256, sBar + kh * 8);
            tma_2d(sB + 65536 + kh * 32768, &wmap, nt * 128 + 64, kh * 256, sBar + kh * 8);
        }
    }
    const int er = threadIdx.x >> 2, ec = (threadIdx.x & 3) * 32;
    const int row = mt * 64 + er;
    uint4 xv[4];
    #pragma unroll
    for (int j = 0; j < 4; j++) xv[j] = __ldg((const uint4*)(x + (size_t)row * D_ + nt * 128 + ec) + j);
    pdl_wait();
    TL(2, 1);
    if (threadIdx.x == 0) {
        for (int q = 0; q < 4; q++) {
            mbar_expect_tx(sBar + 16 + q * 8, 16384);
            bulk_g2s(sA + q * 16384, g_O + (size_t)mt * 4096 + q * 1024, 16384, sBar + 16 + q * 8);
        }
    }
    const int sel0 = g_sel[0], sel1 = g_sel[1];
    const float2 st = g_stats[row];
    uint32_t bb[16];
    {
        const uint32_t xu[16] = {xv[0].x, xv[0].y, xv[0].z, xv[0].w, xv[1].x, xv[1].y, xv[1].z, xv[1].w,
                                 xv[2].x, xv[2].y, xv[2].z, xv[2].w, xv[3].x, xv[3].y, xv[3].z, xv[3].w};
        #pragma unroll
        for (int j = 0; j < 16; j++) bb[j] = pack_bf16(bf16r(bf_lo(xu[j]) - st.x) * st.y, bf16r(bf_hi(xu[j]) - st.x) * st.y);
        const int slot = row == sel0 ? 0 : (row == sel1 ? 1 : -1);
        if (slot >= 0) {
            const float gate = bf16r(1.0f / (1.0f + __expf(-g_r[row])));
            const int c0 = nt * 128 + ec;
            #pragma unroll
            for (int j = 0; j < 16; j++) {
                const float2 a = *(const float2*)&g_ypart[0][slot][c0 + 2 * j], b = *(const float2*)&g_ypart[1][slot][c0 + 2 * j];
                const float2 c = *(const float2*)&g_ypart[2][slot][c0 + 2 * j], d = *(const float2*)&g_ypart[3][slot][c0 + 2 * j];
                bb[j] = pack_bf16(bf_lo(bb[j]) + bf16r(bf16r(a.x + b.x + c.x + d.x) * gate), bf_hi(bb[j]) + bf16r(bf16r(a.y + b.y + c.y + d.y) * gate));
            }
        }
    }
    __syncthreads();
    float acc[32];
    #pragma unroll
    for (int i = 0; i < 32; i++) acc[i] = 0.f;
    const uint64_t da0 = make_desc(sA, 16, 1024, 1);
    const uint64_t db0 = make_desc(sB + wg * 65536, 8192, 1024, 1);
    #pragma unroll 1
    for (int q = 0; q < 4; q++) {
        if ((q & 1) == 0) mbar_wait(sBar + (q >> 1) * 8, 0);
        mbar_wait(sBar + 16 + q * 8, 0);
        WG_FENCE();
        #pragma unroll
        for (int kk = 0; kk < 8; kk++)
            wgmma_n64(acc, da0 + (uint64_t)(q * 1024 + (kk >> 2) * 512 + (kk & 3) * 2), db0 + (uint64_t)(q * 1024 + kk * 128));
        WG_COMMIT();
    }
    wg_wait<0>();
    touch32(acc);
    TL(2, 2);
    __syncthreads();
    {
        const int g = lane >> 2, t = lane & 3;
        unsigned char* sp = smem + ((warp & 3) * 16 + g) * 272 + wg * 128 + t * 4;
        #pragma unroll
        for (int j = 0; j < 8; j++) {
            *(uint32_t*)(sp + j * 16) = pack_bf16(acc[4 * j], acc[4 * j + 1]);
            *(uint32_t*)(sp + 8 * 272 + j * 16) = pack_bf16(acc[4 * j + 2], acc[4 * j + 3]);
        }
    }
    __syncthreads();
    #pragma unroll
    for (int j = 0; j < 4; j++) {
        const uint4 av = *(const uint4*)(smem + er * 272 + ec * 2 + j * 16);
        const uint32_t au[4] = {av.x, av.y, av.z, av.w}, xu[4] = {xv[j].x, xv[j].y, xv[j].z, xv[j].w};
        uint32_t o[4];
        #pragma unroll
        for (int i = 0; i < 4; i++) {
            uint32_t t2;
            asm("add.rn.bf16x2 %0, %1, %2;" : "=r"(t2) : "r"(xu[i]), "r"(au[i]));
            asm("add.rn.bf16x2 %0, %1, %2;" : "=r"(o[i]) : "r"(t2), "r"(bb[j * 4 + i]));
        }
        *((uint4*)(out + (size_t)row * D_ + nt * 128 + ec) + j) = make_uint4(o[0], o[1], o[2], o[3]);
    }
    TL(2, 3);
}

typedef CUresult (*EncodeFn)(CUtensorMap*, CUtensorMapDataType, cuuint32_t, void*, const cuuint64_t*, const cuuint64_t*,
                             const cuuint32_t*, const cuuint32_t*, CUtensorMapInterleave, CUtensorMapSwizzle,
                             CUtensorMapL2promotion, CUtensorMapFloatOOBfill);

void make_wmap(EncodeFn fn, CUtensorMap* map, const void* ptr, int rows, int cols, int box_rows) {
    cuuint64_t dims[2] = {(cuuint64_t)cols, (cuuint64_t)rows};
    cuuint64_t strides[1] = {(cuuint64_t)cols * 2};
    cuuint32_t box[2] = {64, (cuuint32_t)box_rows};
    cuuint32_t es[2] = {1, 1};
    fn(map, CU_TENSOR_MAP_DATA_TYPE_BFLOAT16, 2, (void*)ptr, dims, strides, box, es, CU_TENSOR_MAP_INTERLEAVE_NONE,
       CU_TENSOR_MAP_SWIZZLE_128B, CU_TENSOR_MAP_L2_PROMOTION_L2_256B, CU_TENSOR_MAP_FLOAT_OOB_FILL_NONE);
}

}

extern "C" void kernel_launch(void* const* d_in, const int* in_sizes, int n_in, void* d_out, int out_size) {
    const __nv_bfloat16* x = (const __nv_bfloat16*)d_in[0];
    const __nv_bfloat16* wqkv = (const __nv_bfloat16*)d_in[1];
    const __nv_bfloat16* wo = (const __nv_bfloat16*)d_in[2];
    const __nv_bfloat16* w_r = (const __nv_bfloat16*)d_in[4];
    const __nv_bfloat16* w_gate = (const __nv_bfloat16*)d_in[5];
    const __nv_bfloat16* w_up = (const __nv_bfloat16*)d_in[6];
    const __nv_bfloat16* w_down = (const __nv_bfloat16*)d_in[7];
    __nv_bfloat16* out = (__nv_bfloat16*)d_out;

    static EncodeFn encode = nullptr;
    if (!encode) {
        void* fn = nullptr;
        cudaDriverEntryPointQueryResult qres;
        cudaGetDriverEntryPoint("cuTensorMapEncodeTiled", &fn, cudaEnableDefault, &qres);
        encode = (EncodeFn)fn;
        cudaFuncSetAttribute(k1_ln_qkv, cudaFuncAttributeMaxDynamicSharedMemorySize, K1_SMEM);
        cudaFuncSetAttribute(k2_attn, cudaFuncAttributeMaxDynamicSharedMemorySize, K2_SMEM);
        cudaFuncSetAttribute(k3_out, cudaFuncAttributeMaxDynamicSharedMemorySize, K3_SMEM);
    }
    CUtensorMap map_qkv, map_wo, map_x, map_g, map_u, map_d;
    make_wmap(encode, &map_g, w_gate, D_, F_, 256);
    make_wmap(encode, &map_u, w_up, D_, F_, 256);
    make_wmap(encode, &map_d, w_down, F_, D_, 224);
    make_wmap(encode, &map_x, x, S_, D_, 64);
    make_wmap(encode, &map_qkv, wqkv, D_, 3 * D_, 64);
    make_wmap(encode, &map_wo, wo, D_, D_, 256);

    k1_ln_qkv<<<128, K1_THREADS, K1_SMEM, cudaStreamPerThread>>>(map_qkv, map_x, w_r);
    cudaLaunchAttribute at[1];
    at[0].id = cudaLaunchAttributeProgrammaticStreamSerialization;
    at[0].val.programmaticStreamSerializationAllowed = 1;
    cudaLaunchConfig_t cfg = {};
    cfg.stream = cudaStreamPerThread;
    cfg.attrs = at; cfg.numAttrs = 1;
    cfg.gridDim = dim3(132); cfg.blockDim = dim3(K2_THREADS); cfg.dynamicSmemBytes = K2_SMEM;
    cudaLaunchKernelEx(&cfg, k2_attn, x, map_g, map_u, map_d);
    cfg.gridDim = dim3(128); cfg.blockDim = dim3(K3_THREADS); cfg.dynamicSmemBytes = K3_SMEM;
    cudaLaunchKernelEx(&cfg, k3_out, map_wo, x, out);
}
```

```cpp
#include <cuda_runtime.h>
#include <cuda_bf16.h>
#include <cuda.h>
#include <stdint.h>

namespace {

constexpr int S_ = 2048, D_ = 512, H_ = 32, F_ = 1792;

constexpr uint32_t PMASK = 0xDB6;

__device__ __align__(1024) uint4 g_QKV[3 * H_ * S_ * 2];
#define g_Q (g_QKV)
#define g_K (g_QKV + H_ * S_ * 2)
#define g_V (g_QKV + 2 * H_ * S_ * 2)
__device__ __align__(1024) uint4 g_O[S_ * D_ / 8];
__device__ float2 g_stats[S_];
__device__ uint32_t g_const[2] = {0x3F803F80u, 0x42294229u};
__device__ float g_r[S_];
__device__ __align__(16) float g_ypart[4][2][D_];
__device__ int g_sel[2];

#define TL(k, p)
#define CK(i)
__device__ __forceinline__ uint32_t smem_u32(const void* p) { return (uint32_t)__cvta_generic_to_shared(p); }
__device__ __forceinline__ float bf16r(float x) { return __bfloat162float(__float2bfloat16_rn(x)); }
__device__ __forceinline__ uint32_t pack_bf16(float lo, float hi) {
    uint32_t r; asm("cvt.rn.bf16x2.f32 %0, %1, %2;" : "=r"(r) : "f"(hi), "f"(lo)); return r;
}
__device__ __forceinline__ float bf_lo(uint32_t u) { return __uint_as_float(u << 16); }
__device__ __forceinline__ float bf_hi(uint32_t u) { return __uint_as_float(u & 0xFFFF0000u); }
__device__ __forceinline__ float ex2(float x) { float y; asm("ex2.approx.ftz.f32 %0, %1;" : "=f"(y) : "f"(x)); return y; }

__device__ __forceinline__ void mbar_init(uint32_t bar, uint32_t count) {
    asm volatile("mbarrier.init.shared::cta.b64 [%0], %1;" :: "r"(bar), "r"(count) : "memory");
}
__device__ __forceinline__ void mbar_expect_tx(uint32_t bar, uint32_t bytes) {
    asm volatile("mbarrier.arrive.expect_tx.shared::cta.b64 _, [%0], %1;" :: "r"(bar), "r"(bytes) : "memory");
}
__device__ __forceinline__ void mbar_arrive(uint32_t bar) {
    asm volatile("mbarrier.arrive.shared::cta.b64 _, [%0];" :: "r"(bar) : "memory");
}
__device__ __forceinline__ void mbar_wait(uint32_t bar, uint32_t parity) {
    uint32_t done;
    #pragma unroll 1
    for (int it = 0; it < (1 << 26); it++) {
        asm volatile("{.reg .pred p; mbarrier.try_wait.parity.shared::cta.b64 p, [%1], %2; selp.u32 %0, 1, 0, p;}"
                     : "=r"(done) : "r"(bar), "r"(parity) : "memory");
        if (done) return;
    }
    __trap();
}
__device__ __forceinline__ void bulk_g2s(uint32_t dst, const void* src, uint32_t bytes, uint32_t bar) {
    asm volatile("cp.async.bulk.shared::cluster.global.mbarrier::complete_tx::bytes [%0], [%1], %2, [%3];"
                 :: "r"(dst), "l"(src), "r"(bytes), "r"(bar) : "memory");
}
__device__ __forceinline__ void tma_2d(uint32_t dst, const CUtensorMap* map, int c0, int c1, uint32_t bar) {
    asm volatile("cp.async.bulk.tensor.2d.shared::cluster.global.mbarrier::complete_tx::bytes [%0], [%1, {%3, %4}], [%2];"
                 :: "r"(dst), "l"(map), "r"(bar), "r"(c0), "r"(c1) : "memory");
}
__device__ __forceinline__ void fence_async_smem() { asm volatile("fence.proxy.async.shared::cta;" ::: "memory"); }
__device__ __forceinline__ void named_bar(int id, int n) { asm volatile("bar.sync %0, %1;" :: "r"(id), "r"(n) : "memory"); }

__device__ __forceinline__ uint64_t make_desc(uint32_t saddr, uint32_t lbo, uint32_t sbo, uint32_t swz) {
    return (uint64_t)((saddr & 0x3FFFF) >> 4) | ((uint64_t)(lbo >> 4) << 16) | ((uint64_t)(sbo >> 4) << 32) | ((uint64_t)swz << 62);
}
#define WG_FENCE() asm volatile("wgmma.fence.sync.aligned;" ::: "memory")
#define WG_COMMIT() asm volatile("wgmma.commit_group.sync.aligned;" ::: "memory")
template <int N> __device__ __forceinline__ void wg_wait() { asm volatile("wgmma.wait_group.sync.aligned %0;" :: "n"(N) : "memory"); }

#define F4(d, o) "+f"(d[o]), "+f"(d[o + 1]), "+f"(d[o + 2]), "+f"(d[o + 3])
#define F16(d, o) F4(d, o), F4(d, o + 4), F4(d, o + 8), F4(d, o + 12)
#define F32(d, o) F16(d, o), F16(d, o + 16)

__device__ __forceinline__ void wgmma_rs_n128(float* d, const uint32_t* a, uint64_t db) {
    asm volatile("wgmma.mma_async.sync.aligned.m64n128k16.f32.bf16.bf16 "
        "{%0,%1,%2,%3,%4,%5,%6,%7,%8,%9,%10,%11,%12,%13,%14,%15,%16,%17,%18,%19,%20,%21,%22,%23,%24,%25,%26,%27,%28,%29,%30,%31,"
        "%32,%33,%34,%35,%36,%37,%38,%39,%40,%41,%42,%43,%44,%45,%46,%47,%48,%49,%50,%51,%52,%53,%54,%55,%56,%57,%58,%59,%60,%61,%62,%63}, "
        "{%64,%65,%66,%67}, %68, 1, 1, 1, 1;\n"
        : F32(d, 0), F32(d, 32) : "r"(a[0]), "r"(a[1]), "r"(a[2]), "r"(a[3]), "l"(db));
}
__device__ __forceinline__ void wgmma_rs_n64(float* d, const uint32_t* a, uint64_t db) {
    asm volatile("wgmma.mma_async.sync.aligned.m64n64k16.f32.bf16.bf16 "
        "{%0,%1,%2,%3,%4,%5,%6,%7,%8,%9,%10,%11,%12,%13,%14,%15,%16,%17,%18,%19,%20,%21,%22,%23,%24,%25,%26,%27,%28,%29,%30,%31}, "
        "{%32,%33,%34,%35}, %36, 1, 1, 1, 1;\n"
        : F32(d, 0) : "r"(a[0]), "r"(a[1]), "r"(a[2]), "r"(a[3]), "l"(db));
}
__device__ __forceinline__ void wgmma_n64(float* d, uint64_t da, uint64_t db) {
    asm volatile("wgmma.mma_async.sync.aligned.m64n64k16.f32.bf16.bf16 "
        "{%0,%1,%2,%3,%4,%5,%6,%7,%8,%9,%10,%11,%12,%13,%14,%15,%16,%17,%18,%19,%20,%21,%22,%23,%24,%25,%26,%27,%28,%29,%30,%31}, "
        "%32, %33, 1, 1, 1, 0, 1;\n"
        : F32(d, 0) : "l"(da), "l"(db));
}
__device__ __forceinline__ void wgmma_qk32(float* d, uint32_t qd, uint32_t kd) {
    asm volatile("{.reg .b64 a, b; mov.b64 a, {%16, 16}; mov.b64 b, {%17, 16};\n"
        "wgmma.mma_async.sync.aligned.m64n32k16.f32.bf16.bf16 {%0,%1,%2,%3,%4,%5,%6,%7,%8,%9,%10,%11,%12,%13,%14,%15}, a, b, 0, 1, 1, 0, 0;}\n"
        : F16(d, 0) : "r"(qd), "r"(kd));
}
__device__ __forceinline__ void wgmma_pv(float* d, const uint32_t* a, uint32_t vd) {
    asm volatile("{.reg .b64 b; mov.b64 b, {%16, 2048};\n"
        "wgmma.mma_async.sync.aligned.m64n24k16.f32.bf16.bf16 {%0,%1,%2,%3,%4,%5,%6,%7,%8,%9,%10,%11}, {%12,%13,%14,%15}, b, 1, 1, 1, 1;}\n"
        : F4(d, 0), F4(d, 4), F4(d, 8) : "r"(a[0]), "r"(a[1]), "r"(a[2]), "r"(a[3]), "r"(vd));
}
__device__ __forceinline__ void touch16(float* d) { asm volatile("" : F16(d, 0) :: "memory"); }
__device__ __forceinline__ void touch12(float* d) { asm volatile("" : F4(d, 0), F4(d, 4), F4(d, 8) :: "memory"); }
__device__ __forceinline__ void touch32(float* d) { asm volatile("" : F32(d, 0) :: "memory"); }
__device__ __forceinline__ void touch64(float* d) { asm volatile("" : F32(d, 0), F32(d, 32) :: "memory"); }

__device__ __forceinline__ float ln_elem(float x, float mean_b, float rden) {
    return bf16r(bf16r(x - mean_b) * rden);
}
__device__ __forceinline__ void pdl_wait() { asm volatile("griddepcontrol.wait;" ::: "memory"); }
__device__ __forceinline__ void pdl_launch() { asm volatile("griddepcontrol.launch_dependents;" ::: "memory"); }
__device__ __forceinline__ void cluster_arrive() { asm volatile("barrier.cluster.arrive.release.aligned;" ::: "memory"); }
__device__ __forceinline__ void cluster_wait() { asm volatile("barrier.cluster.wait.acquire.aligned;" ::: "memory"); }

constexpr int K1_THREADS = 288;
constexpr int K1_SMEM = 131072 + 6 * 16384 + 128 + 1024;

__device__ __forceinline__ void ldsm4(uint32_t* r, uint32_t addr) {
    asm volatile("ldmatrix.sync.aligned.m8n8.x4.shared.b16 {%0, %1, %2, %3}, [%4];" : "=r"(r[0]), "=r"(r[1]), "=r"(r[2]), "=r"(r[3]) : "r"(addr) : "memory");
}
__device__ __forceinline__ void stsm4(uint32_t addr, uint32_t r0, uint32_t r1, uint32_t r2, uint32_t r3) {
    asm volatile("stmatrix.sync.aligned.m8n8.x4.shared.b16 [%0], {%1, %2, %3, %4};" :: "r"(addr), "r"(r0), "r"(r1), "r"(r2), "r"(r3) : "memory");
}
__device__ __forceinline__ void mma16816(float* d, const uint32_t* a, uint32_t b0, uint32_t b1) {
    asm("mma.sync.aligned.m16n8k16.row.col.f32.bf16.bf16.f32 {%0,%1,%2,%3}, {%4,%5,%6,%7}, {%8,%9}, {%0,%1,%2,%3};"
        : "+f"(d[0]), "+f"(d[1]), "+f"(d[2]), "+f"(d[3]) : "r"(a[0]), "r"(a[1]), "r"(a[2]), "r"(a[3]), "r"(b0), "r"(b1));
}
__device__ __forceinline__ uint32_t sub_bf16x2(uint32_t a, uint32_t b) {
    uint32_t d; asm("sub.rn.bf16x2 %0, %1, %2;" : "=r"(d) : "r"(a), "r"(b)); return d;
}
__device__ __forceinline__ uint32_t ln_pair(uint32_t x2, uint32_t mean2, uint32_t rhi2, uint32_t rlo2) {
    const uint32_t d = sub_bf16x2(x2, mean2);
    uint32_t t, y;
    asm("mul.rn.bf16x2 %0, %1, %2;" : "=r"(t) : "r"(d), "r"(rlo2));
    asm("fma.rn.bf16x2 %0, %1, %2, %3;" : "=r"(y) : "r"(d), "r"(rhi2), "r"(t));
    return y;
}
struct LnRow { uint32_t m2, hi2, lo2; };
__device__ __forceinline__ LnRow ln_row(float mean, float rden) {
    LnRow r;
    r.m2 = pack_bf16(mean, mean);
    r.hi2 = pack_bf16(rden, rden);
    const float lo = rden - bf_lo(r.hi2);
    r.lo2 = pack_bf16(lo, lo);
    return r;
}
__device__ __forceinline__ void ln_frag(uint32_t* a, const LnRow& r0, const LnRow& r1) {
    a[0] = ln_pair(a[0], r0.m2, r0.hi2, r0.lo2); a[1] = ln_pair(a[1], r1.m2, r1.hi2, r1.lo2);
    a[2] = ln_pair(a[2], r0.m2, r0.hi2, r0.lo2); a[3] = ln_pair(a[3], r1.m2, r1.hi2, r1.lo2);
}

template <int NJ>
__device__ __forceinline__ void k1_store(const float* acc, int jj0, int nt, int row0, int lane) {
    const int g = lane >> 2, t = lane & 3, g8a = row0 >> 3;
    const int off_qk = g8a * 64 + g * 4 + t, off_v = (row0 + g) * 4 + t;
    #pragma unroll
    for (int jj = 0; jj < NJ; jj++) {
        const int hg = nt * 12 + jj0 + jj;
        const bool isv = hg >= 64;
        const float m = isv ? 1.0f : 8.8817841970012523e-16f;
        uint32_t* base = (uint32_t*)g_QKV + (size_t)hg * 16384 + (isv ? off_v : off_qk);
        const int hs = isv ? 8192 : 32, rs = isv ? 32 : 64;
        base[0] = pack_bf16(acc[8 * jj] * m, acc[8 * jj + 1] * m);
        base[rs] = pack_bf16(acc[8 * jj + 2] * m, acc[8 * jj + 3] * m);
        base[hs] = pack_bf16(acc[8 * jj + 4] * m, acc[8 * jj + 5] * m);
        base[hs + rs] = pack_bf16(acc[8 * jj + 6] * m, acc[8 * jj + 7] * m);
    }
}

__global__ void __launch_bounds__(K1_THREADS, 1)
k1_ln_qkv(const __grid_constant__ CUtensorMap wmap, const __grid_constant__ CUtensorMap xmap, const __nv_bfloat16* __restrict__ w_r) {
    extern __shared__ __align__(1024) unsigned char smem[];
    const uint32_t sA = smem_u32(smem), sB = sA + 131072, sBar = sB + 6 * 16384;
    const int warp = __shfl_sync(~0u, threadIdx.x >> 5, 0), lane = threadIdx.x & 31;
    const int nt = blockIdx.x & 7, mt = blockIdx.x >> 3;
    const int wg = warp >> 2;
    CK(0);
    pdl_launch();
    uint32_t* s_wr = (uint32_t*)(smem + 131072 + 6 * 16384 + 128);
    if (warp == 8) {
        if (lane == 0) {
            for (int i = 0; i < 6; i++) { mbar_init(sBar + i * 8, 1); mbar_init(sBar + 48 + i * 8, 2); }
            mbar_init(sBar + 96, 1); mbar_init(sBar + 104, 1);
            asm volatile("fence.mbarrier_init.release.cluster;" ::: "memory");
            mbar_expect_tx(sBar + 96, 65536); mbar_expect_tx(sBar + 104, 65536);
            for (int i = 0; i < 6; i++) mbar_expect_tx(sBar + i * 8, 16384);
        }
        __syncwarp();
        if (lane < 16) tma_2d(sA + (lane & 7) * 16384 + (lane >> 3) * 8192, &xmap, (lane & 7) * 64, mt * 128 + (lane >> 3) * 64, sBar + 96 + (lane >> 3) * 8);
        named_bar(3, K1_THREADS);
        mbar_wait(sBar + 96, 0);
        if (lane < 12) {
            const int ld = lane >> 1, j = lane & 1;
            tma_2d(sB + ld * 16384 + j * 8192, &wmap, nt * 192 + j * 64, ld * 64, sBar + ld * 8);
        }
        __syncwarp();
        if (lane < 2) {
            for (int ld = 6; ld < 12; ld++) {
                const int sl = ld - 6;
                mbar_wait(sBar + 48 + sl * 8, 0);
                if (lane == 0) mbar_expect_tx(sBar + sl * 8, 16384);
                __syncwarp(3);
                if (ld < 8) tma_2d(sB + sl * 16384 + lane * 8192, &wmap, nt * 192 + lane * 64, ld * 64, sBar + sl * 8);
                else tma_2d(sB + sl * 16384 + lane * 8192, &wmap, nt * 192 + 128, (ld - 8) * 128 + lane * 64, sBar + sl * 8);
            }
        }
        return;
    }
    if (nt == 0) s_wr[threadIdx.x] = __ldg((const uint32_t*)w_r + threadIdx.x);
    named_bar(3, K1_THREADS);
    const int g = lane >> 2, t = lane & 3;
    const int lrow = warp * 16 + (lane & 7) + ((lane >> 3) & 1) * 8;
    const uint32_t lbase = sA + lrow * 128;
    const int lsw = lane & 7, lhi = lane >> 4;
    uint32_t laddr[4];
    #pragma unroll
    for (int k4 = 0; k4 < 4; k4++) laddr[k4] = lbase + (((k4 * 2 + lhi) ^ lsw) * 16);
    CK(1);
    mbar_wait(sBar + 96 + wg * 8, 0);
    CK(2);
    float dsum[4] = {0.f, 0.f, 0.f, 0.f}, dq0[4] = {0.f, 0.f, 0.f, 0.f}, dq1[4] = {0.f, 0.f, 0.f, 0.f};
    float esum[4] = {0.f, 0.f, 0.f, 0.f}, eq0[4] = {0.f, 0.f, 0.f, 0.f}, eq1[4] = {0.f, 0.f, 0.f, 0.f};
    #pragma unroll 2
    for (int pn = 0; pn < 8; pn++) {
        uint32_t a[4][4];
        #pragma unroll
        for (int k4 = 0; k4 < 4; k4++) ldsm4(a[k4], laddr[k4] + pn * 16384);
        #pragma unroll
        for (int k4 = 0; k4 < 4; k4 += 2) {
            mma16816(dsum, a[k4], 0x3F803F80u, 0x3F803F80u);
            mma16816(dq0, a[k4], a[k4][0], a[k4][2]);
            mma16816(dq1, a[k4], a[k4][1], a[k4][3]);
            mma16816(esum, a[k4 + 1], 0x3F803F80u, 0x3F803F80u);
            mma16816(eq0, a[k4 + 1], a[k4 + 1][0], a[k4 + 1][2]);
            mma16816(eq1, a[k4 + 1], a[k4 + 1][1], a[k4 + 1][3]);
        }
    }
    #pragma unroll
    for (int i = 0; i < 4; i++) { dsum[i] += esum[i]; dq0[i] += eq0[i]; dq1[i] += eq1[i]; }
    CK(3);
    const int dsrc = g * 4 + (g >> 1);
    const float sq0 = __shfl_sync(~0u, (g & 1) ? dq0[1] : dq0[0], dsrc), sq1 = __shfl_sync(~0u, (g & 1) ? dq1[3] : dq1[2], dsrc);
    const float mean0 = dsum[0] * (1.0f / D_), mean1 = dsum[2] * (1.0f / D_);
    float var0 = fmaf(-mean0, mean0, sq0 * (1.0f / D_)), var1 = fmaf(-mean1, mean1, sq1 * (1.0f / D_));
    if (__any_sync(~0u, !(mean0 * mean0 <= 16.0f * var0) || !(mean1 * mean1 <= 16.0f * var1))) {
        float q0 = 0.f, q1 = 0.f;
        #pragma unroll 1
        for (int ks = 0; ks < 32; ks++) {
            uint32_t a[4];
            ldsm4(a, lbase + (ks >> 2) * 16384 + ((((ks & 3) * 2 + lhi) ^ lsw) * 16));
            #pragma unroll
            for (int i = 0; i < 4; i++) {
                const float m = (i & 1) ? mean1 : mean0;
                const float d0 = bf_lo(a[i]) - m, d1 = bf_hi(a[i]) - m;
                if (i & 1) q1 = fmaf(d0, d0, fmaf(d1, d1, q1)); else q0 = fmaf(d0, d0, fmaf(d1, d1, q0));
            }
        }
        q0 += __shfl_xor_sync(~0u, q0, 1); q0 += __shfl_xor_sync(~0u, q0, 2);
        q1 += __shfl_xor_sync(~0u, q1, 1); q1 += __shfl_xor_sync(~0u, q1, 2);
        var0 = q0 * (1.0f / D_); var1 = q1 * (1.0f / D_);
    }
    const float rs0 = __frcp_rn(bf16r(__fsqrt_rn(bf16r(bf16r(var0) + 1e-5f))));
    const float rs1 = __frcp_rn(bf16r(__fsqrt_rn(bf16r(bf16r(var1) + 1e-5f))));
    const LnRow lr0 = ln_row(mean0, rs0), lr1 = ln_row(mean1, rs1);
    float acc[64];
    #pragma unroll
    for (int i = 0; i < 64; i++) acc[i] = 0.f;
    float dr[4] = {0.f, 0.f, 0.f, 0.f};
    const uint64_t db0 = make_desc(sB, 8192, 1024, 1);
    #pragma unroll 1
    for (int kc = 0; kc < 8; kc += 2) {
        #pragma unroll
        for (int h2 = 0; h2 < 2; h2++) {
            const int ld = kc + h2, sl = ld < 6 ? ld : ld - 6;
            uint32_t a[4][4];
            #pragma unroll
            for (int k4 = 0; k4 < 4; k4++) ldsm4(a[k4], laddr[k4] + ld * 16384);
            #pragma unroll
            for (int k4 = 0; k4 < 4; k4++) ln_frag(a[k4], lr0, lr1);
            if (nt == 0) {
                #pragma unroll
                for (int k4 = 0; k4 < 4; k4++) mma16816(dr, a[k4], s_wr[(ld * 4 + k4) * 8 + t], s_wr[(ld * 4 + k4) * 8 + 4 + t]);
            }
            mbar_wait(sBar + sl * 8, ld >= 6);
            WG_FENCE();
            #pragma unroll
            for (int k4 = 0; k4 < 4; k4++) wgmma_rs_n128(acc, a[k4], db0 + (uint64_t)(sl * 1024 + k4 * 128));
            WG_COMMIT();
            wg_wait<1>();
            if (ld >= 1 && ld <= 6 && (threadIdx.x & 127) == 0) mbar_arrive(sBar + 48 + (ld - 1) * 8);
        }
    }
    const int row0 = mt * 128 + warp * 16;
    if (nt == 0 && t == 0) {
        g_r[row0 + g] = bf16r(dr[0]); g_r[row0 + g + 8] = bf16r(dr[2]);
        g_stats[row0 + g] = make_float2(bf_lo(lr0.m2), rs0); g_stats[row0 + g + 8] = make_float2(bf_lo(lr1.m2), rs1);
    }
    wg_wait<0>();
    touch64(acc);
    CK(4);
    float acc2[32];
    #pragma unroll
    for (int i = 0; i < 32; i++) acc2[i] = 0.f;
    #pragma unroll 1
    for (int q = 0; q < 4; q++) {
        const int sl = q + 2;
        #pragma unroll
        for (int h2 = 0; h2 < 2; h2++) {
            uint32_t a[4][4];
            #pragma unroll
            for (int k4 = 0; k4 < 4; k4++) ldsm4(a[k4], laddr[k4] + (q * 2 + h2) * 16384);
            #pragma unroll
            for (int k4 = 0; k4 < 4; k4++) ln_frag(a[k4], lr0, lr1);
            if (h2 == 0) mbar_wait(sBar + sl * 8, 1);
            WG_FENCE();
            #pragma unroll
            for (int k4 = 0; k4 < 4; k4++) wgmma_rs_n64(acc2, a[k4], db0 + (uint64_t)(sl * 1024 + (h2 * 4 + k4) * 128));
            WG_COMMIT();
            wg_wait<1>();
        }
        if (q == 0) k1_store<4>(acc, 0, nt, row0, lane);
        if (q == 1) k1_store<4>(acc + 32, 4, nt, row0, lane);
    }
    wg_wait<0>();
    touch32(acc2);
    CK(5);
    k1_store<4>(acc2, 8, nt, row0, lane);
    CK(6);
}

constexpr int K2_THREADS = 512;
constexpr int K2_SMEM = 65536 + 98304 + 16384 + 128;

constexpr float QS = 0.25f * 1.4426950408889634f;
constexpr float SC100 = 1.2676506002282294e30f;
__device__ __forceinline__ uint32_t polyexp2(float s0, float s1, float cd, uint32_t one2, uint32_t ca2) {
    constexpr float A = 128.0f * QS * 1.7763568394002505e-15f;
    float t0, t1;
    asm("fma.rn.f32 %0, %1, %2, %3;" : "=f"(t0) : "f"(s0), "f"(A), "f"(cd));
    asm("fma.rn.f32 %0, %1, %2, %3;" : "=f"(t1) : "f"(s1), "f"(A), "f"(cd));
    uint32_t W, U, h, G;
    asm("cvt.pack.sat.s16.s32 %0, %1, %2;" : "=r"(W) : "r"(__float_as_int(t1)), "r"(__float_as_int(t0)));
    asm("lop3.b32 %0, %1, 0x007F007F, %2, 0xEA;" : "=r"(U) : "r"(W), "r"(one2));
    asm("fma.rn.bf16x2 %0, %1, %2, %3;" : "=r"(h) : "r"(U), "r"(ca2), "r"(0xC300C300u));
    asm("fma.rn.bf16x2 %0, %1, %2, %3;" : "=r"(G) : "r"(h), "r"(U), "r"(0x438B438Bu));
    return W + G - 0x43404340u;
}

struct ExpC { float nm0, nm1, cd0, cd1; uint32_t one2, ca2; };

template <int G>
__device__ __forceinline__ void exp_block(const float* s, uint32_t* p, const ExpC& c) {
    #pragma unroll
    for (int hf = 0; hf < 2; hf++) {
        const float* x = s + hf * 4;
        if ((PMASK >> (G + hf)) & 1) {
            p[hf * 2 + 0] = polyexp2(x[0], x[1], c.cd0, c.one2, c.ca2);
            p[hf * 2 + 1] = polyexp2(x[2], x[3], c.cd1, c.one2, c.ca2);
        } else {
            p[hf * 2 + 0] = pack_bf16(ex2(fmaf(x[0], QS * SC100, c.nm0)), ex2(fmaf(x[1], QS * SC100, c.nm0)));
            p[hf * 2 + 1] = pack_bf16(ex2(fmaf(x[2], QS * SC100, c.nm1)), ex2(fmaf(x[3], QS * SC100, c.nm1)));
        }
    }
}

__device__ __forceinline__ void max16(const float* s, float& mx0, float& mx1) {
    #pragma unroll
    for (int j = 0; j < 4; j++) {
        mx0 = fmaxf(mx0, fmaxf(s[4 * j], s[4 * j + 1]));
        mx1 = fmaxf(mx1, fmaxf(s[4 * j + 2], s[4 * j + 3]));
    }
}

constexpr int MOE_SLOTS = 10, MOE_BOXES = 88;
__device__ __forceinline__ void moe_load(int b, int part, uint32_t ring, uint32_t bars, const CUtensorMap* mg, const CUtensorMap* mu, const CUtensorMap* md) {
    const int sl = b % MOE_SLOTS, grp = b & 1;
    if (b < 56) {
        const int j = b >> 1;
        mbar_expect_tx(bars + sl * 8, 16384);
        tma_2d(ring + sl * 16384, grp ? mu : mg, part * 448 + (j >> 2) * 64, (j & 3) * 128, bars + sl * 8);
    } else {
        const int j = (b - 56) >> 1;
        mbar_expect_tx(bars + sl * 8, 14336);
        tma_2d(ring + sl * 16384, md, ((j >> 2) * 2 + grp) * 64, part * 448 + (j & 3) * 112, bars + sl * 8);
    }
}

__device__ void moe_cta(int part, unsigned char* smem, const __nv_bfloat16* __restrict__ x, const CUtensorMap* mg, const CUtensorMap* mu, const CUtensorMap* md) {
    const uint32_t ring = smem_u32(smem), bars = ring + MOE_SLOTS * 16384;
    __nv_bfloat16* xs = (__nv_bfloat16*)(smem + MOE_SLOTS * 16384 + 128);
    float* gu = (float*)(smem + MOE_SLOTS * 16384 + 128 + 2048);
    float* s_v = gu + 4 * 448;
    int* s_i = (int*)(s_v + 16);
    int* s_sel = s_i + 16;
    const int tid = threadIdx.x, warp = __shfl_sync(~0u, tid >> 5, 0), lane = tid & 31;
    if (tid == 0) {
        for (int i = 0; i < MOE_SLOTS; i++) mbar_init(bars + i * 8, 1);
        asm volatile("fence.mbarrier_init.release.cluster;" ::: "memory");
        for (int b = 0; b < MOE_SLOTS; b++) moe_load(b, part, ring, bars, mg, mu, md);
    }
    pdl_wait();
    TL(1, 1);
    float rv[4];
    #pragma unroll
    for (int i = 0; i < 4; i++) rv[i] = g_r[tid + i * K2_THREADS];
    for (int pass = 0; pass < 2; pass++) {
        float bv = -INFINITY; int bi = 0x7fffffff;
        const int excl = pass ? s_sel[0] : -1;
        #pragma unroll
        for (int i = 0; i < 4; i++) {
            const int idx = tid + i * K2_THREADS;
            if (idx != excl && (rv[i] > bv || bi == 0x7fffffff)) { bv = rv[i]; bi = idx; }
        }
        #pragma unroll
        for (int o = 16; o; o >>= 1) {
            float ov = __shfl_xor_sync(~0u, bv, o); int oi = __shfl_xor_sync(~0u, bi, o);
            if (ov > bv || (ov == bv && oi < bi)) { bv = ov; bi = oi; }
        }
        if (lane == 0) { s_v[warp] = bv; s_i[warp] = bi; }
        __syncthreads();
        if (warp == 0) {
            bv = lane < 16 ? s_v[lane] : -INFINITY; bi = lane < 16 ? s_i[lane] : 0x7fffffff;
            #pragma unroll
            for (int o = 16; o; o >>= 1) {
                float ov = __shfl_xor_sync(~0u, bv, o); int oi = __shfl_xor_sync(~0u, bi, o);
                if (ov > bv || (ov == bv && oi < bi)) { bv = ov; bi = oi; }
            }
            if (lane == 0) s_sel[pass] = (bi == 0x7fffffff) ? pass : bi;
        }
        __syncthreads();
    }
    for (int i = tid; i < 1024; i += K2_THREADS) {
        const int tok = s_sel[i >> 9];
        const float2 st = g_stats[tok];
        xs[i] = __float2bfloat16_rn(ln_elem(__bfloat162float(x[(size_t)tok * D_ + (i & 511)]), st.x, st.y));
    }
    if (part == 0 && tid < 2) g_sel[tid] = s_sel[tid];
    __syncthreads();
    const int grp = warp >> 3, nj = warp & 7, g = lane >> 2, t = lane & 3;
    const uint32_t* xw = (const uint32_t*)xs + (g & 1) * 256 + t;
    float acc[4] = {0.f, 0.f, 0.f, 0.f}, acb[4] = {0.f, 0.f, 0.f, 0.f};
    #pragma unroll 1
    for (int j = 0; j < MOE_BOXES / 2; j++) {
        const int b = j * 2 + grp, sl = b % MOE_SLOTS;
        const bool down = j >= 28;
        if (j == 28) {
            __syncthreads();
            for (int i = tid; i < 896; i += K2_THREADS) {
                const float gs = bf16r(gu[i]), us = bf16r(gu[896 + i]);
                const float sl_ = bf16r(gs / (1.0f + __expf(-gs)));
                xs[(i / 448) * 512 + (i % 448)] = __float2bfloat16_rn(sl_ * us);
            }
            __syncthreads();
        }
        const int kbase = (j & 3) * (down ? 56 : 64);
        uint32_t a[8][4];
        #pragma unroll
        for (int ks = 0; ks < 8; ks++) {
            a[ks][1] = 0u; a[ks][3] = 0u;
            const bool on = g < 2 && !(down && ks == 7);
            a[ks][0] = on ? xw[kbase + ks * 8] : 0u; a[ks][2] = on ? xw[kbase + ks * 8 + 4] : 0u;
        }
        mbar_wait(bars + sl * 8, (b / MOE_SLOTS) & 1);
        const uint32_t baddr = ring + sl * 16384 + lane * 128 + ((nj ^ (lane & 7)) * 16);
        uint32_t bf[4][4];
        #pragma unroll
        for (int k2 = 0; k2 < 4; k2++)
            asm volatile("ldmatrix.sync.aligned.m8n8.x4.trans.shared.b16 {%0, %1, %2, %3}, [%4];"
                         : "=r"(bf[k2][0]), "=r"(bf[k2][1]), "=r"(bf[k2][2]), "=r"(bf[k2][3]) : "r"(baddr + k2 * 4096) : "memory");
        if (down) { bf[3][2] = 0u; bf[3][3] = 0u; }
        named_bar(1 + grp, 256);
        if ((tid & 255) == 0 && b + MOE_SLOTS < MOE_BOXES) moe_load(b + MOE_SLOTS, part, ring, bars, mg, mu, md);
        #pragma unroll
        for (int k2 = 0; k2 < 4; k2++) {
            mma16816(acc, a[2 * k2], bf[k2][0], bf[k2][1]);
            mma16816(acb, a[2 * k2 + 1], bf[k2][2], bf[k2][3]);
        }
        if ((j & 3) == 3) {
            if (g < 2) {
                const float2 v = make_float2(acc[0] + acb[0], acc[1] + acb[1]);
                if (!down) *(float2*)&gu[(grp * 2 + g) * 448 + (j >> 2) * 64 + nj * 8 + t * 2] = v;
                else *(float2*)&g_ypart[part][g][(((j - 28) >> 2) * 2 + grp) * 64 + nj * 8 + t * 2] = v;
            }
            #pragma unroll
            for (int i = 0; i < 4; i++) { acc[i] = 0.f; acb[i] = 0.f; }
        }
    }
}

__global__ void __launch_bounds__(K2_THREADS, 1)
k2_attn(const __nv_bfloat16* __restrict__ x, const __nv_bfloat16* __restrict__ w_gate, const __nv_bfloat16* __restrict__ w_up,
        const __nv_bfloat16* __restrict__ w_down, const __grid_constant__ CUtensorMap mg, const __grid_constant__ CUtensorMap mu,
        const __grid_constant__ CUtensorMap md) {
    extern __shared__ __align__(1024) unsigned char smem[];
    TL(1, 0);
    pdl_launch();
    if (blockIdx.x >= 128) { moe_cta(blockIdx.x - 128, smem, x, &mg, &mu, &md); TL(1, 2); return; }
    if (threadIdx.x >= 32 && threadIdx.x < 35) {
        const __nv_bfloat16* w = threadIdx.x == 32 ? w_gate : (threadIdx.x == 33 ? w_up : w_down);
        asm volatile("cp.async.bulk.prefetch.L2.global [%0], %1;" :: "l"(w + (size_t)blockIdx.x * (D_ * F_ / 128)), "r"(D_ * F_ / 64) : "memory");
    }
    const uint32_t sK = smem_u32(smem), sV = sK + 65536, sQ = sV + 98304, sBar = sQ + 16384;
    const int h = blockIdx.x >> 2, qb = blockIdx.x & 3;
    const int warp = __shfl_sync(~0u, threadIdx.x >> 5, 0), lane = threadIdx.x & 31, wg = warp >> 2;
    if (threadIdx.x == 0) {
        mbar_init(sBar, 1); mbar_init(sBar + 8, 1);
        asm volatile("fence.mbarrier_init.release.cluster;" ::: "memory");
        mbar_expect_tx(sBar, 16384 + 16384 + 2 * 8192);
        mbar_expect_tx(sBar + 8, 49152 + 2 * 24576);
    }
    for (int i = threadIdx.x; i < 2048; i += K2_THREADS)
        *(uint4*)(smem + 65536 + 65536 + i * 16) = make_uint4(0x3F803F80u, 0x3F803F80u, 0x3F803F80u, 0x3F803F80u);
    fence_async_smem();
    __syncthreads();
    if (warp == 0) {
        pdl_wait();
        TL(1, 1);
        const uint4* gk = g_K + (size_t)h * 4096;
        const uint4* gv = g_V + (size_t)h * 4096;
        if (lane == 0) bulk_g2s(sQ, g_Q + (size_t)h * 4096 + qb * 1024, 16384, sBar);
        if (lane == 1) bulk_g2s(sK, gk, 16384, sBar);
        if (lane == 2) bulk_g2s(sV, gv, 8192, sBar);
        if (lane == 3) bulk_g2s(sV + 32768, gv + 2048, 8192, sBar);
        if (lane == 4) bulk_g2s(sK + 16384, gk + 1024, 49152, sBar + 8);
        if (lane == 5) bulk_g2s(sV + 8192, gv + 512, 24576, sBar + 8);
        if (lane == 6) bulk_g2s(sV + 32768 + 8192, gv + 2048 + 512, 24576, sBar + 8);
        __syncwarp();
    }
    ExpC c;
    {
        const volatile uint32_t* cc = g_const;
        c.one2 = cc[0]; c.ca2 = cc[1];
    }
    const uint32_t kdesc0 = (uint32_t)make_desc(sK, 128, 256, 0);
    const uint32_t vdesc0 = (uint32_t)make_desc(sV, 128, 32768, 0);
    #pragma unroll 1
    for (int pass = 0; pass < 2; pass++) {
        const bool dry = false;
        if (pass == 0) { mbar_wait(sBar, 0); __syncwarp(); TL(1, 2); }
        const int unit = (pass & 1) * 4 + wg;
        const uint32_t q = (uint32_t)make_desc(sQ + unit * 2048, 128, 256, 0);
        float o[12];
        #pragma unroll 1
        for (int attempt = 0; attempt < 2; attempt++) {
            float s0[16], s1[16], s2[16];
            #pragma unroll
            for (int i = 0; i < 16; i++) { s0[i] = 0.f; s1[i] = 0.f; s2[i] = 0.f; }
            float mx0 = -INFINITY, mx1 = -INFINITY;
            if (attempt) {
                #pragma unroll 1
                for (int it = 0; it < 64; it++) {
                    WG_FENCE();
                    wgmma_qk32(s0, q, kdesc0 + it * 64);
                    WG_COMMIT();
                    wg_wait<0>();
                    touch16(s0);
                    max16(s0, mx0, mx1);
                }
            }
            #pragma unroll
            for (int i = 0; i < 12; i++) o[i] = 0.f;
            WG_FENCE();
            wgmma_qk32(s2, q, kdesc0);
            wgmma_qk32(s0, q, kdesc0 + 64);
            wgmma_qk32(s1, q, kdesc0 + 128);
            WG_COMMIT();
            wg_wait<0>();
            touch16(s0); touch16(s1); touch16(s2);
            max16(s0, mx0, mx1); max16(s1, mx0, mx1); max16(s2, mx0, mx1);
            mx0 = fmaxf(mx0, __shfl_xor_sync(~0u, mx0, 1)); mx0 = fmaxf(mx0, __shfl_xor_sync(~0u, mx0, 2));
            mx1 = fmaxf(mx1, __shfl_xor_sync(~0u, mx1, 1)); mx1 = fmaxf(mx1, __shfl_xor_sync(~0u, mx1, 2));
            const float bias = attempt ? 0.0f : 128.0f * 64.0f;
            const float y0 = ceilf(fmaf(mx0, 128.0f * QS * SC100, bias)), y1 = ceilf(fmaf(mx1, 128.0f * QS * SC100, bias));
            c.nm0 = __shfl_sync(~0u, y0 * (-1.0f / 128.0f), lane); c.nm1 = __shfl_sync(~0u, y1 * (-1.0f / 128.0f), lane);
            c.cd0 = __shfl_sync(~0u, __fmul_rn(16256.0f - y0, __int_as_float(1)), lane);
            c.cd1 = __shfl_sync(~0u, __fmul_rn(16256.0f - y1, __int_as_float(1)), lane);
            uint32_t kd = kdesc0 + 192, vd = vdesc0 + 32;
            {
                uint32_t pa[4], pb[4];
                exp_block<12>(s2, pa, c);
                exp_block<14>(s2 + 8, pb, c);
                WG_FENCE();
                wgmma_pv(o, pa, vdesc0); wgmma_pv(o, pb, vdesc0 + 16);
                WG_COMMIT();
            }
            #pragma unroll 1
            for (int seg = 0; seg < (dry ? 1 : 2); seg++) {
            if (seg) { wg_wait<0>(); mbar_wait(sBar + 8, 0); __syncwarp(); }
            #pragma unroll 1
            for (int it = seg ? 3 : (dry ? 2 : 0); it < (seg ? 21 : 3); it++) {
                uint32_t p[6][4];
                WG_FENCE();
                wgmma_qk32(s2, q, kd);
                WG_COMMIT();
                exp_block<0>(s0, p[0], c);
                exp_block<2>(s0 + 8, p[1], c);
                WG_FENCE();
                wgmma_pv(o, p[0], vd); wgmma_pv(o, p[1], vd + 16);
                wgmma_qk32(s0, q, kd + 64);
                WG_COMMIT();
                wg_wait<1>();
                touch16(s2);
                exp_block<4>(s1, p[2], c);
                exp_block<6>(s1 + 8, p[3], c);
                WG_FENCE();
                wgmma_pv(o, p[2], vd + 32); wgmma_pv(o, p[3], vd + 48);
                wgmma_qk32(s1, q, kd + 128);
                WG_COMMIT();
                wg_wait<1>();
                touch16(s0);
                exp_block<8>(s2, p[4], c);
                exp_block<10>(s2 + 8, p[5], c);
                WG_FENCE();
                wgmma_pv(o, p[4], vd + 64); wgmma_pv(o, p[5], vd + 80);
                WG_COMMIT();
                vd += 96; kd += 192;
                wg_wait<1>();
                touch16(s1);
            }
            }
            wg_wait<0>();
            touch12(o);
            if (attempt) break;
            float big = 0.f;
            #pragma unroll
            for (int i = 0; i < 12; i++) big = fmaxf(big, fabsf(o[i]));
            bool bad = !(big < 1e30f);
            #pragma unroll
            for (int i = 0; i < 12; i++) bad |= (o[i] != o[i]);
            uint32_t any;
            asm volatile("{.reg .pred p, q; setp.ne.u32 p, %1, 0; barrier.cta.red.or.pred.aligned q, %2, 128, p; selp.u32 %0, 1, 0, q;}"
                         : "=r"(any) : "r"((uint32_t)bad), "r"(1 + wg) : "memory");
            if (dry || !__any_sync(~0u, any)) break;
        }
        const int g = lane >> 2, t = lane & 3;
        const int r = (warp & 3) * 16 + g;
        const float i0 = __fdiv_rn(1.0f, o[8]), i1 = __fdiv_rn(1.0f, o[10]);
        uint32_t* ob = (uint32_t*)(g_O + (size_t)(qb * 8 + unit) * 4096 + (h >> 2) * 512 + r * 8) + t;
        const int c0 = ((h & 3) * 2) ^ (r & 7), c1 = ((h & 3) * 2 + 1) ^ (r & 7);
        if (!dry) {
            ob[c0 * 4] = pack_bf16(o[0] * i0, o[1] * i0);
            ob[c1 * 4] = pack_bf16(o[4] * i0, o[5] * i0);
            ob[256 + c0 * 4] = pack_bf16(o[2] * i1, o[3] * i1);
            ob[256 + c1 * 4] = pack_bf16(o[6] * i1, o[7] * i1);
            TL(1, 3 + pass);
        }
    }
}

constexpr int K3_THREADS = 256;
constexpr int K3_SMEM = 65536 + 131072 + 128;

__global__ void __launch_bounds__(K3_THREADS, 1)
k3_out(const __grid_constant__ CUtensorMap wmap, const __nv_bfloat16* __restrict__ x, __nv_bfloat16* __restrict__ out) {
    extern __shared__ __align__(1024) unsigned char smem[];
    const uint32_t sA = smem_u32(smem), sB = sA + 65536, sBar = sB + 131072;
    const int warp = __shfl_sync(~0u, threadIdx.x >> 5, 0), lane = threadIdx.x & 31, wg = warp >> 2;
    const int nt = blockIdx.x & 3, mt = blockIdx.x >> 2;
    TL(2, 0);
    if (threadIdx.x == 0) {
        for (int i = 0; i < 6; i++) mbar_init(sBar + i * 8, 1);
        asm volatile("fence.mbarrier_init.release.cluster;" ::: "memory");
        for (int kh = 0; kh < 2; kh++) {
            mbar_expect_tx(sBar + kh * 8, 65536);
            tma_2d(sB + kh * 32768, &wmap, nt * 128, kh * 256, sBar + kh * 8);
            tma_2d(sB + 65536 + kh * 32768, &wmap, nt * 128 + 64, kh * 256, sBar + kh * 8);
        }
    }
    const int er = threadIdx.x >> 2, ec = (threadIdx.x & 3) * 32;
    const int row = mt * 64 + er;
    uint4 xv[4];
    #pragma unroll
    for (int j = 0; j < 4; j++) xv[j] = __ldg((const uint4*)(x + (size_t)row * D_ + nt * 128 + ec) + j);
    pdl_wait();
    TL(2, 1);
    if (threadIdx.x == 0) {
        for (int q = 0; q < 4; q++) {
            mbar_expect_tx(sBar + 16 + q * 8, 16384);
            bulk_g2s(sA + q * 16384, g_O + (size_t)mt * 4096 + q * 1024, 16384, sBar + 16 + q * 8);
        }
    }
    const int sel0 = g_sel[0], sel1 = g_sel[1];
    const float2 st = g_stats[row];
    uint32_t bb[16];
    {
        const uint32_t xu[16] = {xv[0].x, xv[0].y, xv[0].z, xv[0].w, xv[1].x, xv[1].y, xv[1].z, xv[1].w,
                                 xv[2].x, xv[2].y, xv[2].z, xv[2].w, xv[3].x, xv[3].y, xv[3].z, xv[3].w};
        #pragma unroll
        for (int j = 0; j < 16; j++) bb[j] = pack_bf16(bf16r(bf_lo(xu[j]) - st.x) * st.y, bf16r(bf_hi(xu[j]) - st.x) * st.y);
        const int slot = row == sel0 ? 0 : (row == sel1 ? 1 : -1);
        if (slot >= 0) {
            const float gate = bf16r(1.0f / (1.0f + __expf(-g_r[row])));
            const int c0 = nt * 128 + ec;
            #pragma unroll
            for (int j = 0; j < 16; j++) {
                const float2 a = *(const float2*)&g_ypart[0][slot][c0 + 2 * j], b = *(const float2*)&g_ypart[1][slot][c0 + 2 * j];
                const float2 c = *(const float2*)&g_ypart[2][slot][c0 + 2 * j], d = *(const float2*)&g_ypart[3][slot][c0 + 2 * j];
                bb[j] = pack_bf16(bf_lo(bb[j]) + bf16r(bf16r(a.x + b.x + c.x + d.x) * gate), bf_hi(bb[j]) + bf16r(bf16r(a.y + b.y + c.y + d.y) * gate));
            }
        }
    }
    __syncthreads();
    float acc[32];
    #pragma unroll
    for (int i = 0; i < 32; i++) acc[i] = 0.f;
    const uint64_t da0 = make_desc(sA, 16, 1024, 1);
    const uint64_t db0 = make_desc(sB + wg * 65536, 8192, 1024, 1);
    #pragma unroll 1
    for (int q = 0; q < 4; q++) {
        if ((q & 1) == 0) mbar_wait(sBar + (q >> 1) * 8, 0);
        mbar_wait(sBar + 16 + q * 8, 0);
        WG_FENCE();
        #pragma unroll
        for (int kk = 0; kk < 8; kk++)
            wgmma_n64(acc, da0 + (uint64_t)(q * 1024 + (kk >> 2) * 512 + (kk & 3) * 2), db0 + (uint64_t)(q * 1024 + kk * 128));
        WG_COMMIT();
    }
    wg_wait<0>();
    touch32(acc);
    TL(2, 2);
    __syncthreads();
    {
        const int g = lane >> 2, t = lane & 3;
        unsigned char* sp = smem + ((warp & 3) * 16 + g) * 272 + wg * 128 + t * 4;
        #pragma unroll
        for (int j = 0; j < 8; j++) {
            *(uint32_t*)(sp + j * 16) = pack_bf16(acc[4 * j], acc[4 * j + 1]);
            *(uint32_t*)(sp + 8 * 272 + j * 16) = pack_bf16(acc[4 * j + 2], acc[4 * j + 3]);
        }
    }
    __syncthreads();
    #pragma unroll
    for (int j = 0; j < 4; j++) {
        const uint4 av = *(const uint4*)(smem + er * 272 + ec * 2 + j * 16);
        const uint32_t au[4] = {av.x, av.y, av.z, av.w}, xu[4] = {xv[j].x, xv[j].y, xv[j].z, xv[j].w};
        uint32_t o[4];
        #pragma unroll
        for (int i = 0; i < 4; i++) {
            uint32_t t2;
            asm("add.rn.bf16x2 %0, %1, %2;" : "=r"(t2) : "r"(xu[i]), "r"(au[i]));
            asm("add.rn.bf16x2 %0, %1, %2;" : "=r"(o[i]) : "r"(t2), "r"(bb[j * 4 + i]));
        }
        *((uint4*)(out + (size_t)row * D_ + nt * 128 + ec) + j) = make_uint4(o[0], o[1], o[2], o[3]);
    }
    TL(2, 3);
}

typedef CUresult (*EncodeFn)(CUtensorMap*, CUtensorMapDataType, cuuint32_t, void*, const cuuint64_t*, const cuuint64_t*,
                             const cuuint32_t*, const cuuint32_t*, CUtensorMapInterleave, CUtensorMapSwizzle,
                             CUtensorMapL2promotion, CUtensorMapFloatOOBfill);

void make_wmap(EncodeFn fn, CUtensorMap* map, const void* ptr, int rows, int cols, int box_rows) {
    cuuint64_t dims[2] = {(cuuint64_t)cols, (cuuint64_t)rows};
    cuuint64_t strides[1] = {(cuuint64_t)cols * 2};
    cuuint32_t box[2] = {64, (cuuint32_t)box_rows};
    cuuint32_t es[2] = {1, 1};
    fn(map, CU_TENSOR_MAP_DATA_TYPE_BFLOAT16, 2, (void*)ptr, dims, strides, box, es, CU_TENSOR_MAP_INTERLEAVE_NONE,
       CU_TENSOR_MAP_SWIZZLE_128B, CU_TENSOR_MAP_L2_PROMOTION_L2_256B, CU_TENSOR_MAP_FLOAT_OOB_FILL_NONE);
}

}

extern "C" void kernel_launch(void* const* d_in, const int* in_sizes, int n_in, void* d_out, int out_size) {
    const __nv_bfloat16* x = (const __nv_bfloat16*)d_in[0];
    const __nv_bfloat16* wqkv = (const __nv_bfloat16*)d_in[1];
    const __nv_bfloat16* wo = (const __nv_bfloat16*)d_in[2];
    const __nv_bfloat16* w_r = (const __nv_bfloat16*)d_in[4];
    const __nv_bfloat16* w_gate = (const __nv_bfloat16*)d_in[5];
    const __nv_bfloat16* w_up = (const __nv_bfloat16*)d_in[6];
    const __nv_bfloat16* w_down = (const __nv_bfloat16*)d_in[7];
    __nv_bfloat16* out = (__nv_bfloat16*)d_out;

    static EncodeFn encode = nullptr;
    if (!encode) {
        void* fn = nullptr;
        cudaDriverEntryPointQueryResult qres;
        cudaGetDriverEntryPoint("cuTensorMapEncodeTiled", &fn, cudaEnableDefault, &qres);
        encode = (EncodeFn)fn;
        cudaFuncSetAttribute(k1_ln_qkv, cudaFuncAttributeMaxDynamicSharedMemorySize, K1_SMEM);
        cudaFuncSetAttribute(k2_attn, cudaFuncAttributeMaxDynamicSharedMemorySize, K2_SMEM);
        cudaFuncSetAttribute(k3_out, cudaFuncAttributeMaxDynamicSharedMemorySize, K3_SMEM);
    }
    CUtensorMap map_qkv, map_wo, map_x, map_g, map_u, map_d;
    make_wmap(encode, &map_g, w_gate, D_, F_, 128);
    make_wmap(encode, &map_u, w_up, D_, F_, 128);
    make_wmap(encode, &map_d, w_down, F_, D_, 112);
    make_wmap(encode, &map_x, x, S_, D_, 64);
    make_wmap(encode, &map_qkv, wqkv, D_, 3 * D_, 64);
    make_wmap(encode, &map_wo, wo, D_, D_, 256);

    k1_ln_qkv<<<128, K1_THREADS, K1_SMEM, cudaStreamPerThread>>>(map_qkv, map_x, w_r);
    cudaLaunchAttribute at[1];
    at[0].id = cudaLaunchAttributeProgrammaticStreamSerialization;
    at[0].val.programmaticStreamSerializationAllowed = 1;
    cudaLaunchConfig_t cfg = {};
    cfg.stream = cudaStreamPerThread;
    cfg.attrs = at; cfg.numAttrs = 1;
    cfg.gridDim = dim3(132); cfg.blockDim = dim3(K2_THREADS); cfg.dynamicSmemBytes = K2_SMEM;
    cudaLaunchKernelEx(&cfg, k2_attn, x, w_gate, w_up, w_down, map_g, map_u, map_d);
    cfg.gridDim = dim3(128); cfg.blockDim = dim3(K3_THREADS); cfg.dynamicSmemBytes = K3_SMEM;
    cudaLaunchKernelEx(&cfg, k3_out, map_wo, x, out);
}
```

```cpp
#include <cuda_runtime.h>
#include <cuda_bf16.h>
#include <cuda.h>
#include <stdint.h>

namespace {

constexpr int S_ = 2048, D_ = 512, H_ = 32, F_ = 1792;

constexpr uint32_t PMASK = 0xDB6;

__device__ __align__(1024) uint4 g_QKV[3 * H_ * S_ * 2];
#define g_Q (g_QKV)
#define g_K (g_QKV + H_ * S_ * 2)
#define g_V (g_QKV + 2 * H_ * S_ * 2)
__device__ __align__(1024) uint4 g_O[S_ * D_ / 8];
__device__ float2 g_stats[S_];
__device__ uint32_t g_const[2] = {0x3F803F80u, 0x42294229u};
__device__ float g_r[S_];
__device__ __align__(16) float g_ypart[4][2][D_];
__device__ int g_sel[2];

#define TL(k, p)
#define CK(i)
__device__ __forceinline__ uint32_t smem_u32(const void* p) { return (uint32_t)__cvta_generic_to_shared(p); }
__device__ __forceinline__ float bf16r(float x) { return __bfloat162float(__float2bfloat16_rn(x)); }
__device__ __forceinline__ uint32_t pack_bf16(float lo, float hi) {
    uint32_t r; asm("cvt.rn.bf16x2.f32 %0, %1, %2;" : "=r"(r) : "f"(hi), "f"(lo)); return r;
}
__device__ __forceinline__ float bf_lo(uint32_t u) { return __uint_as_float(u << 16); }
__device__ __forceinline__ float bf_hi(uint32_t u) { return __uint_as_float(u & 0xFFFF0000u); }
__device__ __forceinline__ float ex2(float x) { float y; asm("ex2.approx.ftz.f32 %0, %1;" : "=f"(y) : "f"(x)); return y; }

__device__ __forceinline__ void mbar_init(uint32_t bar, uint32_t count) {
    asm volatile("mbarrier.init.shared::cta.b64 [%0], %1;" :: "r"(bar), "r"(count) : "memory");
}
__device__ __forceinline__ void mbar_expect_tx(uint32_t bar, uint32_t bytes) {
    asm volatile("mbarrier.arrive.expect_tx.shared::cta.b64 _, [%0], %1;" :: "r"(bar), "r"(bytes) : "memory");
}
__device__ __forceinline__ void mbar_arrive(uint32_t bar) {
    asm volatile("mbarrier.arrive.shared::cta.b64 _, [%0];" :: "r"(bar) : "memory");
}
__device__ __forceinline__ void mbar_wait(uint32_t bar, uint32_t parity) {
    uint32_t done;
    #pragma unroll 1
    for (int it = 0; it < (1 << 26); it++) {
        asm volatile("{.reg .pred p; mbarrier.try_wait.parity.shared::cta.b64 p, [%1], %2; selp.u32 %0, 1, 0, p;}"
                     : "=r"(done) : "r"(bar), "r"(parity) : "memory");
        if (done) return;
    }
    __trap();
}
__device__ __forceinline__ void bulk_g2s(uint32_t dst, const void* src, uint32_t bytes, uint32_t bar) {
    asm volatile("cp.async.bulk.shared::cluster.global.mbarrier::complete_tx::bytes [%0], [%1], %2, [%3];"
                 :: "r"(dst), "l"(src), "r"(bytes), "r"(bar) : "memory");
}
__device__ __forceinline__ void tma_2d(uint32_t dst, const CUtensorMap* map, int c0, int c1, uint32_t bar) {
    asm volatile("cp.async.bulk.tensor.2d.shared::cluster.global.mbarrier::complete_tx::bytes [%0], [%1, {%3, %4}], [%2];"
                 :: "r"(dst), "l"(map), "r"(bar), "r"(c0), "r"(c1) : "memory");
}
__device__ __forceinline__ void fence_async_smem() { asm volatile("fence.proxy.async.shared::cta;" ::: "memory"); }
__device__ __forceinline__ void named_bar(int id, int n) { asm volatile("bar.sync %0, %1;" :: "r"(id), "r"(n) : "memory"); }

__device__ __forceinline__ uint64_t make_desc(uint32_t saddr, uint32_t lbo, uint32_t sbo, uint32_t swz) {
    return (uint64_t)((saddr & 0x3FFFF) >> 4) | ((uint64_t)(lbo >> 4) << 16) | ((uint64_t)(sbo >> 4) << 32) | ((uint64_t)swz << 62);
}
#define WG_FENCE() asm volatile("wgmma.fence.sync.aligned;" ::: "memory")
#define WG_COMMIT() asm volatile("wgmma.commit_group.sync.aligned;" ::: "memory")
template <int N> __device__ __forceinline__ void wg_wait() { asm volatile("wgmma.wait_group.sync.aligned %0;" :: "n"(N) : "memory"); }

#define F4(d, o) "+f"(d[o]), "+f"(d[o + 1]), "+f"(d[o + 2]), "+f"(d[o + 3])
#define F16(d, o) F4(d, o), F4(d, o + 4), F4(d, o + 8), F4(d, o + 12)
#define F32(d, o) F16(d, o), F16(d, o + 16)

__device__ __forceinline__ void wgmma_rs_n128(float* d, const uint32_t* a, uint64_t db) {
    asm volatile("wgmma.mma_async.sync.aligned.m64n128k16.f32.bf16.bf16 "
        "{%0,%1,%2,%3,%4,%5,%6,%7,%8,%9,%10,%11,%12,%13,%14,%15,%16,%17,%18,%19,%20,%21,%22,%23,%24,%25,%26,%27,%28,%29,%30,%31,"
        "%32,%33,%34,%35,%36,%37,%38,%39,%40,%41,%42,%43,%44,%45,%46,%47,%48,%49,%50,%51,%52,%53,%54,%55,%56,%57,%58,%59,%60,%61,%62,%63}, "
        "{%64,%65,%66,%67}, %68, 1, 1, 1, 1;\n"
        : F32(d, 0), F32(d, 32) : "r"(a[0]), "r"(a[1]), "r"(a[2]), "r"(a[3]), "l"(db));
}
__device__ __forceinline__ void wgmma_rs_n64(float* d, const uint32_t* a, uint64_t db) {
    asm volatile("wgmma.mma_async.sync.aligned.m64n64k16.f32.bf16.bf16 "
        "{%0,%1,%2,%3,%4,%5,%6,%7,%8,%9,%10,%11,%12,%13,%14,%15,%16,%17,%18,%19,%20,%21,%22,%23,%24,%25,%26,%27,%28,%29,%30,%31}, "
        "{%32,%33,%34,%35}, %36, 1, 1, 1, 1;\n"
        : F32(d, 0) : "r"(a[0]), "r"(a[1]), "r"(a[2]), "r"(a[3]), "l"(db));
}
__device__ __forceinline__ void wgmma_n64(float* d, uint64_t da, uint64_t db) {
    asm volatile("wgmma.mma_async.sync.aligned.m64n64k16.f32.bf16.bf16 "
        "{%0,%1,%2,%3,%4,%5,%6,%7,%8,%9,%10,%11,%12,%13,%14,%15,%16,%17,%18,%19,%20,%21,%22,%23,%24,%25,%26,%27,%28,%29,%30,%31}, "
        "%32, %33, 1, 1, 1, 0, 1;\n"
        : F32(d, 0) : "l"(da), "l"(db));
}
__device__ __forceinline__ void wgmma_qk32(float* d, uint32_t qd, uint32_t kd) {
    asm volatile("{.reg .b64 a, b; mov.b64 a, {%16, 16}; mov.b64 b, {%17, 16};\n"
        "wgmma.mma_async.sync.aligned.m64n32k16.f32.bf16.bf16 {%0,%1,%2,%3,%4,%5,%6,%7,%8,%9,%10,%11,%12,%13,%14,%15}, a, b, 0, 1, 1, 0, 0;}\n"
        : F16(d, 0) : "r"(qd), "r"(kd));
}
__device__ __forceinline__ void wgmma_pv(float* d, const uint32_t* a, uint32_t vd) {
    asm volatile("{.reg .b64 b; mov.b64 b, {%16, 2048};\n"
        "wgmma.mma_async.sync.aligned.m64n24k16.f32.bf16.bf16 {%0,%1,%2,%3,%4,%5,%6,%7,%8,%9,%10,%11}, {%12,%13,%14,%15}, b, 1, 1, 1, 1;}\n"
        : F4(d, 0), F4(d, 4), F4(d, 8) : "r"(a[0]), "r"(a[1]), "r"(a[2]), "r"(a[3]), "r"(vd));
}
__device__ __forceinline__ void touch16(float* d) { asm volatile("" : F16(d, 0) :: "memory"); }
__device__ __forceinline__ void touch12(float* d) { asm volatile("" : F4(d, 0), F4(d, 4), F4(d, 8) :: "memory"); }
__device__ __forceinline__ void touch32(float* d) { asm volatile("" : F32(d, 0) :: "memory"); }
__device__ __forceinline__ void touch64(float* d) { asm volatile("" : F32(d, 0), F32(d, 32) :: "memory"); }

__device__ __forceinline__ float ln_elem(float x, float mean_b, float rden) {
    return bf16r(bf16r(x - mean_b) * rden);
}
__device__ __forceinline__ void pdl_wait() { asm volatile("griddepcontrol.wait;" ::: "memory"); }
__device__ __forceinline__ void pdl_launch() { asm volatile("griddepcontrol.launch_dependents;" ::: "memory"); }
__device__ __forceinline__ void cluster_arrive() { asm volatile("barrier.cluster.arrive.release.aligned;" ::: "memory"); }
__device__ __forceinline__ void cluster_wait() { asm volatile("barrier.cluster.wait.acquire.aligned;" ::: "memory"); }

constexpr int K1_THREADS = 288;
constexpr int K1_SMEM = 131072 + 6 * 16384 + 128 + 1024;

__device__ __forceinline__ void ldsm4(uint32_t* r, uint32_t addr) {
    asm volatile("ldmatrix.sync.aligned.m8n8.x4.shared.b16 {%0, %1, %2, %3}, [%4];" : "=r"(r[0]), "=r"(r[1]), "=r"(r[2]), "=r"(r[3]) : "r"(addr) : "memory");
}
__device__ __forceinline__ void stsm4(uint32_t addr, uint32_t r0, uint32_t r1, uint32_t r2, uint32_t r3) {
    asm volatile("stmatrix.sync.aligned.m8n8.x4.shared.b16 [%0], {%1, %2, %3, %4};" :: "r"(addr), "r"(r0), "r"(r1), "r"(r2), "r"(r3) : "memory");
}
__device__ __forceinline__ void mma16816(float* d, const uint32_t* a, uint32_t b0, uint32_t b1) {
    asm("mma.sync.aligned.m16n8k16.row.col.f32.bf16.bf16.f32 {%0,%1,%2,%3}, {%4,%5,%6,%7}, {%8,%9}, {%0,%1,%2,%3};"
        : "+f"(d[0]), "+f"(d[1]), "+f"(d[2]), "+f"(d[3]) : "r"(a[0]), "r"(a[1]), "r"(a[2]), "r"(a[3]), "r"(b0), "r"(b1));
}
__device__ __forceinline__ uint32_t sub_bf16x2(uint32_t a, uint32_t b) {
    uint32_t d; asm("sub.rn.bf16x2 %0, %1, %2;" : "=r"(d) : "r"(a), "r"(b)); return d;
}
__device__ __forceinline__ uint32_t ln_pair(uint32_t x2, uint32_t mean2, uint32_t rhi2, uint32_t rlo2) {
    const uint32_t d = sub_bf16x2(x2, mean2);
    uint32_t t, y;
    asm("mul.rn.bf16x2 %0, %1, %2;" : "=r"(t) : "r"(d), "r"(rlo2));
    asm("fma.rn.bf16x2 %0, %1, %2, %3;" : "=r"(y) : "r"(d), "r"(rhi2), "r"(t));
    return y;
}
struct LnRow { uint32_t m2, hi2, lo2; };
__device__ __forceinline__ LnRow ln_row(float mean, float rden) {
    LnRow r;
    r.m2 = pack_bf16(mean, mean);
    r.hi2 = pack_bf16(rden, rden);
    const float lo = rden - bf_lo(r.hi2);
    r.lo2 = pack_bf16(lo, lo);
    return r;
}
__device__ __forceinline__ void ln_frag(uint32_t* a, const LnRow& r0, const LnRow& r1) {
    a[0] = ln_pair(a[0], r0.m2, r0.hi2, r0.lo2); a[1] = ln_pair(a[1], r1.m2, r1.hi2, r1.lo2);
    a[2] = ln_pair(a[2], r0.m2, r0.hi2, r0.lo2); a[3] = ln_pair(a[3], r1.m2, r1.hi2, r1.lo2);
}

template <int NJ>
__device__ __forceinline__ void k1_store(const float* acc, int jj0, int nt, int row0, int lane) {
    const int g = lane >> 2, t = lane & 3, g8a = row0 >> 3;
    const int off_qk = g8a * 64 + g * 4 + t, off_v = (row0 + g) * 4 + t;
    #pragma unroll
    for (int jj = 0; jj < NJ; jj++) {
        const int hg = nt * 12 + jj0 + jj;
        const bool isv = hg >= 64;
        const float m = isv ? 1.0f : 8.8817841970012523e-16f;
        uint32_t* base = (uint32_t*)g_QKV + (size_t)hg * 16384 + (isv ? off_v : off_qk);
        const int hs = isv ? 8192 : 32, rs = isv ? 32 : 64;
        base[0] = pack_bf16(acc[8 * jj] * m, acc[8 * jj + 1] * m);
        base[rs] = pack_bf16(acc[8 * jj + 2] * m, acc[8 * jj + 3] * m);
        base[hs] = pack_bf16(acc[8 * jj + 4] * m, acc[8 * jj + 5] * m);
        base[hs + rs] = pack_bf16(acc[8 * jj + 6] * m, acc[8 * jj + 7] * m);
    }
}

__global__ void __launch_bounds__(K1_THREADS, 1)
k1_ln_qkv(const __grid_constant__ CUtensorMap wmap, const __grid_constant__ CUtensorMap xmap, const __nv_bfloat16* __restrict__ w_r) {
    extern __shared__ __align__(1024) unsigned char smem[];
    const uint32_t sA = smem_u32(smem), sB = sA + 131072, sBar = sB + 6 * 16384;
    const int warp = __shfl_sync(~0u, threadIdx.x >> 5, 0), lane = threadIdx.x & 31;
    const int nt = blockIdx.x & 7, mt = blockIdx.x >> 3;
    const int wg = warp >> 2;
    CK(0);
    pdl_launch();
    uint32_t* s_wr = (uint32_t*)(smem + 131072 + 6 * 16384 + 128);
    if (warp == 8) {
        if (lane == 0) {
            for (int i = 0; i < 6; i++) { mbar_init(sBar + i * 8, 1); mbar_init(sBar + 48 + i * 8, 2); }
            mbar_init(sBar + 96, 1); mbar_init(sBar + 104, 1);
            asm volatile("fence.mbarrier_init.release.cluster;" ::: "memory");
            mbar_expect_tx(sBar + 96, 65536); mbar_expect_tx(sBar + 104, 65536);
            for (int i = 0; i < 6; i++) mbar_expect_tx(sBar + i * 8, 16384);
        }
        __syncwarp();
        if (lane < 16) tma_2d(sA + (lane & 7) * 16384 + (lane >> 3) * 8192, &xmap, (lane & 7) * 64, mt * 128 + (lane >> 3) * 64, sBar + 96 + (lane >> 3) * 8);
        named_bar(3, K1_THREADS);
        mbar_wait(sBar + 96, 0);
        if (lane < 12) {
            const int ld = lane >> 1, j = lane & 1;
            tma_2d(sB + ld * 16384 + j * 8192, &wmap, nt * 192 + j * 64, ld * 64, sBar + ld * 8);
        }
        __syncwarp();
        if (lane < 2) {
            for (int ld = 6; ld < 12; ld++) {
                const int sl = ld - 6;
                mbar_wait(sBar + 48 + sl * 8, 0);
                if (lane == 0) mbar_expect_tx(sBar + sl * 8, 16384);
                __syncwarp(3);
                if (ld < 8) tma_2d(sB + sl * 16384 + lane * 8192, &wmap, nt * 192 + lane * 64, ld * 64, sBar + sl * 8);
                else tma_2d(sB + sl * 16384 + lane * 8192, &wmap, nt * 192 + 128, (ld - 8) * 128 + lane * 64, sBar + sl * 8);
            }
        }
        return;
    }
    if (nt == 0) s_wr[threadIdx.x] = __ldg((const uint32_t*)w_r + threadIdx.x);
    named_bar(3, K1_THREADS);
    const int g = lane >> 2, t = lane & 3;
    const int lrow = warp * 16 + (lane & 7) + ((lane >> 3) & 1) * 8;
    const uint32_t lbase = sA + lrow * 128;
    const int lsw = lane & 7, lhi = lane >> 4;
    uint32_t laddr[4];
    #pragma unroll
    for (int k4 = 0; k4 < 4; k4++) laddr[k4] = lbase + (((k4 * 2 + lhi) ^ lsw) * 16);
    CK(1);
    mbar_wait(sBar + 96 + wg * 8, 0);
    CK(2);
    float dsum[4] = {0.f, 0.f, 0.f, 0.f}, dq0[4] = {0.f, 0.f, 0.f, 0.f}, dq1[4] = {0.f, 0.f, 0.f, 0.f};
    float esum[4] = {0.f, 0.f, 0.f, 0.f}, eq0[4] = {0.f, 0.f, 0.f, 0.f}, eq1[4] = {0.f, 0.f, 0.f, 0.f};
    #pragma unroll 2
    for (int pn = 0; pn < 8; pn++) {
        uint32_t a[4][4];
        #pragma unroll
        for (int k4 = 0; k4 < 4; k4++) ldsm4(a[k4], laddr[k4] + pn * 16384);
        #pragma unroll
        for (int k4 = 0; k4 < 4; k4 += 2) {
            mma16816(dsum, a[k4], 0x3F803F80u, 0x3F803F80u);
            mma16816(dq0, a[k4], a[k4][0], a[k4][2]);
            mma16816(dq1, a[k4], a[k4][1], a[k4][3]);
            mma16816(esum, a[k4 + 1], 0x3F803F80u, 0x3F803F80u);
            mma16816(eq0, a[k4 + 1], a[k4 + 1][0], a[k4 + 1][2]);
            mma16816(eq1, a[k4 + 1], a[k4 + 1][1], a[k4 + 1][3]);
        }
    }
    #pragma unroll
    for (int i = 0; i < 4; i++) { dsum[i] += esum[i]; dq0[i] += eq0[i]; dq1[i] += eq1[i]; }
    CK(3);
    const int dsrc = g * 4 + (g >> 1);
    const float sq0 = __shfl_sync(~0u, (g & 1) ? dq0[1] : dq0[0], dsrc), sq1 = __shfl_sync(~0u, (g & 1) ? dq1[3] : dq1[2], dsrc);
    const float mean0 = dsum[0] * (1.0f / D_), mean1 = dsum[2] * (1.0f / D_);
    float var0 = fmaf(-mean0, mean0, sq0 * (1.0f / D_)), var1 = fmaf(-mean1, mean1, sq1 * (1.0f / D_));
    if (__any_sync(~0u, !(mean0 * mean0 <= 16.0f * var0) || !(mean1 * mean1 <= 16.0f * var1))) {
        float q0 = 0.f, q1 = 0.f;
        #pragma unroll 1
        for (int ks = 0; ks < 32; ks++) {
            uint32_t a[4];
            ldsm4(a, lbase + (ks >> 2) * 16384 + ((((ks & 3) * 2 + lhi) ^ lsw) * 16));
            #pragma unroll
            for (int i = 0; i < 4; i++) {
                const float m = (i & 1) ? mean1 : mean0;
                const float d0 = bf_lo(a[i]) - m, d1 = bf_hi(a[i]) - m;
                if (i & 1) q1 = fmaf(d0, d0, fmaf(d1, d1, q1)); else q0 = fmaf(d0, d0, fmaf(d1, d1, q0));
            }
        }
        q0 += __shfl_xor_sync(~0u, q0, 1); q0 += __shfl_xor_sync(~0u, q0, 2);
        q1 += __shfl_xor_sync(~0u, q1, 1); q1 += __shfl_xor_sync(~0u, q1, 2);
        var0 = q0 * (1.0f / D_); var1 = q1 * (1.0f / D_);
    }
    const float rs0 = __frcp_rn(bf16r(__fsqrt_rn(bf16r(bf16r(var0) + 1e-5f))));
    const float rs1 = __frcp_rn(bf16r(__fsqrt_rn(bf16r(bf16r(var1) + 1e-5f))));
    const LnRow lr0 = ln_row(mean0, rs0), lr1 = ln_row(mean1, rs1);
    float acc[64];
    #pragma unroll
    for (int i = 0; i < 64; i++) acc[i] = 0.f;
    float dr[4] = {0.f, 0.f, 0.f, 0.f};
    const uint64_t db0 = make_desc(sB, 8192, 1024, 1);
    #pragma unroll 1
    for (int kc = 0; kc < 8; kc += 2) {
        #pragma unroll
        for (int h2 = 0; h2 < 2; h2++) {
            const int ld = kc + h2, sl = ld < 6 ? ld : ld - 6;
            uint32_t a[4][4];
            #pragma unroll
            for (int k4 = 0; k4 < 4; k4++) ldsm4(a[k4], laddr[k4] + ld * 16384);
            #pragma unroll
            for (int k4 = 0; k4 < 4; k4++) ln_frag(a[k4], lr0, lr1);
            if (nt == 0) {
                #pragma unroll
                for (int k4 = 0; k4 < 4; k4++) mma16816(dr, a[k4], s_wr[(ld * 4 + k4) * 8 + t], s_wr[(ld * 4 + k4) * 8 + 4 + t]);
            }
            mbar_wait(sBar + sl * 8, ld >= 6);
            WG_FENCE();
            #pragma unroll
            for (int k4 = 0; k4 < 4; k4++) wgmma_rs_n128(acc, a[k4], db0 + (uint64_t)(sl * 1024 + k4 * 128));
            WG_COMMIT();
            wg_wait<1>();
            if (ld >= 1 && ld <= 6 && (threadIdx.x & 127) == 0) mbar_arrive(sBar + 48 + (ld - 1) * 8);
        }
    }
    const int row0 = mt * 128 + warp * 16;
    if (nt == 0 && t == 0) {
        g_r[row0 + g] = bf16r(dr[0]); g_r[row0 + g + 8] = bf16r(dr[2]);
        g_stats[row0 + g] = make_float2(bf_lo(lr0.m2), rs0); g_stats[row0 + g + 8] = make_float2(bf_lo(lr1.m2), rs1);
    }
    wg_wait<0>();
    touch64(acc);
    CK(4);
    float acc2[32];
    #pragma unroll
    for (int i = 0; i < 32; i++) acc2[i] = 0.f;
    #pragma unroll 1
    for (int q = 0; q < 4; q++) {
        const int sl = q + 2;
        #pragma unroll
        for (int h2 = 0; h2 < 2; h2++) {
            uint32_t a[4][4];
            #pragma unroll
            for (int k4 = 0; k4 < 4; k4++) ldsm4(a[k4], laddr[k4] + (q * 2 + h2) * 16384);
            #pragma unroll
            for (int k4 = 0; k4 < 4; k4++) ln_frag(a[k4], lr0, lr1);
            if (h2 == 0) mbar_wait(sBar + sl * 8, 1);
            WG_FENCE();
            #pragma unroll
            for (int k4 = 0; k4 < 4; k4++) wgmma_rs_n64(acc2, a[k4], db0 + (uint64_t)(sl * 1024 + (h2 * 4 + k4) * 128));
            WG_COMMIT();
            wg_wait<1>();
        }
        if (q == 0) k1_store<4>(acc, 0, nt, row0, lane);
        if (q == 1) k1_store<4>(acc + 32, 4, nt, row0, lane);
    }
    wg_wait<0>();
    touch32(acc2);
    CK(5);
    k1_store<4>(acc2, 8, nt, row0, lane);
    CK(6);
}

constexpr int K2_THREADS = 512;
constexpr int K2_SMEM = 65536 + 98304 + 16384 + 128;

constexpr float QS = 0.25f * 1.4426950408889634f;
constexpr float SC100 = 1.2676506002282294e30f;
__device__ __forceinline__ uint32_t polyexp2(float s0, float s1, float cd, uint32_t one2, uint32_t ca2) {
    constexpr float A = 128.0f * QS * 1.7763568394002505e-15f;
    float t0, t1;
    asm("fma.rn.f32 %0, %1, %2, %3;" : "=f"(t0) : "f"(s0), "f"(A), "f"(cd));
    asm("fma.rn.f32 %0, %1, %2, %3;" : "=f"(t1) : "f"(s1), "f"(A), "f"(cd));
    uint32_t W, U, h, G;
    asm("cvt.pack.sat.s16.s32 %0, %1, %2;" : "=r"(W) : "r"(__float_as_int(t1)), "r"(__float_as_int(t0)));
    asm("lop3.b32 %0, %1, 0x007F007F, %2, 0xEA;" : "=r"(U) : "r"(W), "r"(one2));
    asm("fma.rn.bf16x2 %0, %1, %2, %3;" : "=r"(h) : "r"(U), "r"(ca2), "r"(0xC300C300u));
    asm("fma.rn.bf16x2 %0, %1, %2, %3;" : "=r"(G) : "r"(h), "r"(U), "r"(0x438B438Bu));
    return W + G - 0x43404340u;
}

struct ExpC { float nm0, nm1, cd0, cd1; uint32_t one2, ca2; };

template <int G>
__device__ __forceinline__ void exp_block(const float* s, uint32_t* p, const ExpC& c) {
    #pragma unroll
    for (int hf = 0; hf < 2; hf++) {
        const float* x = s + hf * 4;
        if ((PMASK >> (G + hf)) & 1) {
            p[hf * 2 + 0] = polyexp2(x[0], x[1], c.cd0, c.one2, c.ca2);
            p[hf * 2 + 1] = polyexp2(x[2], x[3], c.cd1, c.one2, c.ca2);
        } else {
            p[hf * 2 + 0] = pack_bf16(ex2(fmaf(x[0], QS * SC100, c.nm0)), ex2(fmaf(x[1], QS * SC100, c.nm0)));
            p[hf * 2 + 1] = pack_bf16(ex2(fmaf(x[2], QS * SC100, c.nm1)), ex2(fmaf(x[3], QS * SC100, c.nm1)));
        }
    }
}

__device__ __forceinline__ void max16(const float* s, float& mx0, float& mx1) {
    #pragma unroll
    for (int j = 0; j < 4; j++) {
        mx0 = fmaxf(mx0, fmaxf(s[4 * j], s[4 * j + 1]));
        mx1 = fmaxf(mx1, fmaxf(s[4 * j + 2], s[4 * j + 3]));
    }
}

constexpr int MOE_SLOTS = 10, MOE_BOXES = 88;
__device__ __forceinline__ void moe_load(int b, int part, uint32_t ring, uint32_t bars, const CUtensorMap* mg, const CUtensorMap* mu, const CUtensorMap* md) {
    const int sl = b % MOE_SLOTS, grp = b & 1;
    if (b < 56) {
        const int j = b >> 1;
        mbar_expect_tx(bars + sl * 8, 16384);
        tma_2d(ring + sl * 16384, grp ? mu : mg, part * 448 + (j >> 2) * 64, (j & 3) * 128, bars + sl * 8);
    } else {
        const int j = (b - 56) >> 1;
        mbar_expect_tx(bars + sl * 8, 14336);
        tma_2d(ring + sl * 16384, md, ((j >> 2) * 2 + grp) * 64, part * 448 + (j & 3) * 112, bars + sl * 8);
    }
}

__device__ void moe_cta(int part, unsigned char* smem, const __nv_bfloat16* __restrict__ x, const CUtensorMap* mg, const CUtensorMap* mu, const CUtensorMap* md) {
    const uint32_t ring = smem_u32(smem), bars = ring + MOE_SLOTS * 16384;
    __nv_bfloat16* xs = (__nv_bfloat16*)(smem + MOE_SLOTS * 16384 + 256);
    float* gu = (float*)(smem + MOE_SLOTS * 16384 + 256 + 2048);
    float* s_v = gu + 4 * 448;
    int* s_i = (int*)(s_v + 16);
    int* s_sel = s_i + 16;
    const int tid = threadIdx.x, warp = __shfl_sync(~0u, tid >> 5, 0), lane = tid & 31;
    if (tid == 0) {
        for (int i = 0; i < MOE_SLOTS; i++) { mbar_init(bars + i * 8, 1); mbar_init(bars + 128 + i * 8, 8); }
        asm volatile("fence.mbarrier_init.release.cluster;" ::: "memory");
        for (int b = 0; b < MOE_SLOTS; b++) moe_load(b, part, ring, bars, mg, mu, md);
    }
    pdl_wait();
    TL(1, 1);
    float rv[4];
    #pragma unroll
    for (int i = 0; i < 4; i++) rv[i] = g_r[tid + i * K2_THREADS];
    for (int pass = 0; pass < 2; pass++) {
        float bv = -INFINITY; int bi = 0x7fffffff;
        const int excl = pass ? s_sel[0] : -1;
        #pragma unroll
        for (int i = 0; i < 4; i++) {
            const int idx = tid + i * K2_THREADS;
            if (idx != excl && (rv[i] > bv || bi == 0x7fffffff)) { bv = rv[i]; bi = idx; }
        }
        #pragma unroll
        for (int o = 16; o; o >>= 1) {
            float ov = __shfl_xor_sync(~0u, bv, o); int oi = __shfl_xor_sync(~0u, bi, o);
            if (ov > bv || (ov == bv && oi < bi)) { bv = ov; bi = oi; }
        }
        if (lane == 0) { s_v[warp] = bv; s_i[warp] = bi; }
        __syncthreads();
        if (warp == 0) {
            bv = lane < 16 ? s_v[lane] : -INFINITY; bi = lane < 16 ? s_i[lane] : 0x7fffffff;
            #pragma unroll
            for (int o = 16; o; o >>= 1) {
                float ov = __shfl_xor_sync(~0u, bv, o); int oi = __shfl_xor_sync(~0u, bi, o);
                if (ov > bv || (ov == bv && oi < bi)) { bv = ov; bi = oi; }
            }
            if (lane == 0) s_sel[pass] = (bi == 0x7fffffff) ? pass : bi;
        }
        __syncthreads();
    }
    for (int i = tid; i < 1024; i += K2_THREADS) {
        const int tok = s_sel[i >> 9];
        const float2 st = g_stats[tok];
        xs[i] = __float2bfloat16_rn(ln_elem(__bfloat162float(x[(size_t)tok * D_ + (i & 511)]), st.x, st.y));
    }
    if (part == 0 && tid < 2) g_sel[tid] = s_sel[tid];
    __syncthreads();
    const int grp = warp >> 3, nj = warp & 7, g = lane >> 2, t = lane & 3;
    const uint32_t* xw = (const uint32_t*)xs + (g & 1) * 256 + t;
    float acc[4] = {0.f, 0.f, 0.f, 0.f}, acb[4] = {0.f, 0.f, 0.f, 0.f};
    #pragma unroll 1
    for (int j = 0; j < MOE_BOXES / 2; j++) {
        const int b = j * 2 + grp, sl = b % MOE_SLOTS;
        const bool down = j >= 28;
        if (j == 28) {
            __syncthreads();
            for (int i = tid; i < 896; i += K2_THREADS) {
                const float gs = bf16r(gu[i]), us = bf16r(gu[896 + i]);
                const float sl_ = bf16r(gs / (1.0f + __expf(-gs)));
                xs[(i / 448) * 512 + (i % 448)] = __float2bfloat16_rn(sl_ * us);
            }
            __syncthreads();
        }
        const int kbase = (j & 3) * (down ? 56 : 64);
        uint32_t a[8][4];
        #pragma unroll
        for (int ks = 0; ks < 8; ks++) {
            a[ks][1] = 0u; a[ks][3] = 0u;
            const bool on = g < 2 && !(down && ks == 7);
            a[ks][0] = on ? xw[kbase + ks * 8] : 0u; a[ks][2] = on ? xw[kbase + ks * 8 + 4] : 0u;
        }
        mbar_wait(bars + sl * 8, (b / MOE_SLOTS) & 1);
        const uint32_t baddr = ring + sl * 16384 + lane * 128 + ((nj ^ (lane & 7)) * 16);
        uint32_t bf[4][4];
        #pragma unroll
        for (int k2 = 0; k2 < 4; k2++)
            asm volatile("ldmatrix.sync.aligned.m8n8.x4.trans.shared.b16 {%0, %1, %2, %3}, [%4];"
                         : "=r"(bf[k2][0]), "=r"(bf[k2][1]), "=r"(bf[k2][2]), "=r"(bf[k2][3]) : "r"(baddr + k2 * 4096) : "memory");
        if (down) { bf[3][2] = 0u; bf[3][3] = 0u; }
        __syncwarp();
        if (lane == 0) mbar_arrive(bars + 128 + sl * 8);
        if ((tid & 255) == 0 && j >= 1 && b - 2 + MOE_SLOTS < MOE_BOXES) {
            mbar_wait(bars + 128 + ((b - 2) % MOE_SLOTS) * 8, ((b - 2) / MOE_SLOTS) & 1);
            moe_load(b - 2 + MOE_SLOTS, part, ring, bars, mg, mu, md);
        }
        __syncwarp();
        #pragma unroll
        for (int k2 = 0; k2 < 4; k2++) {
            mma16816(acc, a[2 * k2], bf[k2][0], bf[k2][1]);
            mma16816(acb, a[2 * k2 + 1], bf[k2][2], bf[k2][3]);
        }
        if ((j & 3) == 3) {
            if (g < 2) {
                const float2 v = make_float2(acc[0] + acb[0], acc[1] + acb[1]);
                if (!down) *(float2*)&gu[(grp * 2 + g) * 448 + (j >> 2) * 64 + nj * 8 + t * 2] = v;
                else *(float2*)&g_ypart[part][g][(((j - 28) >> 2) * 2 + grp) * 64 + nj * 8 + t * 2] = v;
            }
            #pragma unroll
            for (int i = 0; i < 4; i++) { acc[i] = 0.f; acb[i] = 0.f; }
        }
    }
}

__global__ void __launch_bounds__(K2_THREADS, 1)
k2_attn(const __nv_bfloat16* __restrict__ x, const __nv_bfloat16* __restrict__ w_gate, const __nv_bfloat16* __restrict__ w_up,
        const __nv_bfloat16* __restrict__ w_down, const __grid_constant__ CUtensorMap mg, const __grid_constant__ CUtensorMap mu,
        const __grid_constant__ CUtensorMap md) {
    extern __shared__ __align__(1024) unsigned char smem[];
    TL(1, 0);
    pdl_launch();
    if (blockIdx.x >= 128) { moe_cta(blockIdx.x - 128, smem, x, &mg, &mu, &md); TL(1, 2); return; }
    if (threadIdx.x >= 32 && threadIdx.x < 35) {
        const __nv_bfloat16* w = threadIdx.x == 32 ? w_gate : (threadIdx.x == 33 ? w_up : w_down);
        asm volatile("cp.async.bulk.prefetch.L2.global [%0], %1;" :: "l"(w + (size_t)blockIdx.x * (D_ * F_ / 128)), "r"(D_ * F_ / 64) : "memory");
    }
    const uint32_t sK = smem_u32(smem), sV = sK + 65536, sQ = sV + 98304, sBar = sQ + 16384;
    const int h = blockIdx.x >> 2, qb = blockIdx.x & 3;
    const int warp = __shfl_sync(~0u, threadIdx.x >> 5, 0), lane = threadIdx.x & 31, wg = warp >> 2;
    if (threadIdx.x == 0) {
        mbar_init(sBar, 1); mbar_init(sBar + 8, 1);
        asm volatile("fence.mbarrier_init.release.cluster;" ::: "memory");
        mbar_expect_tx(sBar, 16384 + 16384 + 2 * 8192);
        mbar_expect_tx(sBar + 8, 49152 + 2 * 24576);
    }
    for (int i = threadIdx.x; i < 2048; i += K2_THREADS)
        *(uint4*)(smem + 65536 + 65536 + i * 16) = make_uint4(0x3F803F80u, 0x3F803F80u, 0x3F803F80u, 0x3F803F80u);
    fence_async_smem();
    __syncthreads();
    if (warp == 0) {
        pdl_wait();
        TL(1, 1);
        const uint4* gk = g_K + (size_t)h * 4096;
        const uint4* gv = g_V + (size_t)h * 4096;
        if (lane == 0) bulk_g2s(sQ, g_Q + (size_t)h * 4096 + qb * 1024, 16384, sBar);
        if (lane == 1) bulk_g2s(sK, gk, 16384, sBar);
        if (lane == 2) bulk_g2s(sV, gv, 8192, sBar);
        if (lane == 3) bulk_g2s(sV + 32768, gv + 2048, 8192, sBar);
        if (lane == 4) bulk_g2s(sK + 16384, gk + 1024, 49152, sBar + 8);
        if (lane == 5) bulk_g2s(sV + 8192, gv + 512, 24576, sBar + 8);
        if (lane == 6) bulk_g2s(sV + 32768 + 8192, gv + 2048 + 512, 24576, sBar + 8);
        __syncwarp();
    }
    ExpC c;
    {
        const volatile uint32_t* cc = g_const;
        c.one2 = cc[0]; c.ca2 = cc[1];
    }
    const uint32_t kdesc0 = (uint32_t)make_desc(sK, 128, 256, 0);
    const uint32_t vdesc0 = (uint32_t)make_desc(sV, 128, 32768, 0);
    #pragma unroll 1
    for (int pass = 0; pass < 2; pass++) {
        const bool dry = false;
        if (pass == 0) { mbar_wait(sBar, 0); __syncwarp(); TL(1, 2); }
        const int unit = (pass & 1) * 4 + wg;
        const uint32_t q = (uint32_t)make_desc(sQ + unit * 2048, 128, 256, 0);
        float o[12];
        #pragma unroll 1
        for (int attempt = 0; attempt < 2; attempt++) {
            float s0[16], s1[16], s2[16];
            #pragma unroll
            for (int i = 0; i < 16; i++) { s0[i] = 0.f; s1[i] = 0.f; s2[i] = 0.f; }
            float mx0 = -INFINITY, mx1 = -INFINITY;
            if (attempt) {
                #pragma unroll 1
                for (int it = 0; it < 64; it++) {
                    WG_FENCE();
                    wgmma_qk32(s0, q, kdesc0 + it * 64);
                    WG_COMMIT();
                    wg_wait<0>();
                    touch16(s0);
                    max16(s0, mx0, mx1);
                }
            }
            #pragma unroll
            for (int i = 0; i < 12; i++) o[i] = 0.f;
            WG_FENCE();
            wgmma_qk32(s2, q, kdesc0);
            wgmma_qk32(s0, q, kdesc0 + 64);
            wgmma_qk32(s1, q, kdesc0 + 128);
            WG_COMMIT();
            wg_wait<0>();
            touch16(s0); touch16(s1); touch16(s2);
            max16(s0, mx0, mx1); max16(s1, mx0, mx1); max16(s2, mx0, mx1);
            mx0 = fmaxf(mx0, __shfl_xor_sync(~0u, mx0, 1)); mx0 = fmaxf(mx0, __shfl_xor_sync(~0u, mx0, 2));
            mx1 = fmaxf(mx1, __shfl_xor_sync(~0u, mx1, 1)); mx1 = fmaxf(mx1, __shfl_xor_sync(~0u, mx1, 2));
            const float bias = attempt ? 0.0f : 128.0f * 64.0f;
            const float y0 = ceilf(fmaf(mx0, 128.0f * QS * SC100, bias)), y1 = ceilf(fmaf(mx1, 128.0f * QS * SC100, bias));
            c.nm0 = __shfl_sync(~0u, y0 * (-1.0f / 128.0f), lane); c.nm1 = __shfl_sync(~0u, y1 * (-1.0f / 128.0f), lane);
            c.cd0 = __shfl_sync(~0u, __fmul_rn(16256.0f - y0, __int_as_float(1)), lane);
            c.cd1 = __shfl_sync(~0u, __fmul_rn(16256.0f - y1, __int_as_float(1)), lane);
            uint32_t kd = kdesc0 + 192, vd = vdesc0 + 32;
            {
                uint32_t pa[4], pb[4];
                exp_block<12>(s2, pa, c);
                exp_block<14>(s2 + 8, pb, c);
                WG_FENCE();
                wgmma_pv(o, pa, vdesc0); wgmma_pv(o, pb, vdesc0 + 16);
                WG_COMMIT();
            }
            #pragma unroll 1
            for (int seg = 0; seg < (dry ? 1 : 2); seg++) {
            if (seg) { wg_wait<0>(); mbar_wait(sBar + 8, 0); __syncwarp(); }
            #pragma unroll 1
            for (int it = seg ? 3 : (dry ? 2 : 0); it < (seg ? 21 : 3); it++) {
                uint32_t p[6][4];
                WG_FENCE();
                wgmma_qk32(s2, q, kd);
                WG_COMMIT();
                exp_block<0>(s0, p[0], c);
                exp_block<2>(s0 + 8, p[1], c);
                WG_FENCE();
                wgmma_pv(o, p[0], vd); wgmma_pv(o, p[1], vd + 16);
                wgmma_qk32(s0, q, kd + 64);
                WG_COMMIT();
                wg_wait<1>();
                touch16(s2);
                exp_block<4>(s1, p[2], c);
                exp_block<6>(s1 + 8, p[3], c);
                WG_FENCE();
                wgmma_pv(o, p[2], vd + 32); wgmma_pv(o, p[3], vd + 48);
                wgmma_qk32(s1, q, kd + 128);
                WG_COMMIT();
                wg_wait<1>();
                touch16(s0);
                exp_block<8>(s2, p[4], c);
                exp_block<10>(s2 + 8, p[5], c);
                WG_FENCE();
                wgmma_pv(o, p[4], vd + 64); wgmma_pv(o, p[5], vd + 80);
                WG_COMMIT();
                vd += 96; kd += 192;
                wg_wait<1>();
                touch16(s1);
            }
            }
            wg_wait<0>();
            touch12(o);
            if (attempt) break;
            float big = 0.f;
            #pragma unroll
            for (int i = 0; i < 12; i++) big = fmaxf(big, fabsf(o[i]));
            bool bad = !(big < 1e30f);
            #pragma unroll
            for (int i = 0; i < 12; i++) bad |= (o[i] != o[i]);
            uint32_t any;
            asm volatile("{.reg .pred p, q; setp.ne.u32 p, %1, 0; barrier.cta.red.or.pred.aligned q, %2, 128, p; selp.u32 %0, 1, 0, q;}"
                         : "=r"(any) : "r"((uint32_t)bad), "r"(1 + wg) : "memory");
            if (dry || !__any_sync(~0u, any)) break;
        }
        const int g = lane >> 2, t = lane & 3;
        const int r = (warp & 3) * 16 + g;
        const float i0 = __fdiv_rn(1.0f, o[8]), i1 = __fdiv_rn(1.0f, o[10]);
        uint32_t* ob = (uint32_t*)(g_O + (size_t)(qb * 8 + unit) * 4096 + (h >> 2) * 512 + r * 8) + t;
        const int c0 = ((h & 3) * 2) ^ (r & 7), c1 = ((h & 3) * 2 + 1) ^ (r & 7);
        if (!dry) {
            ob[c0 * 4] = pack_bf16(o[0] * i0, o[1] * i0);
            ob[c1 * 4] = pack_bf16(o[4] * i0, o[5] * i0);
            ob[256 + c0 * 4] = pack_bf16(o[2] * i1, o[3] * i1);
            ob[256 + c1 * 4] = pack_bf16(o[6] * i1, o[7] * i1);
            TL(1, 3 + pass);
        }
    }
}

constexpr int K3_THREADS = 256;
constexpr int K3_SMEM = 65536 + 131072 + 128;

__global__ void __launch_bounds__(K3_THREADS, 1)
k3_out(const __grid_constant__ CUtensorMap wmap, const __nv_bfloat16* __restrict__ x, __nv_bfloat16* __restrict__ out) {
    extern __shared__ __align__(1024) unsigned char smem[];
    const uint32_t sA = smem_u32(smem), sB = sA + 65536, sBar = sB + 131072;
    const int warp = __shfl_sync(~0u, threadIdx.x >> 5, 0), lane = threadIdx.x & 31, wg = warp >> 2;
    const int nt = blockIdx.x & 3, mt = blockIdx.x >> 2;
    TL(2, 0);
    if (threadIdx.x == 0) {
        for (int i = 0; i < 6; i++) mbar_init(sBar + i * 8, 1);
        asm volatile("fence.mbarrier_init.release.cluster;" ::: "memory");
        for (int kh = 0; kh < 2; kh++) {
            mbar_expect_tx(sBar + kh * 8, 65536);
            tma_2d(sB + kh * 32768, &wmap, nt * 128, kh * 256, sBar + kh * 8);
            tma_2d(sB + 65536 + kh * 32768, &wmap, nt * 128 + 64, kh * 256, sBar + kh * 8);
        }
    }
    const int er = threadIdx.x >> 2, ec = (threadIdx.x & 3) * 32;
    const int row = mt * 64 + er;
    uint4 xv[4];
    #pragma unroll
    for (int j = 0; j < 4; j++) xv[j] = __ldg((const uint4*)(x + (size_t)row * D_ + nt * 128 + ec) + j);
    pdl_wait();
    TL(2, 1);
    if (threadIdx.x == 0) {
        for (int q = 0; q < 4; q++) {
            mbar_expect_tx(sBar + 16 + q * 8, 16384);
            bulk_g2s(sA + q * 16384, g_O + (size_t)mt * 4096 + q * 1024, 16384, sBar + 16 + q * 8);
        }
    }
    const int sel0 = g_sel[0], sel1 = g_sel[1];
    const float2 st = g_stats[row];
    uint32_t bb[16];
    {
        const uint32_t xu[16] = {xv[0].x, xv[0].y, xv[0].z, xv[0].w, xv[1].x, xv[1].y, xv[1].z, xv[1].w,
                                 xv[2].x, xv[2].y, xv[2].z, xv[2].w, xv[3].x, xv[3].y, xv[3].z, xv[3].w};
        #pragma unroll
        for (int j = 0; j < 16; j++) bb[j] = pack_bf16(bf16r(bf_lo(xu[j]) - st.x) * st.y, bf16r(bf_hi(xu[j]) - st.x) * st.y);
        const int slot = row == sel0 ? 0 : (row == sel1 ? 1 : -1);
        if (slot >= 0) {
            const float gate = bf16r(1.0f / (1.0f + __expf(-g_r[row])));
            const int c0 = nt * 128 + ec;
            #pragma unroll
            for (int j = 0; j < 16; j++) {
                const float2 a = *(const float2*)&g_ypart[0][slot][c0 + 2 * j], b = *(const float2*)&g_ypart[1][slot][c0 + 2 * j];
                const float2 c = *(const float2*)&g_ypart[2][slot][c0 + 2 * j], d = *(const float2*)&g_ypart[3][slot][c0 + 2 * j];
                bb[j] = pack_bf16(bf_lo(bb[j]) + bf16r(bf16r(a.x + b.x + c.x + d.x) * gate), bf_hi(bb[j]) + bf16r(bf16r(a.y + b.y + c.y + d.y) * gate));
            }
        }
    }
    __syncthreads();
    float acc[32];
    #pragma unroll
    for (int i = 0; i < 32; i++) acc[i] = 0.f;
    const uint64_t da0 = make_desc(sA, 16, 1024, 1);
    const uint64_t db0 = make_desc(sB + wg * 65536, 8192, 1024, 1);
    #pragma unroll 1
    for (int q = 0; q < 4; q++) {
        if ((q & 1) == 0) mbar_wait(sBar + (q >> 1) * 8, 0);
        mbar_wait(sBar + 16 + q * 8, 0);
        WG_FENCE();
        #pragma unroll
        for (int kk = 0; kk < 8; kk++)
            wgmma_n64(acc, da0 + (uint64_t)(q * 1024 + (kk >> 2) * 512 + (kk & 3) * 2), db0 + (uint64_t)(q * 1024 + kk * 128));
        WG_COMMIT();
    }
    wg_wait<0>();
    touch32(acc);
    TL(2, 2);
    __syncthreads();
    {
        const int g = lane >> 2, t = lane & 3;
        unsigned char* sp = smem + ((warp & 3) * 16 + g) * 272 + wg * 128 + t * 4;
        #pragma unroll
        for (int j = 0; j < 8; j++) {
            *(uint32_t*)(sp + j * 16) = pack_bf16(acc[4 * j], acc[4 * j + 1]);
            *(uint32_t*)(sp + 8 * 272 + j * 16) = pack_bf16(acc[4 * j + 2], acc[4 * j + 3]);
        }
    }
    __syncthreads();
    #pragma unroll
    for (int j = 0; j < 4; j++) {
        const uint4 av = *(const uint4*)(smem + er * 272 + ec * 2 + j * 16);
        const uint32_t au[4] = {av.x, av.y, av.z, av.w}, xu[4] = {xv[j].x, xv[j].y, xv[j].z, xv[j].w};
        uint32_t o[4];
        #pragma unroll
        for (int i = 0; i < 4; i++) {
            uint32_t t2;
            asm("add.rn.bf16x2 %0, %1, %2;" : "=r"(t2) : "r"(xu[i]), "r"(au[i]));
            asm("add.rn.bf16x2 %0, %1, %2;" : "=r"(o[i]) : "r"(t2), "r"(bb[j * 4 + i]));
        }
        *((uint4*)(out + (size_t)row * D_ + nt * 128 + ec) + j) = make_uint4(o[0], o[1], o[2], o[3]);
    }
    TL(2, 3);
}

typedef CUresult (*EncodeFn)(CUtensorMap*, CUtensorMapDataType, cuuint32_t, void*, const cuuint64_t*, const cuuint64_t*,
                             const cuuint32_t*, const cuuint32_t*, CUtensorMapInterleave, CUtensorMapSwizzle,
                             CUtensorMapL2promotion, CUtensorMapFloatOOBfill);

void make_wmap(EncodeFn fn, CUtensorMap* map, const void* ptr, int rows, int cols, int box_rows) {
    cuuint64_t dims[2] = {(cuuint64_t)cols, (cuuint64_t)rows};
    cuuint64_t strides[1] = {(cuuint64_t)cols * 2};
    cuuint32_t box[2] = {64, (cuuint32_t)box_rows};
    cuuint32_t es[2] = {1, 1};
    fn(map, CU_TENSOR_MAP_DATA_TYPE_BFLOAT16, 2, (void*)ptr, dims, strides, box, es, CU_TENSOR_MAP_INTERLEAVE_NONE,
       CU_TENSOR_MAP_SWIZZLE_128B, CU_TENSOR_MAP_L2_PROMOTION_L2_256B, CU_TENSOR_MAP_FLOAT_OOB_FILL_NONE);
}

}

extern "C" void kernel_launch(void* const* d_in, const int* in_sizes, int n_in, void* d_out, int out_size) {
    const __nv_bfloat16* x = (const __nv_bfloat16*)d_in[0];
    const __nv_bfloat16* wqkv = (const __nv_bfloat16*)d_in[1];
    const __nv_bfloat16* wo = (const __nv_bfloat16*)d_in[2];
    const __nv_bfloat16* w_r = (const __nv_bfloat16*)d_in[4];
    const __nv_bfloat16* w_gate = (const __nv_bfloat16*)d_in[5];
    const __nv_bfloat16* w_up = (const __nv_bfloat16*)d_in[6];
    const __nv_bfloat16* w_down = (const __nv_bfloat16*)d_in[7];
    __nv_bfloat16* out = (__nv_bfloat16*)d_out;

    static EncodeFn encode = nullptr;
    if (!encode) {
        void* fn = nullptr;
        cudaDriverEntryPointQueryResult qres;
        cudaGetDriverEntryPoint("cuTensorMapEncodeTiled", &fn, cudaEnableDefault, &qres);
        encode = (EncodeFn)fn;
        cudaFuncSetAttribute(k1_ln_qkv, cudaFuncAttributeMaxDynamicSharedMemorySize, K1_SMEM);
        cudaFuncSetAttribute(k2_attn, cudaFuncAttributeMaxDynamicSharedMemorySize, K2_SMEM);
        cudaFuncSetAttribute(k3_out, cudaFuncAttributeMaxDynamicSharedMemorySize, K3_SMEM);
    }
    CUtensorMap map_qkv, map_wo, map_x, map_g, map_u, map_d;
    make_wmap(encode, &map_g, w_gate, D_, F_, 128);
    make_wmap(encode, &map_u, w_up, D_, F_, 128);
    make_wmap(encode, &map_d, w_down, F_, D_, 112);
    make_wmap(encode, &map_x, x, S_, D_, 64);
    make_wmap(encode, &map_qkv, wqkv, D_, 3 * D_, 64);
    make_wmap(encode, &map_wo, wo, D_, D_, 256);

    k1_ln_qkv<<<128, K1_THREADS, K1_SMEM, cudaStreamPerThread>>>(map_qkv, map_x, w_r);
    cudaLaunchAttribute at[1];
    at[0].id = cudaLaunchAttributeProgrammaticStreamSerialization;
    at[0].val.programmaticStreamSerializationAllowed = 1;
    cudaLaunchConfig_t cfg = {};
    cfg.stream = cudaStreamPerThread;
    cfg.attrs = at; cfg.numAttrs = 1;
    cfg.gridDim = dim3(132); cfg.blockDim = dim3(K2_THREADS); cfg.dynamicSmemBytes = K2_SMEM;
    cudaLaunchKernelEx(&cfg, k2_attn, x, w_gate, w_up, w_down, map_g, map_u, map_d);
    cfg.gridDim = dim3(128); cfg.blockDim = dim3(K3_THREADS); cfg.dynamicSmemBytes = K3_SMEM;
    cudaLaunchKernelEx(&cfg, k3_out, map_wo, x, out);
}
```

```cpp
#include <cuda_runtime.h>
#include <cuda_bf16.h>
#include <cuda.h>
#include <stdint.h>

namespace {

constexpr int S_ = 2048, D_ = 512, H_ = 32, F_ = 1792;

constexpr uint32_t PMASK = 0xDB6;

__device__ __align__(1024) uint4 g_QKV[3 * H_ * S_ * 2];
#define g_Q (g_QKV)
#define g_K (g_QKV + H_ * S_ * 2)
#define g_V (g_QKV + 2 * H_ * S_ * 2)
__device__ __align__(1024) uint4 g_O[S_ * D_ / 8];
__device__ float2 g_stats[S_];
__device__ uint32_t g_const[2] = {0x3F803F80u, 0x42294229u};
__device__ float g_r[S_];
__device__ __align__(16) float g_ypart[4][2][D_];
__device__ int g_sel[2];

#define TL(k, p)
#define CK(i)
__device__ __forceinline__ uint32_t smem_u32(const void* p) { return (uint32_t)__cvta_generic_to_shared(p); }
__device__ __forceinline__ float bf16r(float x) { return __bfloat162float(__float2bfloat16_rn(x)); }
__device__ __forceinline__ uint32_t pack_bf16(float lo, float hi) {
    uint32_t r; asm("cvt.rn.bf16x2.f32 %0, %1, %2;" : "=r"(r) : "f"(hi), "f"(lo)); return r;
}
__device__ __forceinline__ float bf_lo(uint32_t u) { return __uint_as_float(u << 16); }
__device__ __forceinline__ float bf_hi(uint32_t u) { return __uint_as_float(u & 0xFFFF0000u); }
__device__ __forceinline__ float ex2(float x) { float y; asm("ex2.approx.ftz.f32 %0, %1;" : "=f"(y) : "f"(x)); return y; }

__device__ __forceinline__ void mbar_init(uint32_t bar, uint32_t count) {
    asm volatile("mbarrier.init.shared::cta.b64 [%0], %1;" :: "r"(bar), "r"(count) : "memory");
}
__device__ __forceinline__ void mbar_expect_tx(uint32_t bar, uint32_t bytes) {
    asm volatile("mbarrier.arrive.expect_tx.shared::cta.b64 _, [%0], %1;" :: "r"(bar), "r"(bytes) : "memory");
}
__device__ __forceinline__ void mbar_arrive(uint32_t bar) {
    asm volatile("mbarrier.arrive.shared::cta.b64 _, [%0];" :: "r"(bar) : "memory");
}
__device__ __forceinline__ void mbar_wait(uint32_t bar, uint32_t parity) {
    uint32_t done;
    #pragma unroll 1
    for (int it = 0; it < (1 << 26); it++) {
        asm volatile("{.reg .pred p; mbarrier.try_wait.parity.shared::cta.b64 p, [%1], %2; selp.u32 %0, 1, 0, p;}"
                     : "=r"(done) : "r"(bar), "r"(parity) : "memory");
        if (done) return;
    }
    __trap();
}
__device__ __forceinline__ void bulk_g2s(uint32_t dst, const void* src, uint32_t bytes, uint32_t bar) {
    asm volatile("cp.async.bulk.shared::cluster.global.mbarrier::complete_tx::bytes [%0], [%1], %2, [%3];"
                 :: "r"(dst), "l"(src), "r"(bytes), "r"(bar) : "memory");
}
__device__ __forceinline__ void tma_2d(uint32_t dst, const CUtensorMap* map, int c0, int c1, uint32_t bar) {
    asm volatile("cp.async.bulk.tensor.2d.shared::cluster.global.mbarrier::complete_tx::bytes [%0], [%1, {%3, %4}], [%2];"
                 :: "r"(dst), "l"(map), "r"(bar), "r"(c0), "r"(c1) : "memory");
}
__device__ __forceinline__ void fence_async_smem() { asm volatile("fence.proxy.async.shared::cta;" ::: "memory"); }
__device__ __forceinline__ void named_bar(int id, int n) { asm volatile("bar.sync %0, %1;" :: "r"(id), "r"(n) : "memory"); }

__device__ __forceinline__ uint64_t make_desc(uint32_t saddr, uint32_t lbo, uint32_t sbo, uint32_t swz) {
    return (uint64_t)((saddr & 0x3FFFF) >> 4) | ((uint64_t)(lbo >> 4) << 16) | ((uint64_t)(sbo >> 4) << 32) | ((uint64_t)swz << 62);
}
#define WG_FENCE() asm volatile("wgmma.fence.sync.aligned;" ::: "memory")
#define WG_COMMIT() asm volatile("wgmma.commit_group.sync.aligned;" ::: "memory")
template <int N> __device__ __forceinline__ void wg_wait() { asm volatile("wgmma.wait_group.sync.aligned %0;" :: "n"(N) : "memory"); }

#define F4(d, o) "+f"(d[o]), "+f"(d[o + 1]), "+f"(d[o + 2]), "+f"(d[o + 3])
#define F16(d, o) F4(d, o), F4(d, o + 4), F4(d, o + 8), F4(d, o + 12)
#define F32(d, o) F16(d, o), F16(d, o + 16)

__device__ __forceinline__ void wgmma_rs_n128(float* d, const uint32_t* a, uint64_t db) {
    asm volatile("wgmma.mma_async.sync.aligned.m64n128k16.f32.bf16.bf16 "
        "{%0,%1,%2,%3,%4,%5,%6,%7,%8,%9,%10,%11,%12,%13,%14,%15,%16,%17,%18,%19,%20,%21,%22,%23,%24,%25,%26,%27,%28,%29,%30,%31,"
        "%32,%33,%34,%35,%36,%37,%38,%39,%40,%41,%42,%43,%44,%45,%46,%47,%48,%49,%50,%51,%52,%53,%54,%55,%56,%57,%58,%59,%60,%61,%62,%63}, "
        "{%64,%65,%66,%67}, %68, 1, 1, 1, 1;\n"
        : F32(d, 0), F32(d, 32) : "r"(a[0]), "r"(a[1]), "r"(a[2]), "r"(a[3]), "l"(db));
}
__device__ __forceinline__ void wgmma_rs_n64(float* d, const uint32_t* a, uint64_t db) {
    asm volatile("wgmma.mma_async.sync.aligned.m64n64k16.f32.bf16.bf16 "
        "{%0,%1,%2,%3,%4,%5,%6,%7,%8,%9,%10,%11,%12,%13,%14,%15,%16,%17,%18,%19,%20,%21,%22,%23,%24,%25,%26,%27,%28,%29,%30,%31}, "
        "{%32,%33,%34,%35}, %36, 1, 1, 1, 1;\n"
        : F32(d, 0) : "r"(a[0]), "r"(a[1]), "r"(a[2]), "r"(a[3]), "l"(db));
}
__device__ __forceinline__ void wgmma_n64(float* d, uint64_t da, uint64_t db) {
    asm volatile("wgmma.mma_async.sync.aligned.m64n64k16.f32.bf16.bf16 "
        "{%0,%1,%2,%3,%4,%5,%6,%7,%8,%9,%10,%11,%12,%13,%14,%15,%16,%17,%18,%19,%20,%21,%22,%23,%24,%25,%26,%27,%28,%29,%30,%31}, "
        "%32, %33, 1, 1, 1, 0, 1;\n"
        : F32(d, 0) : "l"(da), "l"(db));
}
__device__ __forceinline__ void wgmma_qk32(float* d, uint32_t qd, uint32_t kd) {
    asm volatile("{.reg .b64 a, b; mov.b64 a, {%16, 16}; mov.b64 b, {%17, 16};\n"
        "wgmma.mma_async.sync.aligned.m64n32k16.f32.bf16.bf16 {%0,%1,%2,%3,%4,%5,%6,%7,%8,%9,%10,%11,%12,%13,%14,%15}, a, b, 0, 1, 1, 0, 0;}\n"
        : F16(d, 0) : "r"(qd), "r"(kd));
}
__device__ __forceinline__ void wgmma_pv(float* d, const uint32_t* a, uint32_t vd) {
    asm volatile("{.reg .b64 b; mov.b64 b, {%16, 2048};\n"
        "wgmma.mma_async.sync.aligned.m64n24k16.f32.bf16.bf16 {%0,%1,%2,%3,%4,%5,%6,%7,%8,%9,%10,%11}, {%12,%13,%14,%15}, b, 1, 1, 1, 1;}\n"
        : F4(d, 0), F4(d, 4), F4(d, 8) : "r"(a[0]), "r"(a[1]), "r"(a[2]), "r"(a[3]), "r"(vd));
}
__device__ __forceinline__ void touch16(float* d) { asm volatile("" : F16(d, 0) :: "memory"); }
__device__ __forceinline__ void touch12(float* d) { asm volatile("" : F4(d, 0), F4(d, 4), F4(d, 8) :: "memory"); }
__device__ __forceinline__ void touch32(float* d) { asm volatile("" : F32(d, 0) :: "memory"); }
__device__ __forceinline__ void touch64(float* d) { asm volatile("" : F32(d, 0), F32(d, 32) :: "memory"); }

__device__ __forceinline__ float ln_elem(float x, float mean_b, float rden) {
    return bf16r(bf16r(x - mean_b) * rden);
}
__device__ __forceinline__ void pdl_wait() { asm volatile("griddepcontrol.wait;" ::: "memory"); }
__device__ __forceinline__ void pdl_launch() { asm volatile("griddepcontrol.launch_dependents;" ::: "memory"); }
__device__ __forceinline__ void cluster_arrive() { asm volatile("barrier.cluster.arrive.release.aligned;" ::: "memory"); }
__device__ __forceinline__ void cluster_wait() { asm volatile("barrier.cluster.wait.acquire.aligned;" ::: "memory"); }

constexpr int K1_THREADS = 288;
constexpr int K1_SMEM = 131072 + 6 * 16384 + 128 + 1024;

__device__ __forceinline__ void ldsm4(uint32_t* r, uint32_t addr) {
    asm volatile("ldmatrix.sync.aligned.m8n8.x4.shared.b16 {%0, %1, %2, %3}, [%4];" : "=r"(r[0]), "=r"(r[1]), "=r"(r[2]), "=r"(r[3]) : "r"(addr) : "memory");
}
__device__ __forceinline__ void stsm4(uint32_t addr, uint32_t r0, uint32_t r1, uint32_t r2, uint32_t r3) {
    asm volatile("stmatrix.sync.aligned.m8n8.x4.shared.b16 [%0], {%1, %2, %3, %4};" :: "r"(addr), "r"(r0), "r"(r1), "r"(r2), "r"(r3) : "memory");
}
__device__ __forceinline__ void mma16816(float* d, const uint32_t* a, uint32_t b0, uint32_t b1) {
    asm("mma.sync.aligned.m16n8k16.row.col.f32.bf16.bf16.f32 {%0,%1,%2,%3}, {%4,%5,%6,%7}, {%8,%9}, {%0,%1,%2,%3};"
        : "+f"(d[0]), "+f"(d[1]), "+f"(d[2]), "+f"(d[3]) : "r"(a[0]), "r"(a[1]), "r"(a[2]), "r"(a[3]), "r"(b0), "r"(b1));
}
__device__ __forceinline__ uint32_t sub_bf16x2(uint32_t a, uint32_t b) {
    uint32_t d; asm("sub.rn.bf16x2 %0, %1, %2;" : "=r"(d) : "r"(a), "r"(b)); return d;
}
__device__ __forceinline__ uint32_t ln_pair(uint32_t x2, uint32_t mean2, uint32_t rhi2, uint32_t rlo2) {
    const uint32_t d = sub_bf16x2(x2, mean2);
    uint32_t t, y;
    asm("mul.rn.bf16x2 %0, %1, %2;" : "=r"(t) : "r"(d), "r"(rlo2));
    asm("fma.rn.bf16x2 %0, %1, %2, %3;" : "=r"(y) : "r"(d), "r"(rhi2), "r"(t));
    return y;
}
struct LnRow { uint32_t m2, hi2, lo2; };
__device__ __forceinline__ LnRow ln_row(float mean, float rden) {
    LnRow r;
    r.m2 = pack_bf16(mean, mean);
    r.hi2 = pack_bf16(rden, rden);
    const float lo = rden - bf_lo(r.hi2);
    r.lo2 = pack_bf16(lo, lo);
    return r;
}
__device__ __forceinline__ void ln_frag(uint32_t* a, const LnRow& r0, const LnRow& r1) {
    a[0] = ln_pair(a[0], r0.m2, r0.hi2, r0.lo2); a[1] = ln_pair(a[1], r1.m2, r1.hi2, r1.lo2);
    a[2] = ln_pair(a[2], r0.m2, r0.hi2, r0.lo2); a[3] = ln_pair(a[3], r1.m2, r1.hi2, r1.lo2);
}

template <int NJ>
__device__ __forceinline__ void k1_store(const float* acc, int jj0, int nt, int row0, int lane) {
    const int g = lane >> 2, t = lane & 3, g8a = row0 >> 3;
    const int off_qk = g8a * 64 + g * 4 + t, off_v = (row0 + g) * 4 + t;
    #pragma unroll
    for (int jj = 0; jj < NJ; jj++) {
        const int hg = nt * 12 + jj0 + jj;
        const bool isv = hg >= 64;
        const float m = isv ? 1.0f : 8.8817841970012523e-16f;
        uint32_t* base = (uint32_t*)g_QKV + (size_t)hg * 16384 + (isv ? off_v : off_qk);
        const int hs = isv ? 8192 : 32, rs = isv ? 32 : 64;
        base[0] = pack_bf16(acc[8 * jj] * m, acc[8 * jj + 1] * m);
        base[rs] = pack_bf16(acc[8 * jj + 2] * m, acc[8 * jj + 3] * m);
        base[hs] = pack_bf16(acc[8 * jj + 4] * m, acc[8 * jj + 5] * m);
        base[hs + rs] = pack_bf16(acc[8 * jj + 6] * m, acc[8 * jj + 7] * m);
    }
}

__global__ void __launch_bounds__(K1_THREADS, 1)
k1_ln_qkv(const __grid_constant__ CUtensorMap wmap, const __grid_constant__ CUtensorMap xmap, const __nv_bfloat16* __restrict__ w_r) {
    extern __shared__ __align__(1024) unsigned char smem[];
    const uint32_t sA = smem_u32(smem), sB = sA + 131072, sBar = sB + 6 * 16384;
    const int warp = __shfl_sync(~0u, threadIdx.x >> 5, 0), lane = threadIdx.x & 31;
    const int nt = blockIdx.x & 7, mt = blockIdx.x >> 3;
    const int wg = warp >> 2;
    CK(0);
    pdl_launch();
    uint32_t* s_wr = (uint32_t*)(smem + 131072 + 6 * 16384 + 128);
    if (warp == 8) {
        if (lane == 0) {
            for (int i = 0; i < 6; i++) { mbar_init(sBar + i * 8, 1); mbar_init(sBar + 48 + i * 8, 2); }
            mbar_init(sBar + 96, 1); mbar_init(sBar + 104, 1);
            asm volatile("fence.mbarrier_init.release.cluster;" ::: "memory");
            mbar_expect_tx(sBar + 96, 65536); mbar_expect_tx(sBar + 104, 65536);
            for (int i = 0; i < 6; i++) mbar_expect_tx(sBar + i * 8, 16384);
        }
        __syncwarp();
        if (lane < 16) tma_2d(sA + (lane & 7) * 16384 + (lane >> 3) * 8192, &xmap, (lane & 7) * 64, mt * 128 + (lane >> 3) * 64, sBar + 96 + (lane >> 3) * 8);
        named_bar(3, K1_THREADS);
        mbar_wait(sBar + 96, 0);
        if (lane < 12) {
            const int ld = lane >> 1, j = lane & 1;
            tma_2d(sB + ld * 16384 + j * 8192, &wmap, nt * 192 + j * 64, ld * 64, sBar + ld * 8);
        }
        __syncwarp();
        if (lane < 2) {
            for (int ld = 6; ld < 12; ld++) {
                const int sl = ld - 6;
                mbar_wait(sBar + 48 + sl * 8, 0);
                if (lane == 0) mbar_expect_tx(sBar + sl * 8, 16384);
                __syncwarp(3);
                if (ld < 8) tma_2d(sB + sl * 16384 + lane * 8192, &wmap, nt * 192 + lane * 64, ld * 64, sBar + sl * 8);
                else tma_2d(sB + sl * 16384 + lane * 8192, &wmap, nt * 192 + 128, (ld - 8) * 128 + lane * 64, sBar + sl * 8);
            }
        }
        return;
    }
    if (nt == 0) s_wr[threadIdx.x] = __ldg((const uint32_t*)w_r + threadIdx.x);
    named_bar(3, K1_THREADS);
    const int g = lane >> 2, t = lane & 3;
    const int lrow = warp * 16 + (lane & 7) + ((lane >> 3) & 1) * 8;
    const uint32_t lbase = sA + lrow * 128;
    const int lsw = lane & 7, lhi = lane >> 4;
    uint32_t laddr[4];
    #pragma unroll
    for (int k4 = 0; k4 < 4; k4++) laddr[k4] = lbase + (((k4 * 2 + lhi) ^ lsw) * 16);
    CK(1);
    mbar_wait(sBar + 96 + wg * 8, 0);
    CK(2);
    float dsum[4] = {0.f, 0.f, 0.f, 0.f}, dq0[4] = {0.f, 0.f, 0.f, 0.f}, dq1[4] = {0.f, 0.f, 0.f, 0.f};
    float esum[4] = {0.f, 0.f, 0.f, 0.f}, eq0[4] = {0.f, 0.f, 0.f, 0.f}, eq1[4] = {0.f, 0.f, 0.f, 0.f};
    #pragma unroll 2
    for (int pn = 0; pn < 8; pn++) {
        uint32_t a[4][4];
        #pragma unroll
        for (int k4 = 0; k4 < 4; k4++) ldsm4(a[k4], laddr[k4] + pn * 16384);
        #pragma unroll
        for (int k4 = 0; k4 < 4; k4 += 2) {
            mma16816(dsum, a[k4], 0x3F803F80u, 0x3F803F80u);
            mma16816(dq0, a[k4], a[k4][0], a[k4][2]);
            mma16816(dq1, a[k4], a[k4][1], a[k4][3]);
            mma16816(esum, a[k4 + 1], 0x3F803F80u, 0x3F803F80u);
            mma16816(eq0, a[k4 + 1], a[k4 + 1][0], a[k4 + 1][2]);
            mma16816(eq1, a[k4 + 1], a[k4 + 1][1], a[k4 + 1][3]);
        }
    }
    #pragma unroll
    for (int i = 0; i < 4; i++) { dsum[i] += esum[i]; dq0[i] += eq0[i]; dq1[i] += eq1[i]; }
    CK(3);
    const int dsrc = g * 4 + (g >> 1);
    const float sq0 = __shfl_sync(~0u, (g & 1) ? dq0[1] : dq0[0], dsrc), sq1 = __shfl_sync(~0u, (g & 1) ? dq1[3] : dq1[2], dsrc);
    const float mean0 = dsum[0] * (1.0f / D_), mean1 = dsum[2] * (1.0f / D_);
    float var0 = fmaf(-mean0, mean0, sq0 * (1.0f / D_)), var1 = fmaf(-mean1, mean1, sq1 * (1.0f / D_));
    if (__any_sync(~0u, !(mean0 * mean0 <= 16.0f * var0) || !(mean1 * mean1 <= 16.0f * var1))) {
        float q0 = 0.f, q1 = 0.f;
        #pragma unroll 1
        for (int ks = 0; ks < 32; ks++) {
            uint32_t a[4];
            ldsm4(a, lbase + (ks >> 2) * 16384 + ((((ks & 3) * 2 + lhi) ^ lsw) * 16));
            #pragma unroll
            for (int i = 0; i < 4; i++) {
                const float m = (i & 1) ? mean1 : mean0;
                const float d0 = bf_lo(a[i]) - m, d1 = bf_hi(a[i]) - m;
                if (i & 1) q1 = fmaf(d0, d0, fmaf(d1, d1, q1)); else q0 = fmaf(d0, d0, fmaf(d1, d1, q0));
            }
        }
        q0 += __shfl_xor_sync(~0u, q0, 1); q0 += __shfl_xor_sync(~0u, q0, 2);
        q1 += __shfl_xor_sync(~0u, q1, 1); q1 += __shfl_xor_sync(~0u, q1, 2);
        var0 = q0 * (1.0f / D_); var1 = q1 * (1.0f / D_);
    }
    const float rs0 = __frcp_rn(bf16r(__fsqrt_rn(bf16r(bf16r(var0) + 1e-5f))));
    const float rs1 = __frcp_rn(bf16r(__fsqrt_rn(bf16r(bf16r(var1) + 1e-5f))));
    const LnRow lr0 = ln_row(mean0, rs0), lr1 = ln_row(mean1, rs1);
    float acc[64];
    #pragma unroll
    for (int i = 0; i < 64; i++) acc[i] = 0.f;
    float dr[4] = {0.f, 0.f, 0.f, 0.f};
    const uint64_t db0 = make_desc(sB, 8192, 1024, 1);
    #pragma unroll 1
    for (int kc = 0; kc < 8; kc += 2) {
        #pragma unroll
        for (int h2 = 0; h2 < 2; h2++) {
            const int ld = kc + h2, sl = ld < 6 ? ld : ld - 6;
            uint32_t a[4][4];
            #pragma unroll
            for (int k4 = 0; k4 < 4; k4++) ldsm4(a[k4], laddr[k4] + ld * 16384);
            #pragma unroll
            for (int k4 = 0; k4 < 4; k4++) ln_frag(a[k4], lr0, lr1);
            if (nt == 0) {
                #pragma unroll
                for (int k4 = 0; k4 < 4; k4++) mma16816(dr, a[k4], s_wr[(ld * 4 + k4) * 8 + t], s_wr[(ld * 4 + k4) * 8 + 4 + t]);
            }
            mbar_wait(sBar + sl * 8, ld >= 6);
            WG_FENCE();
            #pragma unroll
            for (int k4 = 0; k4 < 4; k4++) wgmma_rs_n128(acc, a[k4], db0 + (uint64_t)(sl * 1024 + k4 * 128));
            WG_COMMIT();
            wg_wait<1>();
            if (ld >= 1 && ld <= 6 && (threadIdx.x & 127) == 0) mbar_arrive(sBar + 48 + (ld - 1) * 8);
        }
    }
    const int row0 = mt * 128 + warp * 16;
    if (nt == 0 && t == 0) {
        g_r[row0 + g] = bf16r(dr[0]); g_r[row0 + g + 8] = bf16r(dr[2]);
        g_stats[row0 + g] = make_float2(bf_lo(lr0.m2), rs0); g_stats[row0 + g + 8] = make_float2(bf_lo(lr1.m2), rs1);
    }
    wg_wait<0>();
    touch64(acc);
    CK(4);
    float acc2[32];
    #pragma unroll
    for (int i = 0; i < 32; i++) acc2[i] = 0.f;
    #pragma unroll 1
    for (int q = 0; q < 4; q++) {
        const int sl = q + 2;
        #pragma unroll
        for (int h2 = 0; h2 < 2; h2++) {
            uint32_t a[4][4];
            #pragma unroll
            for (int k4 = 0; k4 < 4; k4++) ldsm4(a[k4], laddr[k4] + (q * 2 + h2) * 16384);
            #pragma unroll
            for (int k4 = 0; k4 < 4; k4++) ln_frag(a[k4], lr0, lr1);
            if (h2 == 0) mbar_wait(sBar + sl * 8, 1);
            WG_FENCE();
            #pragma unroll
            for (int k4 = 0; k4 < 4; k4++) wgmma_rs_n64(acc2, a[k4], db0 + (uint64_t)(sl * 1024 + (h2 * 4 + k4) * 128));
            WG_COMMIT();
            wg_wait<1>();
        }
        if (q == 0) k1_store<4>(acc, 0, nt, row0, lane);
        if (q == 1) k1_store<4>(acc + 32, 4, nt, row0, lane);
    }
    wg_wait<0>();
    touch32(acc2);
    CK(5);
    k1_store<4>(acc2, 8, nt, row0, lane);
    CK(6);
}

constexpr int K2_THREADS = 512;
constexpr int K2_SMEM = 6 * 32768 + 12288;

constexpr float QS = 0.25f * 1.4426950408889634f;
constexpr float SC100 = 1.2676506002282294e30f;
__device__ __forceinline__ uint32_t polyexp2(float s0, float s1, float cd, uint32_t one2, uint32_t ca2) {
    constexpr float A = 128.0f * QS * 1.7763568394002505e-15f;
    float t0, t1;
    asm("fma.rn.f32 %0, %1, %2, %3;" : "=f"(t0) : "f"(s0), "f"(A), "f"(cd));
    asm("fma.rn.f32 %0, %1, %2, %3;" : "=f"(t1) : "f"(s1), "f"(A), "f"(cd));
    uint32_t W, U, h, G;
    asm("cvt.pack.sat.s16.s32 %0, %1, %2;" : "=r"(W) : "r"(__float_as_int(t1)), "r"(__float_as_int(t0)));
    asm("lop3.b32 %0, %1, 0x007F007F, %2, 0xEA;" : "=r"(U) : "r"(W), "r"(one2));
    asm("fma.rn.bf16x2 %0, %1, %2, %3;" : "=r"(h) : "r"(U), "r"(ca2), "r"(0xC300C300u));
    asm("fma.rn.bf16x2 %0, %1, %2, %3;" : "=r"(G) : "r"(h), "r"(U), "r"(0x438B438Bu));
    return W + G - 0x43404340u;
}

struct ExpC { float nm0, nm1, cd0, cd1; uint32_t one2, ca2; };

template <int G>
__device__ __forceinline__ void exp_block(const float* s, uint32_t* p, const ExpC& c) {
    #pragma unroll
    for (int hf = 0; hf < 2; hf++) {
        const float* x = s + hf * 4;
        if ((PMASK >> (G + hf)) & 1) {
            p[hf * 2 + 0] = polyexp2(x[0], x[1], c.cd0, c.one2, c.ca2);
            p[hf * 2 + 1] = polyexp2(x[2], x[3], c.cd1, c.one2, c.ca2);
        } else {
            p[hf * 2 + 0] = pack_bf16(ex2(fmaf(x[0], QS * SC100, c.nm0)), ex2(fmaf(x[1], QS * SC100, c.nm0)));
            p[hf * 2 + 1] = pack_bf16(ex2(fmaf(x[2], QS * SC100, c.nm1)), ex2(fmaf(x[3], QS * SC100, c.nm1)));
        }
    }
}

__device__ __forceinline__ void max16(const float* s, float& mx0, float& mx1) {
    #pragma unroll
    for (int j = 0; j < 4; j++) {
        mx0 = fmaxf(mx0, fmaxf(s[4 * j], s[4 * j + 1]));
        mx1 = fmaxf(mx1, fmaxf(s[4 * j + 2], s[4 * j + 3]));
    }
}

constexpr int MOE_SLOTS = 6, MOE_BOXES = 44;
__device__ __forceinline__ void moe_load(int b, int part, uint32_t ring, uint32_t bars, const CUtensorMap* mg, const CUtensorMap* mu, const CUtensorMap* md) {
    const int sl = b % MOE_SLOTS, grp = b & 1;
    if (b < 28) {
        const int j = b >> 1;
        mbar_expect_tx(bars + sl * 8, 32768);
        tma_2d(ring + sl * 32768, grp ? mu : mg, part * 448 + (j >> 1) * 64, (j & 1) * 256, bars + sl * 8);
    } else {
        const int j = (b - 28) >> 1;
        mbar_expect_tx(bars + sl * 8, 28672);
        tma_2d(ring + sl * 32768, md, ((j >> 1) * 2 + grp) * 64, part * 448 + (j & 1) * 224, bars + sl * 8);
    }
}
__device__ __forceinline__ void mma_2row(float* d, uint32_t a0, uint32_t a2, uint32_t b0, uint32_t b1) {
    asm("mma.sync.aligned.m16n8k16.row.col.f32.bf16.bf16.f32 {%0,%1,%2,%3}, {%4,%5,%6,%5}, {%7,%8}, {%0,%1,%2,%3};"
        : "+f"(d[0]), "+f"(d[1]), "+f"(d[2]), "+f"(d[3]) : "r"(a0), "r"(0u), "r"(a2), "r"(b0), "r"(b1));
}

__device__ void moe_cta(int part, unsigned char* smem, const __nv_bfloat16* __restrict__ x, const CUtensorMap* mg, const CUtensorMap* mu, const CUtensorMap* md) {
    const uint32_t ring = smem_u32(smem), bars = ring + MOE_SLOTS * 32768;
    __nv_bfloat16* xs = (__nv_bfloat16*)(smem + MOE_SLOTS * 32768 + 256);
    float* gu = (float*)(smem + MOE_SLOTS * 32768 + 256 + 2048);
    float* s_v = gu + 4 * 448;
    int* s_i = (int*)(s_v + 16);
    int* s_sel = s_i + 16;
    const int tid = threadIdx.x, warp = __shfl_sync(~0u, tid >> 5, 0), lane = tid & 31;
    if (tid == 0) {
        for (int i = 0; i < MOE_SLOTS; i++) { mbar_init(bars + i * 8, 1); mbar_init(bars + 128 + i * 8, 8); }
        asm volatile("fence.mbarrier_init.release.cluster;" ::: "memory");
        for (int b = 0; b < MOE_SLOTS; b++) moe_load(b, part, ring, bars, mg, mu, md);
    }
    pdl_wait();
    TL(1, 1);
    float rv[4];
    #pragma unroll
    for (int i = 0; i < 4; i++) rv[i] = g_r[tid + i * K2_THREADS];
    for (int pass = 0; pass < 2; pass++) {
        float bv = -INFINITY; int bi = 0x7fffffff;
        const int excl = pass ? s_sel[0] : -1;
        #pragma unroll
        for (int i = 0; i < 4; i++) {
            const int idx = tid + i * K2_THREADS;
            if (idx != excl && (rv[i] > bv || bi == 0x7fffffff)) { bv = rv[i]; bi = idx; }
        }
        #pragma unroll
        for (int o = 16; o; o >>= 1) {
            float ov = __shfl_xor_sync(~0u, bv, o); int oi = __shfl_xor_sync(~0u, bi, o);
            if (ov > bv || (ov == bv && oi < bi)) { bv = ov; bi = oi; }
        }
        if (lane == 0) { s_v[warp] = bv; s_i[warp] = bi; }
        __syncthreads();
        if (warp == 0) {
            bv = lane < 16 ? s_v[lane] : -INFINITY; bi = lane < 16 ? s_i[lane] : 0x7fffffff;
            #pragma unroll
            for (int o = 16; o; o >>= 1) {
                float ov = __shfl_xor_sync(~0u, bv, o); int oi = __shfl_xor_sync(~0u, bi, o);
                if (ov > bv || (ov == bv && oi < bi)) { bv = ov; bi = oi; }
            }
            if (lane == 0) s_sel[pass] = (bi == 0x7fffffff) ? pass : bi;
        }
        __syncthreads();
    }
    for (int i = tid; i < 1024; i += K2_THREADS) {
        const int tok = s_sel[i >> 9];
        const float2 st = g_stats[tok];
        xs[i] = __float2bfloat16_rn(ln_elem(__bfloat162float(x[(size_t)tok * D_ + (i & 511)]), st.x, st.y));
    }
    if (part == 0 && tid < 2) g_sel[tid] = s_sel[tid];
    __syncthreads();
    const int grp = warp >> 3, nj = warp & 7, g = lane >> 2, t = lane & 3;
    const uint32_t* xw = (const uint32_t*)xs + (g & 1) * 256 + t;
    uint32_t a[2][32];
    #pragma unroll
    for (int i = 0; i < 32; i++) { a[0][i] = xw[i * 4]; a[1][i] = xw[128 + i * 4]; }
    #pragma unroll 1
    for (int jp = 0; jp < MOE_BOXES / 4; jp++) {
        const bool down = jp >= 7;
        if (jp == 7) {
            __syncthreads();
            for (int i = tid; i < 896; i += K2_THREADS) {
                const float gs = bf16r(gu[i]), us = bf16r(gu[896 + i]);
                const float sl_ = bf16r(gs / (1.0f + __expf(-gs)));
                xs[(i / 448) * 512 + (i % 448)] = __float2bfloat16_rn(sl_ * us);
            }
            __syncthreads();
            #pragma unroll
            for (int i = 0; i < 28; i++) { a[0][i] = xw[i * 4]; a[1][i] = xw[112 + i * 4]; }
        }
        float acc[4] = {0.f, 0.f, 0.f, 0.f}, acb[4] = {0.f, 0.f, 0.f, 0.f};
        #pragma unroll
        for (int hf = 0; hf < 2; hf++) {
            const int b = (jp * 2 + hf) * 2 + grp, sl = b % MOE_SLOTS;
            mbar_wait(bars + sl * 8, (b / MOE_SLOTS) & 1);
            const uint32_t baddr = ring + sl * 32768 + lane * 128 + ((nj ^ (lane & 7)) * 16);
            uint32_t bf[8][4];
            #pragma unroll
            for (int k2 = 0; k2 < 8; k2++)
                asm volatile("ldmatrix.sync.aligned.m8n8.x4.trans.shared.b16 {%0, %1, %2, %3}, [%4];"
                             : "=r"(bf[k2][0]), "=r"(bf[k2][1]), "=r"(bf[k2][2]), "=r"(bf[k2][3]) : "r"(baddr + k2 * 4096) : "memory");
            #pragma unroll
            for (int k2 = 0; k2 < 7; k2++) {
                mma_2row(acc, a[hf][4 * k2], a[hf][4 * k2 + 1], bf[k2][0], bf[k2][1]);
                mma_2row(acb, a[hf][4 * k2 + 2], a[hf][4 * k2 + 3], bf[k2][2], bf[k2][3]);
            }
            if (!down) {
                mma_2row(acc, a[hf][28], a[hf][29], bf[7][0], bf[7][1]);
                mma_2row(acb, a[hf][30], a[hf][31], bf[7][2], bf[7][3]);
            }
            __syncwarp();
            if (lane == 0) mbar_arrive(bars + 128 + sl * 8);
            if ((tid & 255) == 0 && b >= 2 && b - 2 + MOE_SLOTS < MOE_BOXES) {
                mbar_wait(bars + 128 + ((b - 2) % MOE_SLOTS) * 8, ((b - 2) / MOE_SLOTS) & 1);
                moe_load(b - 2 + MOE_SLOTS, part, ring, bars, mg, mu, md);
            }
            __syncwarp();
        }
        if (g < 2) {
            const float2 v = make_float2(acc[0] + acb[0], acc[1] + acb[1]);
            if (!down) *(float2*)&gu[(grp * 2 + g) * 448 + jp * 64 + nj * 8 + t * 2] = v;
            else *(float2*)&g_ypart[part][g][((jp - 7) * 2 + grp) * 64 + nj * 8 + t * 2] = v;
        }
    }
}

__global__ void __launch_bounds__(K2_THREADS, 1)
k2_attn(const __nv_bfloat16* __restrict__ x, const __nv_bfloat16* __restrict__ w_gate, const __nv_bfloat16* __restrict__ w_up,
        const __nv_bfloat16* __restrict__ w_down, const __grid_constant__ CUtensorMap mg, const __grid_constant__ CUtensorMap mu,
        const __grid_constant__ CUtensorMap md) {
    extern __shared__ __align__(1024) unsigned char smem[];
    TL(1, 0);
    pdl_launch();
    if (blockIdx.x >= 128) { moe_cta(blockIdx.x - 128, smem, x, &mg, &mu, &md); TL(1, 2); return; }
    if (threadIdx.x >= 32 && threadIdx.x < 35) {
        const __nv_bfloat16* w = threadIdx.x == 32 ? w_gate : (threadIdx.x == 33 ? w_up : w_down);
        asm volatile("cp.async.bulk.prefetch.L2.global [%0], %1;" :: "l"(w + (size_t)blockIdx.x * (D_ * F_ / 128)), "r"(D_ * F_ / 64) : "memory");
    }
    const uint32_t sK = smem_u32(smem), sV = sK + 65536, sQ = sV + 98304, sBar = sQ + 16384;
    const int h = blockIdx.x >> 2, qb = blockIdx.x & 3;
    const int warp = __shfl_sync(~0u, threadIdx.x >> 5, 0), lane = threadIdx.x & 31, wg = warp >> 2;
    if (threadIdx.x == 0) {
        mbar_init(sBar, 1); mbar_init(sBar + 8, 1);
        asm volatile("fence.mbarrier_init.release.cluster;" ::: "memory");
        mbar_expect_tx(sBar, 16384 + 16384 + 2 * 8192);
        mbar_expect_tx(sBar + 8, 49152 + 2 * 24576);
    }
    for (int i = threadIdx.x; i < 2048; i += K2_THREADS)
        *(uint4*)(smem + 65536 + 65536 + i * 16) = make_uint4(0x3F803F80u, 0x3F803F80u, 0x3F803F80u, 0x3F803F80u);
    fence_async_smem();
    __syncthreads();
    if (warp == 0) {
        pdl_wait();
        TL(1, 1);
        const uint4* gk = g_K + (size_t)h * 4096;
        const uint4* gv = g_V + (size_t)h * 4096;
        if (lane == 0) bulk_g2s(sQ, g_Q + (size_t)h * 4096 + qb * 1024, 16384, sBar);
        if (lane == 1) bulk_g2s(sK, gk, 16384, sBar);
        if (lane == 2) bulk_g2s(sV, gv, 8192, sBar);
        if (lane == 3) bulk_g2s(sV + 32768, gv + 2048, 8192, sBar);
        if (lane == 4) bulk_g2s(sK + 16384, gk + 1024, 49152, sBar + 8);
        if (lane == 5) bulk_g2s(sV + 8192, gv + 512, 24576, sBar + 8);
        if (lane == 6) bulk_g2s(sV + 32768 + 8192, gv + 2048 + 512, 24576, sBar + 8);
        __syncwarp();
    }
    ExpC c;
    {
        const volatile uint32_t* cc = g_const;
        c.one2 = cc[0]; c.ca2 = cc[1];
    }
    const uint32_t kdesc0 = (uint32_t)make_desc(sK, 128, 256, 0);
    const uint32_t vdesc0 = (uint32_t)make_desc(sV, 128, 32768, 0);
    #pragma unroll 1
    for (int pass = 0; pass < 2; pass++) {
        const bool dry = false;
        if (pass == 0) { mbar_wait(sBar, 0); __syncwarp(); TL(1, 2); }
        const int unit = (pass & 1) * 4 + wg;
        const uint32_t q = (uint32_t)make_desc(sQ + unit * 2048, 128, 256, 0);
        float o[12];
        #pragma unroll 1
        for (int attempt = 0; attempt < 2; attempt++) {
            float s0[16], s1[16], s2[16];
            #pragma unroll
            for (int i = 0; i < 16; i++) { s0[i] = 0.f; s1[i] = 0.f; s2[i] = 0.f; }
            float mx0 = -INFINITY, mx1 = -INFINITY;
            if (attempt) {
                #pragma unroll 1
                for (int it = 0; it < 64; it++) {
                    WG_FENCE();
                    wgmma_qk32(s0, q, kdesc0 + it * 64);
                    WG_COMMIT();
                    wg_wait<0>();
                    touch16(s0);
                    max16(s0, mx0, mx1);
                }
            }
            #pragma unroll
            for (int i = 0; i < 12; i++) o[i] = 0.f;
            WG_FENCE();
            wgmma_qk32(s2, q, kdesc0);
            wgmma_qk32(s0, q, kdesc0 + 64);
            wgmma_qk32(s1, q, kdesc0 + 128);
            WG_COMMIT();
            wg_wait<0>();
            touch16(s0); touch16(s1); touch16(s2);
            max16(s0, mx0, mx1); max16(s1, mx0, mx1); max16(s2, mx0, mx1);
            mx0 = fmaxf(mx0, __shfl_xor_sync(~0u, mx0, 1)); mx0 = fmaxf(mx0, __shfl_xor_sync(~0u, mx0, 2));
            mx1 = fmaxf(mx1, __shfl_xor_sync(~0u, mx1, 1)); mx1 = fmaxf(mx1, __shfl_xor_sync(~0u, mx1, 2));
            const float bias = attempt ? 0.0f : 128.0f * 64.0f;
            const float y0 = ceilf(fmaf(mx0, 128.0f * QS * SC100, bias)), y1 = ceilf(fmaf(mx1, 128.0f * QS * SC100, bias));
            c.nm0 = __shfl_sync(~0u, y0 * (-1.0f / 128.0f), lane); c.nm1 = __shfl_sync(~0u, y1 * (-1.0f / 128.0f), lane);
            c.cd0 = __shfl_sync(~0u, __fmul_rn(16256.0f - y0, __int_as_float(1)), lane);
            c.cd1 = __shfl_sync(~0u, __fmul_rn(16256.0f - y1, __int_as_float(1)), lane);
            uint32_t kd = kdesc0 + 192, vd = vdesc0 + 32;
            {
                uint32_t pa[4], pb[4];
                exp_block<12>(s2, pa, c);
                exp_block<14>(s2 + 8, pb, c);
                WG_FENCE();
                wgmma_pv(o, pa, vdesc0); wgmma_pv(o, pb, vdesc0 + 16);
                WG_COMMIT();
            }
            #pragma unroll 1
            for (int seg = 0; seg < (dry ? 1 : 2); seg++) {
            if (seg) { wg_wait<0>(); mbar_wait(sBar + 8, 0); __syncwarp(); }
            #pragma unroll 1
            for (int it = seg ? 3 : (dry ? 2 : 0); it < (seg ? 21 : 3); it++) {
                uint32_t p[6][4];
                WG_FENCE();
                wgmma_qk32(s2, q, kd);
                WG_COMMIT();
                exp_block<0>(s0, p[0], c);
                exp_block<2>(s0 + 8, p[1], c);
                WG_FENCE();
                wgmma_pv(o, p[0], vd); wgmma_pv(o, p[1], vd + 16);
                wgmma_qk32(s0, q, kd + 64);
                WG_COMMIT();
                wg_wait<1>();
                touch16(s2);
                exp_block<4>(s1, p[2], c);
                exp_block<6>(s1 + 8, p[3], c);
                WG_FENCE();
                wgmma_pv(o, p[2], vd + 32); wgmma_pv(o, p[3], vd + 48);
                wgmma_qk32(s1, q, kd + 128);
                WG_COMMIT();
                wg_wait<1>();
                touch16(s0);
                exp_block<8>(s2, p[4], c);
                exp_block<10>(s2 + 8, p[5], c);
                WG_FENCE();
                wgmma_pv(o, p[4], vd + 64); wgmma_pv(o, p[5], vd + 80);
                WG_COMMIT();
                vd += 96; kd += 192;
                wg_wait<1>();
                touch16(s1);
            }
            }
            wg_wait<0>();
            touch12(o);
            if (attempt) break;
            float big = 0.f;
            #pragma unroll
            for (int i = 0; i < 12; i++) big = fmaxf(big, fabsf(o[i]));
            bool bad = !(big < 1e30f);
            #pragma unroll
            for (int i = 0; i < 12; i++) bad |= (o[i] != o[i]);
            uint32_t any;
            asm volatile("{.reg .pred p, q; setp.ne.u32 p, %1, 0; barrier.cta.red.or.pred.aligned q, %2, 128, p; selp.u32 %0, 1, 0, q;}"
                         : "=r"(any) : "r"((uint32_t)bad), "r"(1 + wg) : "memory");
            if (dry || !__any_sync(~0u, any)) break;
        }
        const int g = lane >> 2, t = lane & 3;
        const int r = (warp & 3) * 16 + g;
        const float i0 = __fdiv_rn(1.0f, o[8]), i1 = __fdiv_rn(1.0f, o[10]);
        uint32_t* ob = (uint32_t*)(g_O + (size_t)(qb * 8 + unit) * 4096 + (h >> 2) * 512 + r * 8) + t;
        const int c0 = ((h & 3) * 2) ^ (r & 7), c1 = ((h & 3) * 2 + 1) ^ (r & 7);
        if (!dry) {
            ob[c0 * 4] = pack_bf16(o[0] * i0, o[1] * i0);
            ob[c1 * 4] = pack_bf16(o[4] * i0, o[5] * i0);
            ob[256 + c0 * 4] = pack_bf16(o[2] * i1, o[3] * i1);
            ob[256 + c1 * 4] = pack_bf16(o[6] * i1, o[7] * i1);
            TL(1, 3 + pass);
        }
    }
}

constexpr int K3_THREADS = 256;
constexpr int K3_SMEM = 65536 + 131072 + 128;

__global__ void __launch_bounds__(K3_THREADS, 1)
k3_out(const __grid_constant__ CUtensorMap wmap, const __nv_bfloat16* __restrict__ x, __nv_bfloat16* __restrict__ out) {
    extern __shared__ __align__(1024) unsigned char smem[];
    const uint32_t sA = smem_u32(smem), sB = sA + 65536, sBar = sB + 131072;
    const int warp = __shfl_sync(~0u, threadIdx.x >> 5, 0), lane = threadIdx.x & 31, wg = warp >> 2;
    const int nt = blockIdx.x & 3, mt = blockIdx.x >> 2;
    TL(2, 0);
    if (threadIdx.x == 0) {
        for (int i = 0; i < 6; i++) mbar_init(sBar + i * 8, 1);
        asm volatile("fence.mbarrier_init.release.cluster;" ::: "memory");
        for (int kh = 0; kh < 2; kh++) {
            mbar_expect_tx(sBar + kh * 8, 65536);
            tma_2d(sB + kh * 32768, &wmap, nt * 128, kh * 256, sBar + kh * 8);
            tma_2d(sB + 65536 + kh * 32768, &wmap, nt * 128 + 64, kh * 256, sBar + kh * 8);
        }
    }
    const int er = threadIdx.x >> 2, ec = (threadIdx.x & 3) * 32;
    const int row = mt * 64 + er;
    uint4 xv[4];
    #pragma unroll
    for (int j = 0; j < 4; j++) xv[j] = __ldg((const uint4*)(x + (size_t)row * D_ + nt * 128 + ec) + j);
    pdl_wait();
    TL(2, 1);
    if (threadIdx.x == 0) {
        for (int q = 0; q < 4; q++) {
            mbar_expect_tx(sBar + 16 + q * 8, 16384);
            bulk_g2s(sA + q * 16384, g_O + (size_t)mt * 4096 + q * 1024, 16384, sBar + 16 + q * 8);
        }
    }
    const int sel0 = g_sel[0], sel1 = g_sel[1];
    const float2 st = g_stats[row];
    uint32_t bb[16];
    {
        const uint32_t xu[16] = {xv[0].x, xv[0].y, xv[0].z, xv[0].w, xv[1].x, xv[1].y, xv[1].z, xv[1].w,
                                 xv[2].x, xv[2].y, xv[2].z, xv[2].w, xv[3].x, xv[3].y, xv[3].z, xv[3].w};
        #pragma unroll
        for (int j = 0; j < 16; j++) bb[j] = pack_bf16(bf16r(bf_lo(xu[j]) - st.x) * st.y, bf16r(bf_hi(xu[j]) - st.x) * st.y);
        const int slot = row == sel0 ? 0 : (row == sel1 ? 1 : -1);
        if (slot >= 0) {
            const float gate = bf16r(1.0f / (1.0f + __expf(-g_r[row])));
            const int c0 = nt * 128 + ec;
            #pragma unroll
            for (int j = 0; j < 16; j++) {
                const float2 a = *(const float2*)&g_ypart[0][slot][c0 + 2 * j], b = *(const float2*)&g_ypart[1][slot][c0 + 2 * j];
                const float2 c = *(const float2*)&g_ypart[2][slot][c0 + 2 * j], d = *(const float2*)&g_ypart[3][slot][c0 + 2 * j];
                bb[j] = pack_bf16(bf_lo(bb[j]) + bf16r(bf16r(a.x + b.x + c.x + d.x) * gate), bf_hi(bb[j]) + bf16r(bf16r(a.y + b.y + c.y + d.y) * gate));
            }
        }
    }
    __syncthreads();
    float acc[32];
    #pragma unroll
    for (int i = 0; i < 32; i++) acc[i] = 0.f;
    const uint64_t da0 = make_desc(sA, 16, 1024, 1);
    const uint64_t db0 = make_desc(sB + wg * 65536, 8192, 1024, 1);
    #pragma unroll 1
    for (int q = 0; q < 4; q++) {
        if ((q & 1) == 0) mbar_wait(sBar + (q >> 1) * 8, 0);
        mbar_wait(sBar + 16 + q * 8, 0);
        WG_FENCE();
        #pragma unroll
        for (int kk = 0; kk < 8; kk++)
            wgmma_n64(acc, da0 + (uint64_t)(q * 1024 + (kk >> 2) * 512 + (kk & 3) * 2), db0 + (uint64_t)(q * 1024 + kk * 128));
        WG_COMMIT();
    }
    wg_wait<0>();
    touch32(acc);
    TL(2, 2);
    __syncthreads();
    {
        const int g = lane >> 2, t = lane & 3;
        unsigned char* sp = smem + ((warp & 3) * 16 + g) * 272 + wg * 128 + t * 4;
        #pragma unroll
        for (int j = 0; j < 8; j++) {
            *(uint32_t*)(sp + j * 16) = pack_bf16(acc[4 * j], acc[4 * j + 1]);
            *(uint32_t*)(sp + 8 * 272 + j * 16) = pack_bf16(acc[4 * j + 2], acc[4 * j + 3]);
        }
    }
    __syncthreads();
    #pragma unroll
    for (int j = 0; j < 4; j++) {
        const uint4 av = *(const uint4*)(smem + er * 272 + ec * 2 + j * 16);
        const uint32_t au[4] = {av.x, av.y, av.z, av.w}, xu[4] = {xv[j].x, xv[j].y, xv[j].z, xv[j].w};
        uint32_t o[4];
        #pragma unroll
        for (int i = 0; i < 4; i++) {
            uint32_t t2;
            asm("add.rn.bf16x2 %0, %1, %2;" : "=r"(t2) : "r"(xu[i]), "r"(au[i]));
            asm("add.rn.bf16x2 %0, %1, %2;" : "=r"(o[i]) : "r"(t2), "r"(bb[j * 4 + i]));
        }
        *((uint4*)(out + (size_t)row * D_ + nt * 128 + ec) + j) = make_uint4(o[0], o[1], o[2], o[3]);
    }
    TL(2, 3);
}

typedef CUresult (*EncodeFn)(CUtensorMap*, CUtensorMapDataType, cuuint32_t, void*, const cuuint64_t*, const cuuint64_t*,
                             const cuuint32_t*, const cuuint32_t*, CUtensorMapInterleave, CUtensorMapSwizzle,
                             CUtensorMapL2promotion, CUtensorMapFloatOOBfill);

void make_wmap(EncodeFn fn, CUtensorMap* map, const void* ptr, int rows, int cols, int box_rows) {
    cuuint64_t dims[2] = {(cuuint64_t)cols, (cuuint64_t)rows};
    cuuint64_t strides[1] = {(cuuint64_t)cols * 2};
    cuuint32_t box[2] = {64, (cuuint32_t)box_rows};
    cuuint32_t es[2] = {1, 1};
    fn(map, CU_TENSOR_MAP_DATA_TYPE_BFLOAT16, 2, (void*)ptr, dims, strides, box, es, CU_TENSOR_MAP_INTERLEAVE_NONE,
       CU_TENSOR_MAP_SWIZZLE_128B, CU_TENSOR_MAP_L2_PROMOTION_L2_256B, CU_TENSOR_MAP_FLOAT_OOB_FILL_NONE);
}

}

extern "C" void kernel_launch(void* const* d_in, const int* in_sizes, int n_in, void* d_out, int out_size) {
    const __nv_bfloat16* x = (const __nv_bfloat16*)d_in[0];
    const __nv_bfloat16* wqkv = (const __nv_bfloat16*)d_in[1];
    const __nv_bfloat16* wo = (const __nv_bfloat16*)d_in[2];
    const __nv_bfloat16* w_r = (const __nv_bfloat16*)d_in[4];
    const __nv_bfloat16* w_gate = (const __nv_bfloat16*)d_in[5];
    const __nv_bfloat16* w_up = (const __nv_bfloat16*)d_in[6];
    const __nv_bfloat16* w_down = (const __nv_bfloat16*)d_in[7];
    __nv_bfloat16* out = (__nv_bfloat16*)d_out;

    static EncodeFn encode = nullptr;
    if (!encode) {
        void* fn = nullptr;
        cudaDriverEntryPointQueryResult qres;
        cudaGetDriverEntryPoint("cuTensorMapEncodeTiled", &fn, cudaEnableDefault, &qres);
        encode = (EncodeFn)fn;
        cudaFuncSetAttribute(k1_ln_qkv, cudaFuncAttributeMaxDynamicSharedMemorySize, K1_SMEM);
        cudaFuncSetAttribute(k2_attn, cudaFuncAttributeMaxDynamicSharedMemorySize, K2_SMEM);
        cudaFuncSetAttribute(k3_out, cudaFuncAttributeMaxDynamicSharedMemorySize, K3_SMEM);
    }
    CUtensorMap map_qkv, map_wo, map_x, map_g, map_u, map_d;
    make_wmap(encode, &map_g, w_gate, D_, F_, 256);
    make_wmap(encode, &map_u, w_up, D_, F_, 256);
    make_wmap(encode, &map_d, w_down, F_, D_, 224);
    make_wmap(encode, &map_x, x, S_, D_, 64);
    make_wmap(encode, &map_qkv, wqkv, D_, 3 * D_, 64);
    make_wmap(encode, &map_wo, wo, D_, D_, 256);

    k1_ln_qkv<<<128, K1_THREADS, K1_SMEM, cudaStreamPerThread>>>(map_qkv, map_x, w_r);
    cudaLaunchAttribute at[1];
    at[0].id = cudaLaunchAttributeProgrammaticStreamSerialization;
    at[0].val.programmaticStreamSerializationAllowed = 1;
    cudaLaunchConfig_t cfg = {};
    cfg.stream = cudaStreamPerThread;
    cfg.attrs = at; cfg.numAttrs = 1;
    cfg.gridDim = dim3(132); cfg.blockDim = dim3(K2_THREADS); cfg.dynamicSmemBytes = K2_SMEM;
    cudaLaunchKernelEx(&cfg, k2_attn, x, w_gate, w_up, w_down, map_g, map_u, map_d);
    cfg.gridDim = dim3(128); cfg.blockDim = dim3(K3_THREADS); cfg.dynamicSmemBytes = K3_SMEM;
    cudaLaunchKernelEx(&cfg, k3_out, map_wo, x, out);
}
```

```cpp
#include <cuda_runtime.h>
#include <cuda_bf16.h>
#include <cuda.h>
#include <stdint.h>

namespace {

constexpr int S_ = 2048, D_ = 512, H_ = 32, F_ = 1792;

constexpr uint32_t PMASK = 0xDB6;

__device__ __align__(1024) uint4 g_QKV[3 * H_ * S_ * 2];
#define g_Q (g_QKV)
#define g_K (g_QKV + H_ * S_ * 2)
#define g_V (g_QKV + 2 * H_ * S_ * 2)
__device__ __align__(1024) uint4 g_O[S_ * D_ / 8];
__device__ float2 g_stats[S_];
__device__ uint32_t g_const[2] = {0x3F803F80u, 0x42294229u};
__device__ float g_r[S_];
__device__ __align__(16) float g_ypart[4][2][D_];
__device__ int g_sel[2];

#define TL(k, p)
#define CK(i)
__device__ __forceinline__ uint32_t smem_u32(const void* p) { return (uint32_t)__cvta_generic_to_shared(p); }
__device__ __forceinline__ float bf16r(float x) { return __bfloat162float(__float2bfloat16_rn(x)); }
__device__ __forceinline__ uint32_t pack_bf16(float lo, float hi) {
    uint32_t r; asm("cvt.rn.bf16x2.f32 %0, %1, %2;" : "=r"(r) : "f"(hi), "f"(lo)); return r;
}
__device__ __forceinline__ float bf_lo(uint32_t u) { return __uint_as_float(u << 16); }
__device__ __forceinline__ float bf_hi(uint32_t u) { return __uint_as_float(u & 0xFFFF0000u); }
__device__ __forceinline__ float ex2(float x) { float y; asm("ex2.approx.ftz.f32 %0, %1;" : "=f"(y) : "f"(x)); return y; }

__device__ __forceinline__ void mbar_init(uint32_t bar, uint32_t count) {
    asm volatile("mbarrier.init.shared::cta.b64 [%0], %1;" :: "r"(bar), "r"(count) : "memory");
}
__device__ __forceinline__ void mbar_expect_tx(uint32_t bar, uint32_t bytes) {
    asm volatile("mbarrier.arrive.expect_tx.shared::cta.b64 _, [%0], %1;" :: "r"(bar), "r"(bytes) : "memory");
}
__device__ __forceinline__ void mbar_arrive(uint32_t bar) {
    asm volatile("mbarrier.arrive.shared::cta.b64 _, [%0];" :: "r"(bar) : "memory");
}
__device__ __forceinline__ void mbar_wait(uint32_t bar, uint32_t parity) {
    uint32_t done;
    #pragma unroll 1
    for (int it = 0; it < (1 << 26); it++) {
        asm volatile("{.reg .pred p; mbarrier.try_wait.parity.shared::cta.b64 p, [%1], %2; selp.u32 %0, 1, 0, p;}"
                     : "=r"(done) : "r"(bar), "r"(parity) : "memory");
        if (done) return;
    }
    __trap();
}
__device__ __forceinline__ void bulk_g2s(uint32_t dst, const void* src, uint32_t bytes, uint32_t bar) {
    asm volatile("cp.async.bulk.shared::cluster.global.mbarrier::complete_tx::bytes [%0], [%1], %2, [%3];"
                 :: "r"(dst), "l"(src), "r"(bytes), "r"(bar) : "memory");
}
__device__ __forceinline__ void tma_2d(uint32_t dst, const CUtensorMap* map, int c0, int c1, uint32_t bar) {
    asm volatile("cp.async.bulk.tensor.2d.shared::cluster.global.mbarrier::complete_tx::bytes [%0], [%1, {%3, %4}], [%2];"
                 :: "r"(dst), "l"(map), "r"(bar), "r"(c0), "r"(c1) : "memory");
}
__device__ __forceinline__ void fence_async_smem() { asm volatile("fence.proxy.async.shared::cta;" ::: "memory"); }
__device__ __forceinline__ void named_bar(int id, int n) { asm volatile("bar.sync %0, %1;" :: "r"(id), "r"(n) : "memory"); }

__device__ __forceinline__ uint64_t make_desc(uint32_t saddr, uint32_t lbo, uint32_t sbo, uint32_t swz) {
    return (uint64_t)((saddr & 0x3FFFF) >> 4) | ((uint64_t)(lbo >> 4) << 16) | ((uint64_t)(sbo >> 4) << 32) | ((uint64_t)swz << 62);
}
#define WG_FENCE() asm volatile("wgmma.fence.sync.aligned;" ::: "memory")
#define WG_COMMIT() asm volatile("wgmma.commit_group.sync.aligned;" ::: "memory")
template <int N> __device__ __forceinline__ void wg_wait() { asm volatile("wgmma.wait_group.sync.aligned %0;" :: "n"(N) : "memory"); }

#define F4(d, o) "+f"(d[o]), "+f"(d[o + 1]), "+f"(d[o + 2]), "+f"(d[o + 3])
#define F16(d, o) F4(d, o), F4(d, o + 4), F4(d, o + 8), F4(d, o + 12)
#define F32(d, o) F16(d, o), F16(d, o + 16)

__device__ __forceinline__ void wgmma_rs_n128(float* d, const uint32_t* a, uint64_t db) {
    asm volatile("wgmma.mma_async.sync.aligned.m64n128k16.f32.bf16.bf16 "
        "{%0,%1,%2,%3,%4,%5,%6,%7,%8,%9,%10,%11,%12,%13,%14,%15,%16,%17,%18,%19,%20,%21,%22,%23,%24,%25,%26,%27,%28,%29,%30,%31,"
        "%32,%33,%34,%35,%36,%37,%38,%39,%40,%41,%42,%43,%44,%45,%46,%47,%48,%49,%50,%51,%52,%53,%54,%55,%56,%57,%58,%59,%60,%61,%62,%63}, "
        "{%64,%65,%66,%67}, %68, 1, 1, 1, 1;\n"
        : F32(d, 0), F32(d, 32) : "r"(a[0]), "r"(a[1]), "r"(a[2]), "r"(a[3]), "l"(db));
}
__device__ __forceinline__ void wgmma_rs_n64(float* d, const uint32_t* a, uint64_t db) {
    asm volatile("wgmma.mma_async.sync.aligned.m64n64k16.f32.bf16.bf16 "
        "{%0,%1,%2,%3,%4,%5,%6,%7,%8,%9,%10,%11,%12,%13,%14,%15,%16,%17,%18,%19,%20,%21,%22,%23,%24,%25,%26,%27,%28,%29,%30,%31}, "
        "{%32,%33,%34,%35}, %36, 1, 1, 1, 1;\n"
        : F32(d, 0) : "r"(a[0]), "r"(a[1]), "r"(a[2]), "r"(a[3]), "l"(db));
}
__device__ __forceinline__ void wgmma_n64(float* d, uint64_t da, uint64_t db) {
    asm volatile("wgmma.mma_async.sync.aligned.m64n64k16.f32.bf16.bf16 "
        "{%0,%1,%2,%3,%4,%5,%6,%7,%8,%9,%10,%11,%12,%13,%14,%15,%16,%17,%18,%19,%20,%21,%22,%23,%24,%25,%26,%27,%28,%29,%30,%31}, "
        "%32, %33, 1, 1, 1, 0, 1;\n"
        : F32(d, 0) : "l"(da), "l"(db));
}
__device__ __forceinline__ void wgmma_qk32(float* d, uint32_t qd, uint32_t kd) {
    asm volatile("{.reg .b64 a, b; mov.b64 a, {%16, 16}; mov.b64 b, {%17, 16};\n"
        "wgmma.mma_async.sync.aligned.m64n32k16.f32.bf16.bf16 {%0,%1,%2,%3,%4,%5,%6,%7,%8,%9,%10,%11,%12,%13,%14,%15}, a, b, 0, 1, 1, 0, 0;}\n"
        : F16(d, 0) : "r"(qd), "r"(kd));
}
__device__ __forceinline__ void wgmma_pv(float* d, const uint32_t* a, uint32_t vd) {
    asm volatile("{.reg .b64 b; mov.b64 b, {%16, 2048};\n"
        "wgmma.mma_async.sync.aligned.m64n24k16.f32.bf16.bf16 {%0,%1,%2,%3,%4,%5,%6,%7,%8,%9,%10,%11}, {%12,%13,%14,%15}, b, 1, 1, 1, 1;}\n"
        : F4(d, 0), F4(d, 4), F4(d, 8) : "r"(a[0]), "r"(a[1]), "r"(a[2]), "r"(a[3]), "r"(vd));
}
__device__ __forceinline__ void touch16(float* d) { asm volatile("" : F16(d, 0) :: "memory"); }
__device__ __forceinline__ void touch12(float* d) { asm volatile("" : F4(d, 0), F4(d, 4), F4(d, 8) :: "memory"); }
__device__ __forceinline__ void touch32(float* d) { asm volatile("" : F32(d, 0) :: "memory"); }
__device__ __forceinline__ void touch64(float* d) { asm volatile("" : F32(d, 0), F32(d, 32) :: "memory"); }

__device__ __forceinline__ float ln_elem(float x, float mean_b, float rden) {
    return bf16r(bf16r(x - mean_b) * rden);
}
__device__ __forceinline__ void pdl_wait() { asm volatile("griddepcontrol.wait;" ::: "memory"); }
__device__ __forceinline__ void pdl_launch() { asm volatile("griddepcontrol.launch_dependents;" ::: "memory"); }
__device__ __forceinline__ void cluster_arrive() { asm volatile("barrier.cluster.arrive.release.aligned;" ::: "memory"); }
__device__ __forceinline__ void cluster_wait() { asm volatile("barrier.cluster.wait.acquire.aligned;" ::: "memory"); }

constexpr int K1_THREADS = 288;
constexpr int K1_SMEM = 131072 + 6 * 16384 + 128 + 1024;

__device__ __forceinline__ void ldsm4(uint32_t* r, uint32_t addr) {
    asm volatile("ldmatrix.sync.aligned.m8n8.x4.shared.b16 {%0, %1, %2, %3}, [%4];" : "=r"(r[0]), "=r"(r[1]), "=r"(r[2]), "=r"(r[3]) : "r"(addr) : "memory");
}
__device__ __forceinline__ void stsm4(uint32_t addr, uint32_t r0, uint32_t r1, uint32_t r2, uint32_t r3) {
    asm volatile("stmatrix.sync.aligned.m8n8.x4.shared.b16 [%0], {%1, %2, %3, %4};" :: "r"(addr), "r"(r0), "r"(r1), "r"(r2), "r"(r3) : "memory");
}
__device__ __forceinline__ void mma16816(float* d, const uint32_t* a, uint32_t b0, uint32_t b1) {
    asm("mma.sync.aligned.m16n8k16.row.col.f32.bf16.bf16.f32 {%0,%1,%2,%3}, {%4,%5,%6,%7}, {%8,%9}, {%0,%1,%2,%3};"
        : "+f"(d[0]), "+f"(d[1]), "+f"(d[2]), "+f"(d[3]) : "r"(a[0]), "r"(a[1]), "r"(a[2]), "r"(a[3]), "r"(b0), "r"(b1));
}
__device__ __forceinline__ uint32_t sub_bf16x2(uint32_t a, uint32_t b) {
    uint32_t d; asm("sub.rn.bf16x2 %0, %1, %2;" : "=r"(d) : "r"(a), "r"(b)); return d;
}
__device__ __forceinline__ uint32_t ln_pair(uint32_t x2, uint32_t mean2, uint32_t rhi2, uint32_t rlo2) {
    const uint32_t d = sub_bf16x2(x2, mean2);
    uint32_t t, y;
    asm("mul.rn.bf16x2 %0, %1, %2;" : "=r"(t) : "r"(d), "r"(rlo2));
    asm("fma.rn.bf16x2 %0, %1, %2, %3;" : "=r"(y) : "r"(d), "r"(rhi2), "r"(t));
    return y;
}
struct LnRow { uint32_t m2, hi2, lo2; };
__device__ __forceinline__ LnRow ln_row(float mean, float rden) {
    LnRow r;
    r.m2 = pack_bf16(mean, mean);
    r.hi2 = pack_bf16(rden, rden);
    const float lo = rden - bf_lo(r.hi2);
    r.lo2 = pack_bf16(lo, lo);
    return r;
}
__device__ __forceinline__ void ln_frag(uint32_t* a, const LnRow& r0, const LnRow& r1) {
    a[0] = ln_pair(a[0], r0.m2, r0.hi2, r0.lo2); a[1] = ln_pair(a[1], r1.m2, r1.hi2, r1.lo2);
    a[2] = ln_pair(a[2], r0.m2, r0.hi2, r0.lo2); a[3] = ln_pair(a[3], r1.m2, r1.hi2, r1.lo2);
}

template <int NJ>
__device__ __forceinline__ void k1_store(const float* acc, int jj0, int nt, int row0, int lane) {
    const int g = lane >> 2, t = lane & 3, g8a = row0 >> 3;
    const int off_qk = g8a * 64 + g * 4 + t, off_v = (row0 + g) * 4 + t;
    #pragma unroll
    for (int jj = 0; jj < NJ; jj++) {
        const int hg = nt * 12 + jj0 + jj;
        const bool isv = hg >= 64;
        const float m = isv ? 1.0f : 8.8817841970012523e-16f;
        uint32_t* base = (uint32_t*)g_QKV + (size_t)hg * 16384 + (isv ? off_v : off_qk);
        const int hs = isv ? 8192 : 32, rs = isv ? 32 : 64;
        base[0] = pack_bf16(acc[8 * jj] * m, acc[8 * jj + 1] * m);
        base[rs] = pack_bf16(acc[8 * jj + 2] * m, acc[8 * jj + 3] * m);
        base[hs] = pack_bf16(acc[8 * jj + 4] * m, acc[8 * jj + 5] * m);
        base[hs + rs] = pack_bf16(acc[8 * jj + 6] * m, acc[8 * jj + 7] * m);
    }
}

__global__ void __launch_bounds__(K1_THREADS, 1)
k1_ln_qkv(const __grid_constant__ CUtensorMap wmap, const __grid_constant__ CUtensorMap xmap, const __nv_bfloat16* __restrict__ w_r) {
    extern __shared__ __align__(1024) unsigned char smem[];
    const uint32_t sA = smem_u32(smem), sB = sA + 131072, sBar = sB + 6 * 16384;
    const int warp = __shfl_sync(~0u, threadIdx.x >> 5, 0), lane = threadIdx.x & 31;
    const int nt = blockIdx.x & 7, mt = blockIdx.x >> 3;
    const int wg = warp >> 2;
    CK(0);
    pdl_launch();
    uint32_t* s_wr = (uint32_t*)(smem + 131072 + 6 * 16384 + 128);
    if (warp == 8) {
        if (lane == 0) {
            for (int i = 0; i < 6; i++) { mbar_init(sBar + i * 8, 1); mbar_init(sBar + 48 + i * 8, 2); }
            mbar_init(sBar + 96, 1); mbar_init(sBar + 104, 1);
            asm volatile("fence.mbarrier_init.release.cluster;" ::: "memory");
            mbar_expect_tx(sBar + 96, 65536); mbar_expect_tx(sBar + 104, 65536);
            for (int i = 0; i < 6; i++) mbar_expect_tx(sBar + i * 8, 16384);
        }
        __syncwarp();
        if (lane < 16) tma_2d(sA + (lane & 7) * 16384 + (lane >> 3) * 8192, &xmap, (lane & 7) * 64, mt * 128 + (lane >> 3) * 64, sBar + 96 + (lane >> 3) * 8);
        named_bar(3, K1_THREADS);
        mbar_wait(sBar + 96, 0);
        if (lane < 12) {
            const int ld = lane >> 1, j = lane & 1;
            tma_2d(sB + ld * 16384 + j * 8192, &wmap, nt * 192 + j * 64, ld * 64, sBar + ld * 8);
        }
        __syncwarp();
        if (lane < 2) {
            for (int ld = 6; ld < 12; ld++) {
                const int sl = ld - 6;
                mbar_wait(sBar + 48 + sl * 8, 0);
                if (lane == 0) mbar_expect_tx(sBar + sl * 8, 16384);
                __syncwarp(3);
                if (ld < 8) tma_2d(sB + sl * 16384 + lane * 8192, &wmap, nt * 192 + lane * 64, ld * 64, sBar + sl * 8);
                else tma_2d(sB + sl * 16384 + lane * 8192, &wmap, nt * 192 + 128, (ld - 8) * 128 + lane * 64, sBar + sl * 8);
            }
        }
        return;
    }
    if (nt == 0) s_wr[threadIdx.x] = __ldg((const uint32_t*)w_r + threadIdx.x);
    named_bar(3, K1_THREADS);
    const int g = lane >> 2, t = lane & 3;
    const int lrow = warp * 16 + (lane & 7) + ((lane >> 3) & 1) * 8;
    const uint32_t lbase = sA + lrow * 128;
    const int lsw = lane & 7, lhi = lane >> 4;
    uint32_t laddr[4];
    #pragma unroll
    for (int k4 = 0; k4 < 4; k4++) laddr[k4] = lbase + (((k4 * 2 + lhi) ^ lsw) * 16);
    CK(1);
    mbar_wait(sBar + 96 + wg * 8, 0);
    CK(2);
    float dsum[4] = {0.f, 0.f, 0.f, 0.f}, dq0[4] = {0.f, 0.f, 0.f, 0.f}, dq1[4] = {0.f, 0.f, 0.f, 0.f};
    float esum[4] = {0.f, 0.f, 0.f, 0.f}, eq0[4] = {0.f, 0.f, 0.f, 0.f}, eq1[4] = {0.f, 0.f, 0.f, 0.f};
    #pragma unroll 2
    for (int pn = 0; pn < 8; pn++) {
        uint32_t a[4][4];
        #pragma unroll
        for (int k4 = 0; k4 < 4; k4++) ldsm4(a[k4], laddr[k4] + pn * 16384);
        #pragma unroll
        for (int k4 = 0; k4 < 4; k4 += 2) {
            mma16816(dsum, a[k4], 0x3F803F80u, 0x3F803F80u);
            mma16816(dq0, a[k4], a[k4][0], a[k4][2]);
            mma16816(dq1, a[k4], a[k4][1], a[k4][3]);
            mma16816(esum, a[k4 + 1], 0x3F803F80u, 0x3F803F80u);
            mma16816(eq0, a[k4 + 1], a[k4 + 1][0], a[k4 + 1][2]);
            mma16816(eq1, a[k4 + 1], a[k4 + 1][1], a[k4 + 1][3]);
        }
    }
    #pragma unroll
    for (int i = 0; i < 4; i++) { dsum[i] += esum[i]; dq0[i] += eq0[i]; dq1[i] += eq1[i]; }
    CK(3);
    const int dsrc = g * 4 + (g >> 1);
    const float sq0 = __shfl_sync(~0u, (g & 1) ? dq0[1] : dq0[0], dsrc), sq1 = __shfl_sync(~0u, (g & 1) ? dq1[3] : dq1[2], dsrc);
    const float mean0 = dsum[0] * (1.0f / D_), mean1 = dsum[2] * (1.0f / D_);
    float var0 = fmaf(-mean0, mean0, sq0 * (1.0f / D_)), var1 = fmaf(-mean1, mean1, sq1 * (1.0f / D_));
    if (__any_sync(~0u, !(mean0 * mean0 <= 16.0f * var0) || !(mean1 * mean1 <= 16.0f * var1))) {
        float q0 = 0.f, q1 = 0.f;
        #pragma unroll 1
        for (int ks = 0; ks < 32; ks++) {
            uint32_t a[4];
            ldsm4(a, lbase + (ks >> 2) * 16384 + ((((ks & 3) * 2 + lhi) ^ lsw) * 16));
            #pragma unroll
            for (int i = 0; i < 4; i++) {
                const float m = (i & 1) ? mean1 : mean0;
                const float d0 = bf_lo(a[i]) - m, d1 = bf_hi(a[i]) - m;
                if (i & 1) q1 = fmaf(d0, d0, fmaf(d1, d1, q1)); else q0 = fmaf(d0, d0, fmaf(d1, d1, q0));
            }
        }
        q0 += __shfl_xor_sync(~0u, q0, 1); q0 += __shfl_xor_sync(~0u, q0, 2);
        q1 += __shfl_xor_sync(~0u, q1, 1); q1 += __shfl_xor_sync(~0u, q1, 2);
        var0 = q0 * (1.0f / D_); var1 = q1 * (1.0f / D_);
    }
    const float rs0 = __frcp_rn(bf16r(__fsqrt_rn(bf16r(bf16r(var0) + 1e-5f))));
    const float rs1 = __frcp_rn(bf16r(__fsqrt_rn(bf16r(bf16r(var1) + 1e-5f))));
    const LnRow lr0 = ln_row(mean0, rs0), lr1 = ln_row(mean1, rs1);
    float acc[64];
    #pragma unroll
    for (int i = 0; i < 64; i++) acc[i] = 0.f;
    float dr[4] = {0.f, 0.f, 0.f, 0.f};
    const uint64_t db0 = make_desc(sB, 8192, 1024, 1);
    #pragma unroll 1
    for (int kc = 0; kc < 8; kc += 2) {
        #pragma unroll
        for (int h2 = 0; h2 < 2; h2++) {
            const int ld = kc + h2, sl = ld < 6 ? ld : ld - 6;
            uint32_t a[4][4];
            #pragma unroll
            for (int k4 = 0; k4 < 4; k4++) ldsm4(a[k4], laddr[k4] + ld * 16384);
            #pragma unroll
            for (int k4 = 0; k4 < 4; k4++) ln_frag(a[k4], lr0, lr1);
            if (nt == 0) {
                #pragma unroll
                for (int k4 = 0; k4 < 4; k4++) mma16816(dr, a[k4], s_wr[(ld * 4 + k4) * 8 + t], s_wr[(ld * 4 + k4) * 8 + 4 + t]);
            }
            mbar_wait(sBar + sl * 8, ld >= 6);
            WG_FENCE();
            #pragma unroll
            for (int k4 = 0; k4 < 4; k4++) wgmma_rs_n128(acc, a[k4], db0 + (uint64_t)(sl * 1024 + k4 * 128));
            WG_COMMIT();
            wg_wait<1>();
            if (ld >= 1 && ld <= 6 && (threadIdx.x & 127) == 0) mbar_arrive(sBar + 48 + (ld - 1) * 8);
        }
    }
    const int row0 = mt * 128 + warp * 16;
    if (nt == 0 && t == 0) {
        g_r[row0 + g] = bf16r(dr[0]); g_r[row0 + g + 8] = bf16r(dr[2]);
        g_stats[row0 + g] = make_float2(bf_lo(lr0.m2), rs0); g_stats[row0 + g + 8] = make_float2(bf_lo(lr1.m2), rs1);
    }
    wg_wait<0>();
    touch64(acc);
    CK(4);
    float acc2[32];
    #pragma unroll
    for (int i = 0; i < 32; i++) acc2[i] = 0.f;
    #pragma unroll 1
    for (int q = 0; q < 4; q++) {
        const int sl = q + 2;
        #pragma unroll
        for (int h2 = 0; h2 < 2; h2++) {
            uint32_t a[4][4];
            #pragma unroll
            for (int k4 = 0; k4 < 4; k4++) ldsm4(a[k4], laddr[k4] + (q * 2 + h2) * 16384);
            #pragma unroll
            for (int k4 = 0; k4 < 4; k4++) ln_frag(a[k4], lr0, lr1);
            if (h2 == 0) mbar_wait(sBar + sl * 8, 1);
            WG_FENCE();
            #pragma unroll
            for (int k4 = 0; k4 < 4; k4++) wgmma_rs_n64(acc2, a[k4], db0 + (uint64_t)(sl * 1024 + (h2 * 4 + k4) * 128));
            WG_COMMIT();
            wg_wait<1>();
        }
        if (q == 0) k1_store<4>(acc, 0, nt, row0, lane);
        if (q == 1) k1_store<4>(acc + 32, 4, nt, row0, lane);
    }
    wg_wait<0>();
    touch32(acc2);
    CK(5);
    k1_store<4>(acc2, 8, nt, row0, lane);
    CK(6);
}

constexpr int K2_THREADS = 512;
constexpr int K2_SMEM = 6 * 32768 + 12288;

constexpr float QS = 0.25f * 1.4426950408889634f;
constexpr float SC100 = 1.2676506002282294e30f;
__device__ __forceinline__ uint32_t polyexp2(float s0, float s1, float cd, uint32_t one2, uint32_t ca2) {
    constexpr float A = 128.0f * QS * 1.7763568394002505e-15f;
    float t0, t1;
    asm("fma.rn.f32 %0, %1, %2, %3;" : "=f"(t0) : "f"(s0), "f"(A), "f"(cd));
    asm("fma.rn.f32 %0, %1, %2, %3;" : "=f"(t1) : "f"(s1), "f"(A), "f"(cd));
    uint32_t W, U, h, G;
    asm("cvt.pack.sat.s16.s32 %0, %1, %2;" : "=r"(W) : "r"(__float_as_int(t1)), "r"(__float_as_int(t0)));
    asm("lop3.b32 %0, %1, 0x007F007F, %2, 0xEA;" : "=r"(U) : "r"(W), "r"(one2));
    asm("fma.rn.bf16x2 %0, %1, %2, %3;" : "=r"(h) : "r"(U), "r"(ca2), "r"(0xC300C300u));
    asm("fma.rn.bf16x2 %0, %1, %2, %3;" : "=r"(G) : "r"(h), "r"(U), "r"(0x438B438Bu));
    return W + G - 0x43404340u;
}

struct ExpC { float nm0, nm1, cd0, cd1; uint32_t one2, ca2; };

template <int G>
__device__ __forceinline__ void exp_block(const float* s, uint32_t* p, const ExpC& c) {
    #pragma unroll
    for (int hf = 0; hf < 2; hf++) {
        const float* x = s + hf * 4;
        if ((PMASK >> (G + hf)) & 1) {
            p[hf * 2 + 0] = polyexp2(x[0], x[1], c.cd0, c.one2, c.ca2);
            p[hf * 2 + 1] = polyexp2(x[2], x[3], c.cd1, c.one2, c.ca2);
        } else {
            p[hf * 2 + 0] = pack_bf16(ex2(fmaf(x[0], QS * SC100, c.nm0)), ex2(fmaf(x[1], QS * SC100, c.nm0)));
            p[hf * 2 + 1] = pack_bf16(ex2(fmaf(x[2], QS * SC100, c.nm1)), ex2(fmaf(x[3], QS * SC100, c.nm1)));
        }
    }
}

__device__ __forceinline__ void max16(const float* s, float& mx0, float& mx1) {
    #pragma unroll
    for (int j = 0; j < 4; j++) {
        mx0 = fmaxf(mx0, fmaxf(s[4 * j], s[4 * j + 1]));
        mx1 = fmaxf(mx1, fmaxf(s[4 * j + 2], s[4 * j + 3]));
    }
}

constexpr int MOE_SLOTS = 6, MOE_BOXES = 44;
__device__ __forceinline__ void moe_load(int b, int part, uint32_t ring, uint32_t bars, const CUtensorMap* mg, const CUtensorMap* mu, const CUtensorMap* md) {
    const int sl = b % MOE_SLOTS, grp = b & 1;
    if (b < 28) {
        const int j = b >> 1;
        mbar_expect_tx(bars + sl * 8, 32768);
        tma_2d(ring + sl * 32768, grp ? mu : mg, part * 448 + (j >> 1) * 64, (j & 1) * 256, bars + sl * 8);
    } else {
        const int j = (b - 28) >> 1;
        mbar_expect_tx(bars + sl * 8, 28672);
        tma_2d(ring + sl * 32768, md, ((j >> 1) * 2 + grp) * 64, part * 448 + (j & 1) * 224, bars + sl * 8);
    }
}
__device__ __forceinline__ void mma_2row(float* d, uint32_t a0, uint32_t a2, uint32_t b0, uint32_t b1) {
    asm("mma.sync.aligned.m16n8k16.row.col.f32.bf16.bf16.f32 {%0,%1,%2,%3}, {%4,%5,%6,%5}, {%7,%8}, {%0,%1,%2,%3};"
        : "+f"(d[0]), "+f"(d[1]), "+f"(d[2]), "+f"(d[3]) : "r"(a0), "r"(0u), "r"(a2), "r"(b0), "r"(b1));
}

__device__ void moe_cta(int part, unsigned char* smem, const __nv_bfloat16* __restrict__ x, const CUtensorMap* mg, const CUtensorMap* mu, const CUtensorMap* md) {
    const uint32_t ring = smem_u32(smem), bars = ring + MOE_SLOTS * 32768;
    __nv_bfloat16* xs = (__nv_bfloat16*)(smem + MOE_SLOTS * 32768 + 256);
    float* gu = (float*)(smem + MOE_SLOTS * 32768 + 256 + 2048);
    float* s_v = gu + 4 * 448;
    int* s_i = (int*)(s_v + 16);
    int* s_sel = s_i + 16;
    const int tid = threadIdx.x, warp = __shfl_sync(~0u, tid >> 5, 0), lane = tid & 31;
    if (tid == 0) {
        for (int i = 0; i < MOE_SLOTS; i++) { mbar_init(bars + i * 8, 1); mbar_init(bars + 128 + i * 8, 8); }
        asm volatile("fence.mbarrier_init.release.cluster;" ::: "memory");
        for (int b = 0; b < MOE_SLOTS; b++) moe_load(b, part, ring, bars, mg, mu, md);
    }
    pdl_wait();
    TL(1, 1);
    float rv[4];
    #pragma unroll
    for (int i = 0; i < 4; i++) rv[i] = g_r[tid + i * K2_THREADS];
    for (int pass = 0; pass < 2; pass++) {
        float bv = -INFINITY; int bi = 0x7fffffff;
        const int excl = pass ? s_sel[0] : -1;
        #pragma unroll
        for (int i = 0; i < 4; i++) {
            const int idx = tid + i * K2_THREADS;
            if (idx != excl && (rv[i] > bv || bi == 0x7fffffff)) { bv = rv[i]; bi = idx; }
        }
        #pragma unroll
        for (int o = 16; o; o >>= 1) {
            float ov = __shfl_xor_sync(~0u, bv, o); int oi = __shfl_xor_sync(~0u, bi, o);
            if (ov > bv || (ov == bv && oi < bi)) { bv = ov; bi = oi; }
        }
        if (lane == 0) { s_v[warp] = bv; s_i[warp] = bi; }
        __syncthreads();
        if (warp == 0) {
            bv = lane < 16 ? s_v[lane] : -INFINITY; bi = lane < 16 ? s_i[lane] : 0x7fffffff;
            #pragma unroll
            for (int o = 16; o; o >>= 1) {
                float ov = __shfl_xor_sync(~0u, bv, o); int oi = __shfl_xor_sync(~0u, bi, o);
                if (ov > bv || (ov == bv && oi < bi)) { bv = ov; bi = oi; }
            }
            if (lane == 0) s_sel[pass] = (bi == 0x7fffffff) ? pass : bi;
        }
        __syncthreads();
    }
    for (int i = tid; i < 1024; i += K2_THREADS) {
        const int tok = s_sel[i >> 9];
        const float2 st = g_stats[tok];
        xs[i] = __float2bfloat16_rn(ln_elem(__bfloat162float(x[(size_t)tok * D_ + (i & 511)]), st.x, st.y));
    }
    if (part == 0 && tid < 2) g_sel[tid] = s_sel[tid];
    __syncthreads();
    if (warp == 8) {
        if (lane == 0) {
            for (int b = MOE_SLOTS; b < MOE_BOXES; b++) {
                mbar_wait(bars + 128 + (b % MOE_SLOTS) * 8, (b / MOE_SLOTS - 1) & 1);
                moe_load(b, part, ring, bars, mg, mu, md);
            }
        }
        return;
    }
    if (warp > 8) return;
    const int nj = warp, g = lane >> 2, t = lane & 3;
    const uint32_t* xw = (const uint32_t*)xs + (g & 1) * 256 + t;
    uint32_t a[2][32];
    #pragma unroll
    for (int i = 0; i < 32; i++) { a[0][i] = xw[i * 4]; a[1][i] = xw[128 + i * 4]; }
    #pragma unroll 1
    for (int jp = 0; jp < MOE_BOXES / 4; jp++) {
        const bool down = jp >= 7;
        if (jp == 7) {
            named_bar(1, 256);
            for (int i = tid; i < 896; i += 256) {
                const float gs = bf16r(gu[i]), us = bf16r(gu[896 + i]);
                const float sl_ = bf16r(gs / (1.0f + __expf(-gs)));
                xs[(i / 448) * 512 + (i % 448)] = __float2bfloat16_rn(sl_ * us);
            }
            named_bar(1, 256);
            #pragma unroll
            for (int i = 0; i < 28; i++) { a[0][i] = xw[i * 4]; a[1][i] = xw[112 + i * 4]; }
        }
        float acc[2][4] = {{0.f, 0.f, 0.f, 0.f}, {0.f, 0.f, 0.f, 0.f}}, acb[2][4] = {{0.f, 0.f, 0.f, 0.f}, {0.f, 0.f, 0.f, 0.f}};
        #pragma unroll
        for (int q = 0; q < 4; q++) {
            const int hf = q >> 1, grp = q & 1;
            const int b = jp * 4 + q, sl = b % MOE_SLOTS;
            mbar_wait(bars + sl * 8, (b / MOE_SLOTS) & 1);
            const uint32_t baddr = ring + sl * 32768 + lane * 128 + ((nj ^ (lane & 7)) * 16);
            #pragma unroll
            for (int k4 = 0; k4 < 2; k4++) {
                uint32_t bf[4][4];
                #pragma unroll
                for (int k2 = 0; k2 < 4; k2++)
                    asm volatile("ldmatrix.sync.aligned.m8n8.x4.trans.shared.b16 {%0, %1, %2, %3}, [%4];"
                                 : "=r"(bf[k2][0]), "=r"(bf[k2][1]), "=r"(bf[k2][2]), "=r"(bf[k2][3]) : "r"(baddr + (k4 * 4 + k2) * 4096) : "memory");
                #pragma unroll
                for (int k2 = 0; k2 < 4; k2++) {
                    const int kk = k4 * 4 + k2;
                    if (kk < 7 || !down) {
                        mma_2row(acc[grp], a[hf][4 * kk], a[hf][4 * kk + 1], bf[k2][0], bf[k2][1]);
                        mma_2row(acb[grp], a[hf][4 * kk + 2], a[hf][4 * kk + 3], bf[k2][2], bf[k2][3]);
                    }
                }
            }
            __syncwarp();
            if (lane == 0) mbar_arrive(bars + 128 + sl * 8);
        }
        if (g < 2) {
            #pragma unroll
            for (int grp = 0; grp < 2; grp++) {
                const float2 v = make_float2(acc[grp][0] + acb[grp][0], acc[grp][1] + acb[grp][1]);
                if (!down) *(float2*)&gu[(grp * 2 + g) * 448 + jp * 64 + nj * 8 + t * 2] = v;
                else *(float2*)&g_ypart[part][g][((jp - 7) * 2 + grp) * 64 + nj * 8 + t * 2] = v;
            }
        }
    }
}

__global__ void __launch_bounds__(K2_THREADS, 1)
k2_attn(const __nv_bfloat16* __restrict__ x, const __nv_bfloat16* __restrict__ w_gate, const __nv_bfloat16* __restrict__ w_up,
        const __nv_bfloat16* __restrict__ w_down, const __grid_constant__ CUtensorMap mg, const __grid_constant__ CUtensorMap mu,
        const __grid_constant__ CUtensorMap md) {
    extern __shared__ __align__(1024) unsigned char smem[];
    TL(1, 0);
    pdl_launch();
    if (blockIdx.x >= 128) { moe_cta(blockIdx.x - 128, smem, x, &mg, &mu, &md); TL(1, 2); return; }
    if (threadIdx.x >= 32 && threadIdx.x < 35) {
        const __nv_bfloat16* w = threadIdx.x == 32 ? w_gate : (threadIdx.x == 33 ? w_up : w_down);
        asm volatile("cp.async.bulk.prefetch.L2.global [%0], %1;" :: "l"(w + (size_t)blockIdx.x * (D_ * F_ / 128)), "r"(D_ * F_ / 64) : "memory");
    }
    const uint32_t sK = smem_u32(smem), sV = sK + 65536, sQ = sV + 98304, sBar = sQ + 16384;
    const int h = blockIdx.x >> 2, qb = blockIdx.x & 3;
    const int warp = __shfl_sync(~0u, threadIdx.x >> 5, 0), lane = threadIdx.x & 31, wg = warp >> 2;
    if (threadIdx.x == 0) {
        mbar_init(sBar, 1); mbar_init(sBar + 8, 1);
        asm volatile("fence.mbarrier_init.release.cluster;" ::: "memory");
        mbar_expect_tx(sBar, 16384 + 16384 + 2 * 8192);
        mbar_expect_tx(sBar + 8, 49152 + 2 * 24576);
    }
    for (int i = threadIdx.x; i < 2048; i += K2_THREADS)
        *(uint4*)(smem + 65536 + 65536 + i * 16) = make_uint4(0x3F803F80u, 0x3F803F80u, 0x3F803F80u, 0x3F803F80u);
    fence_async_smem();
    __syncthreads();
    if (warp == 0) {
        pdl_wait();
        TL(1, 1);
        const uint4* gk = g_K + (size_t)h * 4096;
        const uint4* gv = g_V + (size_t)h * 4096;
        if (lane == 0) bulk_g2s(sQ, g_Q + (size_t)h * 4096 + qb * 1024, 16384, sBar);
        if (lane == 1) bulk_g2s(sK, gk, 16384, sBar);
        if (lane == 2) bulk_g2s(sV, gv, 8192, sBar);
        if (lane == 3) bulk_g2s(sV + 32768, gv + 2048, 8192, sBar);
        if (lane == 4) bulk_g2s(sK + 16384, gk + 1024, 49152, sBar + 8);
        if (lane == 5) bulk_g2s(sV + 8192, gv + 512, 24576, sBar + 8);
        if (lane == 6) bulk_g2s(sV + 32768 + 8192, gv + 2048 + 512, 24576, sBar + 8);
        __syncwarp();
    }
    ExpC c;
    {
        const volatile uint32_t* cc = g_const;
        c.one2 = cc[0]; c.ca2 = cc[1];
    }
    const uint32_t kdesc0 = (uint32_t)make_desc(sK, 128, 256, 0);
    const uint32_t vdesc0 = (uint32_t)make_desc(sV, 128, 32768, 0);
    #pragma unroll 1
    for (int pass = 0; pass < 2; pass++) {
        const bool dry = false;
        if (pass == 0) { mbar_wait(sBar, 0); __syncwarp(); TL(1, 2); }
        const int unit = (pass & 1) * 4 + wg;
        const uint32_t q = (uint32_t)make_desc(sQ + unit * 2048, 128, 256, 0);
        float o[12];
        #pragma unroll 1
        for (int attempt = 0; attempt < 2; attempt++) {
            float s0[16], s1[16], s2[16];
            #pragma unroll
            for (int i = 0; i < 16; i++) { s0[i] = 0.f; s1[i] = 0.f; s2[i] = 0.f; }
            float mx0 = -INFINITY, mx1 = -INFINITY;
            if (attempt) {
                #pragma unroll 1
                for (int it = 0; it < 64; it++) {
                    WG_FENCE();
                    wgmma_qk32(s0, q, kdesc0 + it * 64);
                    WG_COMMIT();
                    wg_wait<0>();
                    touch16(s0);
                    max16(s0, mx0, mx1);
                }
            }
            #pragma unroll
            for (int i = 0; i < 12; i++) o[i] = 0.f;
            WG_FENCE();
            wgmma_qk32(s2, q, kdesc0);
            wgmma_qk32(s0, q, kdesc0 + 64);
            wgmma_qk32(s1, q, kdesc0 + 128);
            WG_COMMIT();
            wg_wait<0>();
            touch16(s0); touch16(s1); touch16(s2);
            max16(s0, mx0, mx1); max16(s1, mx0, mx1); max16(s2, mx0, mx1);
            mx0 = fmaxf(mx0, __shfl_xor_sync(~0u, mx0, 1)); mx0 = fmaxf(mx0, __shfl_xor_sync(~0u, mx0, 2));
            mx1 = fmaxf(mx1, __shfl_xor_sync(~0u, mx1, 1)); mx1 = fmaxf(mx1, __shfl_xor_sync(~0u, mx1, 2));
            const float bias = attempt ? 0.0f : 128.0f * 64.0f;
            const float y0 = ceilf(fmaf(mx0, 128.0f * QS * SC100, bias)), y1 = ceilf(fmaf(mx1, 128.0f * QS * SC100, bias));
            c.nm0 = __shfl_sync(~0u, y0 * (-1.0f / 128.0f), lane); c.nm1 = __shfl_sync(~0u, y1 * (-1.0f / 128.0f), lane);
            c.cd0 = __shfl_sync(~0u, __fmul_rn(16256.0f - y0, __int_as_float(1)), lane);
            c.cd1 = __shfl_sync(~0u, __fmul_rn(16256.0f - y1, __int_as_float(1)), lane);
            uint32_t kd = kdesc0 + 192, vd = vdesc0 + 32;
            {
                uint32_t pa[4], pb[4];
                exp_block<12>(s2, pa, c);
                exp_block<14>(s2 + 8, pb, c);
                WG_FENCE();
                wgmma_pv(o, pa, vdesc0); wgmma_pv(o, pb, vdesc0 + 16);
                WG_COMMIT();
            }
            #pragma unroll 1
            for (int seg = 0; seg < (dry ? 1 : 2); seg++) {
            if (seg) { wg_wait<0>(); mbar_wait(sBar + 8, 0); __syncwarp(); }
            #pragma unroll 1
            for (int it = seg ? 3 : (dry ? 2 : 0); it < (seg ? 21 : 3); it++) {
                uint32_t p[6][4];
                WG_FENCE();
                wgmma_qk32(s2, q, kd);
                WG_COMMIT();
                exp_block<0>(s0, p[0], c);
                exp_block<2>(s0 + 8, p[1], c);
                WG_FENCE();
                wgmma_pv(o, p[0], vd); wgmma_pv(o, p[1], vd + 16);
                wgmma_qk32(s0, q, kd + 64);
                WG_COMMIT();
                wg_wait<1>();
                touch16(s2);
                exp_block<4>(s1, p[2], c);
                exp_block<6>(s1 + 8, p[3], c);
                WG_FENCE();
                wgmma_pv(o, p[2], vd + 32); wgmma_pv(o, p[3], vd + 48);
                wgmma_qk32(s1, q, kd + 128);
                WG_COMMIT();
                wg_wait<1>();
                touch16(s0);
                exp_block<8>(s2, p[4], c);
                exp_block<10>(s2 + 8, p[5], c);
                WG_FENCE();
                wgmma_pv(o, p[4], vd + 64); wgmma_pv(o, p[5], vd + 80);
                WG_COMMIT();
                vd += 96; kd += 192;
                wg_wait<1>();
                touch16(s1);
            }
            }
            wg_wait<0>();
            touch12(o);
            if (attempt) break;
            float big = 0.f;
            #pragma unroll
            for (int i = 0; i < 12; i++) big = fmaxf(big, fabsf(o[i]));
            bool bad = !(big < 1e30f);
            #pragma unroll
            for (int i = 0; i < 12; i++) bad |= (o[i] != o[i]);
            uint32_t any;
            asm volatile("{.reg .pred p, q; setp.ne.u32 p, %1, 0; barrier.cta.red.or.pred.aligned q, %2, 128, p; selp.u32 %0, 1, 0, q;}"
                         : "=r"(any) : "r"((uint32_t)bad), "r"(1 + wg) : "memory");
            if (dry || !__any_sync(~0u, any)) break;
        }
        const int g = lane >> 2, t = lane & 3;
        const int r = (warp & 3) * 16 + g;
        const float i0 = __fdiv_rn(1.0f, o[8]), i1 = __fdiv_rn(1.0f, o[10]);
        uint32_t* ob = (uint32_t*)(g_O + (size_t)(qb * 8 + unit) * 4096 + (h >> 2) * 512 + r * 8) + t;
        const int c0 = ((h & 3) * 2) ^ (r & 7), c1 = ((h & 3) * 2 + 1) ^ (r & 7);
        if (!dry) {
            ob[c0 * 4] = pack_bf16(o[0] * i0, o[1] * i0);
            ob[c1 * 4] = pack_bf16(o[4] * i0, o[5] * i0);
            ob[256 + c0 * 4] = pack_bf16(o[2] * i1, o[3] * i1);
            ob[256 + c1 * 4] = pack_bf16(o[6] * i1, o[7] * i1);
            TL(1, 3 + pass);
        }
    }
}

constexpr int K3_THREADS = 256;
constexpr int K3_SMEM = 65536 + 131072 + 128;

__global__ void __launch_bounds__(K3_THREADS, 1)
k3_out(const __grid_constant__ CUtensorMap wmap, const __nv_bfloat16* __restrict__ x, __nv_bfloat16* __restrict__ out) {
    extern __shared__ __align__(1024) unsigned char smem[];
    const uint32_t sA = smem_u32(smem), sB = sA + 65536, sBar = sB + 131072;
    const int warp = __shfl_sync(~0u, threadIdx.x >> 5, 0), lane = threadIdx.x & 31, wg = warp >> 2;
    const int nt = blockIdx.x & 3, mt = blockIdx.x >> 2;
    TL(2, 0);
    if (threadIdx.x == 0) {
        for (int i = 0; i < 6; i++) mbar_init(sBar + i * 8, 1);
        asm volatile("fence.mbarrier_init.release.cluster;" ::: "memory");
        for (int kh = 0; kh < 2; kh++) {
            mbar_expect_tx(sBar + kh * 8, 65536);
            tma_2d(sB + kh * 32768, &wmap, nt * 128, kh * 256, sBar + kh * 8);
            tma_2d(sB + 65536 + kh * 32768, &wmap, nt * 128 + 64, kh * 256, sBar + kh * 8);
        }
    }
    const int er = threadIdx.x >> 2, ec = (threadIdx.x & 3) * 32;
    const int row = mt * 64 + er;
    uint4 xv[4];
    #pragma unroll
    for (int j = 0; j < 4; j++) xv[j] = __ldg((const uint4*)(x + (size_t)row * D_ + nt * 128 + ec) + j);
    pdl_wait();
    TL(2, 1);
    if (threadIdx.x == 0) {
        for (int q = 0; q < 4; q++) {
            mbar_expect_tx(sBar + 16 + q * 8, 16384);
            bulk_g2s(sA + q * 16384, g_O + (size_t)mt * 4096 + q * 1024, 16384, sBar + 16 + q * 8);
        }
    }
    const int sel0 = g_sel[0], sel1 = g_sel[1];
    const float2 st = g_stats[row];
    uint32_t bb[16];
    {
        const uint32_t xu[16] = {xv[0].x, xv[0].y, xv[0].z, xv[0].w, xv[1].x, xv[1].y, xv[1].z, xv[1].w,
                                 xv[2].x, xv[2].y, xv[2].z, xv[2].w, xv[3].x, xv[3].y, xv[3].z, xv[3].w};
        #pragma unroll
        for (int j = 0; j < 16; j++) bb[j] = pack_bf16(bf16r(bf_lo(xu[j]) - st.x) * st.y, bf16r(bf_hi(xu[j]) - st.x) * st.y);
        const int slot = row == sel0 ? 0 : (row == sel1 ? 1 : -1);
        if (slot >= 0) {
            const float gate = bf16r(1.0f / (1.0f + __expf(-g_r[row])));
            const int c0 = nt * 128 + ec;
            #pragma unroll
            for (int j = 0; j < 16; j++) {
                const float2 a = *(const float2*)&g_ypart[0][slot][c0 + 2 * j], b = *(const float2*)&g_ypart[1][slot][c0 + 2 * j];
                const float2 c = *(const float2*)&g_ypart[2][slot][c0 + 2 * j], d = *(const float2*)&g_ypart[3][slot][c0 + 2 * j];
                bb[j] = pack_bf16(bf_lo(bb[j]) + bf16r(bf16r(a.x + b.x + c.x + d.x) * gate), bf_hi(bb[j]) + bf16r(bf16r(a.y + b.y + c.y + d.y) * gate));
            }
        }
    }
    __syncthreads();
    float acc[32];
    #pragma unroll
    for (int i = 0; i < 32; i++) acc[i] = 0.f;
    const uint64_t da0 = make_desc(sA, 16, 1024, 1);
    const uint64_t db0 = make_desc(sB + wg * 65536, 8192, 1024, 1);
    #pragma unroll 1
    for (int q = 0; q < 4; q++) {
        if ((q & 1) == 0) mbar_wait(sBar + (q >> 1) * 8, 0);
        mbar_wait(sBar + 16 + q * 8, 0);
        WG_FENCE();
        #pragma unroll
        for (int kk = 0; kk < 8; kk++)
            wgmma_n64(acc, da0 + (uint64_t)(q * 1024 + (kk >> 2) * 512 + (kk & 3) * 2), db0 + (uint64_t)(q * 1024 + kk * 128));
        WG_COMMIT();
    }
    wg_wait<0>();
    touch32(acc);
    TL(2, 2);
    __syncthreads();
    {
        const int g = lane >> 2, t = lane & 3;
        unsigned char* sp = smem + ((warp & 3) * 16 + g) * 272 + wg * 128 + t * 4;
        #pragma unroll
        for (int j = 0; j < 8; j++) {
            *(uint32_t*)(sp + j * 16) = pack_bf16(acc[4 * j], acc[4 * j + 1]);
            *(uint32_t*)(sp + 8 * 272 + j * 16) = pack_bf16(acc[4 * j + 2], acc[4 * j + 3]);
        }
    }
    __syncthreads();
    #pragma unroll
    for (int j = 0; j < 4; j++) {
        const uint4 av = *(const uint4*)(smem + er * 272 + ec * 2 + j * 16);
        const uint32_t au[4] = {av.x, av.y, av.z, av.w}, xu[4] = {xv[j].x, xv[j].y, xv[j].z, xv[j].w};
        uint32_t o[4];
        #pragma unroll
        for (int i = 0; i < 4; i++) {
            uint32_t t2;
            asm("add.rn.bf16x2 %0, %1, %2;" : "=r"(t2) : "r"(xu[i]), "r"(au[i]));
            asm("add.rn.bf16x2 %0, %1, %2;" : "=r"(o[i]) : "r"(t2), "r"(bb[j * 4 + i]));
        }
        *((uint4*)(out + (size_t)row * D_ + nt * 128 + ec) + j) = make_uint4(o[0], o[1], o[2], o[3]);
    }
    TL(2, 3);
}

typedef CUresult (*EncodeFn)(CUtensorMap*, CUtensorMapDataType, cuuint32_t, void*, const cuuint64_t*, const cuuint64_t*,
                             const cuuint32_t*, const cuuint32_t*, CUtensorMapInterleave, CUtensorMapSwizzle,
                             CUtensorMapL2promotion, CUtensorMapFloatOOBfill);

void make_wmap(EncodeFn fn, CUtensorMap* map, const void* ptr, int rows, int cols, int box_rows) {
    cuuint64_t dims[2] = {(cuuint64_t)cols, (cuuint64_t)rows};
    cuuint64_t strides[1] = {(cuuint64_t)cols * 2};
    cuuint32_t box[2] = {64, (cuuint32_t)box_rows};
    cuuint32_t es[2] = {1, 1};
    fn(map, CU_TENSOR_MAP_DATA_TYPE_BFLOAT16, 2, (void*)ptr, dims, strides, box, es, CU_TENSOR_MAP_INTERLEAVE_NONE,
       CU_TENSOR_MAP_SWIZZLE_128B, CU_TENSOR_MAP_L2_PROMOTION_L2_256B, CU_TENSOR_MAP_FLOAT_OOB_FILL_NONE);
}

}

extern "C" void kernel_launch(void* const* d_in, const int* in_sizes, int n_in, void* d_out, int out_size) {
    const __nv_bfloat16* x = (const __nv_bfloat16*)d_in[0];
    const __nv_bfloat16* wqkv = (const __nv_bfloat16*)d_in[1];
    const __nv_bfloat16* wo = (const __nv_bfloat16*)d_in[2];
    const __nv_bfloat16* w_r = (const __nv_bfloat16*)d_in[4];
    const __nv_bfloat16* w_gate = (const __nv_bfloat16*)d_in[5];
    const __nv_bfloat16* w_up = (const __nv_bfloat16*)d_in[6];
    const __nv_bfloat16* w_down = (const __nv_bfloat16*)d_in[7];
    __nv_bfloat16* out = (__nv_bfloat16*)d_out;

    static EncodeFn encode = nullptr;
    if (!encode) {
        void* fn = nullptr;
        cudaDriverEntryPointQueryResult qres;
        cudaGetDriverEntryPoint("cuTensorMapEncodeTiled", &fn, cudaEnableDefault, &qres);
        encode = (EncodeFn)fn;
        cudaFuncSetAttribute(k1_ln_qkv, cudaFuncAttributeMaxDynamicSharedMemorySize, K1_SMEM);
        cudaFuncSetAttribute(k2_attn, cudaFuncAttributeMaxDynamicSharedMemorySize, K2_SMEM);
        cudaFuncSetAttribute(k3_out, cudaFuncAttributeMaxDynamicSharedMemorySize, K3_SMEM);
    }
    CUtensorMap map_qkv, map_wo, map_x, map_g, map_u, map_d;
    make_wmap(encode, &map_g, w_gate, D_, F_, 256);
    make_wmap(encode, &map_u, w_up, D_, F_, 256);
    make_wmap(encode, &map_d, w_down, F_, D_, 224);
    make_wmap(encode, &map_x, x, S_, D_, 64);
    make_wmap(encode, &map_qkv, wqkv, D_, 3 * D_, 64);
    make_wmap(encode, &map_wo, wo, D_, D_, 256);

    k1_ln_qkv<<<128, K1_THREADS, K1_SMEM, cudaStreamPerThread>>>(map_qkv, map_x, w_r);
    cudaLaunchAttribute at[1];
    at[0].id = cudaLaunchAttributeProgrammaticStreamSerialization;
    at[0].val.programmaticStreamSerializationAllowed = 1;
    cudaLaunchConfig_t cfg = {};
    cfg.stream = cudaStreamPerThread;
    cfg.attrs = at; cfg.numAttrs = 1;
    cfg.gridDim = dim3(132); cfg.blockDim = dim3(K2_THREADS); cfg.dynamicSmemBytes = K2_SMEM;
    cudaLaunchKernelEx(&cfg, k2_attn, x, w_gate, w_up, w_down, map_g, map_u, map_d);
    cfg.gridDim = dim3(128); cfg.blockDim = dim3(K3_THREADS); cfg.dynamicSmemBytes = K3_SMEM;
    cudaLaunchKernelEx(&cfg, k3_out, map_wo, x, out);
}
```

```cpp
#include <cuda_runtime.h>
#include <cuda_bf16.h>
#include <cuda.h>
#include <stdint.h>

namespace {

constexpr int S_ = 2048, D_ = 512, H_ = 32, F_ = 1792;

constexpr uint32_t PMASK = 0xDB6;

__device__ __align__(1024) uint4 g_QKV[3 * H_ * S_ * 2];
#define g_Q (g_QKV)
#define g_K (g_QKV + H_ * S_ * 2)
#define g_V (g_QKV + 2 * H_ * S_ * 2)
__device__ __align__(1024) uint4 g_O[S_ * D_ / 8];
__device__ float2 g_stats[S_];
__device__ uint32_t g_const[2] = {0x3F803F80u, 0x42294229u};
__device__ float g_r[S_];
__device__ __align__(16) float g_ypart[4][2][D_];
__device__ int g_sel[2];

#define TL(k, p)
#define CK(i)
__device__ __forceinline__ uint32_t smem_u32(const void* p) { return (uint32_t)__cvta_generic_to_shared(p); }
__device__ __forceinline__ float bf16r(float x) { return __bfloat162float(__float2bfloat16_rn(x)); }
__device__ __forceinline__ uint32_t pack_bf16(float lo, float hi) {
    uint32_t r; asm("cvt.rn.bf16x2.f32 %0, %1, %2;" : "=r"(r) : "f"(hi), "f"(lo)); return r;
}
__device__ __forceinline__ float bf_lo(uint32_t u) { return __uint_as_float(u << 16); }
__device__ __forceinline__ float bf_hi(uint32_t u) { return __uint_as_float(u & 0xFFFF0000u); }
__device__ __forceinline__ float ex2(float x) { float y; asm("ex2.approx.ftz.f32 %0, %1;" : "=f"(y) : "f"(x)); return y; }

__device__ __forceinline__ void mbar_init(uint32_t bar, uint32_t count) {
    asm volatile("mbarrier.init.shared::cta.b64 [%0], %1;" :: "r"(bar), "r"(count) : "memory");
}
__device__ __forceinline__ void mbar_expect_tx(uint32_t bar, uint32_t bytes) {
    asm volatile("mbarrier.arrive.expect_tx.shared::cta.b64 _, [%0], %1;" :: "r"(bar), "r"(bytes) : "memory");
}
__device__ __forceinline__ void mbar_arrive(uint32_t bar) {
    asm volatile("mbarrier.arrive.shared::cta.b64 _, [%0];" :: "r"(bar) : "memory");
}
__device__ __forceinline__ void mbar_wait(uint32_t bar, uint32_t parity) {
    uint32_t done;
    #pragma unroll 1
    for (int it = 0; it < (1 << 26); it++) {
        asm volatile("{.reg .pred p; mbarrier.try_wait.parity.shared::cta.b64 p, [%1], %2; selp.u32 %0, 1, 0, p;}"
                     : "=r"(done) : "r"(bar), "r"(parity) : "memory");
        if (done) return;
    }
    __trap();
}
__device__ __forceinline__ void bulk_g2s(uint32_t dst, const void* src, uint32_t bytes, uint32_t bar) {
    asm volatile("cp.async.bulk.shared::cluster.global.mbarrier::complete_tx::bytes [%0], [%1], %2, [%3];"
                 :: "r"(dst), "l"(src), "r"(bytes), "r"(bar) : "memory");
}
__device__ __forceinline__ void tma_2d(uint32_t dst, const CUtensorMap* map, int c0, int c1, uint32_t bar) {
    asm volatile("cp.async.bulk.tensor.2d.shared::cluster.global.mbarrier::complete_tx::bytes [%0], [%1, {%3, %4}], [%2];"
                 :: "r"(dst), "l"(map), "r"(bar), "r"(c0), "r"(c1) : "memory");
}
__device__ __forceinline__ void fence_async_smem() { asm volatile("fence.proxy.async.shared::cta;" ::: "memory"); }
__device__ __forceinline__ void named_bar(int id, int n) { asm volatile("bar.sync %0, %1;" :: "r"(id), "r"(n) : "memory"); }

__device__ __forceinline__ uint64_t make_desc(uint32_t saddr, uint32_t lbo, uint32_t sbo, uint32_t swz) {
    return (uint64_t)((saddr & 0x3FFFF) >> 4) | ((uint64_t)(lbo >> 4) << 16) | ((uint64_t)(sbo >> 4) << 32) | ((uint64_t)swz << 62);
}
#define WG_FENCE() asm volatile("wgmma.fence.sync.aligned;" ::: "memory")
#define WG_COMMIT() asm volatile("wgmma.commit_group.sync.aligned;" ::: "memory")
template <int N> __device__ __forceinline__ void wg_wait() { asm volatile("wgmma.wait_group.sync.aligned %0;" :: "n"(N) : "memory"); }

#define F4(d, o) "+f"(d[o]), "+f"(d[o + 1]), "+f"(d[o + 2]), "+f"(d[o + 3])
#define F16(d, o) F4(d, o), F4(d, o + 4), F4(d, o + 8), F4(d, o + 12)
#define F32(d, o) F16(d, o), F16(d, o + 16)

__device__ __forceinline__ void wgmma_rs_n128(float* d, const uint32_t* a, uint64_t db) {
    asm volatile("wgmma.mma_async.sync.aligned.m64n128k16.f32.bf16.bf16 "
        "{%0,%1,%2,%3,%4,%5,%6,%7,%8,%9,%10,%11,%12,%13,%14,%15,%16,%17,%18,%19,%20,%21,%22,%23,%24,%25,%26,%27,%28,%29,%30,%31,"
        "%32,%33,%34,%35,%36,%37,%38,%39,%40,%41,%42,%43,%44,%45,%46,%47,%48,%49,%50,%51,%52,%53,%54,%55,%56,%57,%58,%59,%60,%61,%62,%63}, "
        "{%64,%65,%66,%67}, %68, 1, 1, 1, 1;\n"
        : F32(d, 0), F32(d, 32) : "r"(a[0]), "r"(a[1]), "r"(a[2]), "r"(a[3]), "l"(db));
}
__device__ __forceinline__ void wgmma_rs_n64(float* d, const uint32_t* a, uint64_t db) {
    asm volatile("wgmma.mma_async.sync.aligned.m64n64k16.f32.bf16.bf16 "
        "{%0,%1,%2,%3,%4,%5,%6,%7,%8,%9,%10,%11,%12,%13,%14,%15,%16,%17,%18,%19,%20,%21,%22,%23,%24,%25,%26,%27,%28,%29,%30,%31}, "
        "{%32,%33,%34,%35}, %36, 1, 1, 1, 1;\n"
        : F32(d, 0) : "r"(a[0]), "r"(a[1]), "r"(a[2]), "r"(a[3]), "l"(db));
}
__device__ __forceinline__ void wgmma_n64(float* d, uint64_t da, uint64_t db) {
    asm volatile("wgmma.mma_async.sync.aligned.m64n64k16.f32.bf16.bf16 "
        "{%0,%1,%2,%3,%4,%5,%6,%7,%8,%9,%10,%11,%12,%13,%14,%15,%16,%17,%18,%19,%20,%21,%22,%23,%24,%25,%26,%27,%28,%29,%30,%31}, "
        "%32, %33, 1, 1, 1, 0, 1;\n"
        : F32(d, 0) : "l"(da), "l"(db));
}
__device__ __forceinline__ void wgmma_qk32(float* d, uint64_t qd, uint64_t kd) {
    asm volatile("wgmma.mma_async.sync.aligned.m64n32k16.f32.bf16.bf16 {%0,%1,%2,%3,%4,%5,%6,%7,%8,%9,%10,%11,%12,%13,%14,%15}, %16, %17, 0, 1, 1, 0, 0;\n"
        : F16(d, 0) : "l"(qd), "l"(kd));
}
__device__ __forceinline__ void wgmma_pv(float* d, const uint32_t* a, uint64_t vd) {
    asm volatile("wgmma.mma_async.sync.aligned.m64n24k16.f32.bf16.bf16 {%0,%1,%2,%3,%4,%5,%6,%7,%8,%9,%10,%11}, {%12,%13,%14,%15}, %16, 1, 1, 1, 1;\n"
        : F4(d, 0), F4(d, 4), F4(d, 8) : "r"(a[0]), "r"(a[1]), "r"(a[2]), "r"(a[3]), "l"(vd));
}
__device__ __forceinline__ void touch16(float* d) { asm volatile("" : F16(d, 0) :: "memory"); }
__device__ __forceinline__ void touch12(float* d) { asm volatile("" : F4(d, 0), F4(d, 4), F4(d, 8) :: "memory"); }
__device__ __forceinline__ void touch32(float* d) { asm volatile("" : F32(d, 0) :: "memory"); }
__device__ __forceinline__ void touch64(float* d) { asm volatile("" : F32(d, 0), F32(d, 32) :: "memory"); }

__device__ __forceinline__ float ln_elem(float x, float mean_b, float rden) {
    return bf16r(bf16r(x - mean_b) * rden);
}
__device__ __forceinline__ void pdl_wait() { asm volatile("griddepcontrol.wait;" ::: "memory"); }
__device__ __forceinline__ void pdl_launch() { asm volatile("griddepcontrol.launch_dependents;" ::: "memory"); }
__device__ __forceinline__ void cluster_arrive() { asm volatile("barrier.cluster.arrive.release.aligned;" ::: "memory"); }
__device__ __forceinline__ void cluster_wait() { asm volatile("barrier.cluster.wait.acquire.aligned;" ::: "memory"); }

constexpr int K1_THREADS = 288;
constexpr int K1_SMEM = 131072 + 6 * 16384 + 256 + 1024;

__device__ __forceinline__ void ldsm4(uint32_t* r, uint32_t addr) {
    asm volatile("ldmatrix.sync.aligned.m8n8.x4.shared.b16 {%0, %1, %2, %3}, [%4];" : "=r"(r[0]), "=r"(r[1]), "=r"(r[2]), "=r"(r[3]) : "r"(addr) : "memory");
}
__device__ __forceinline__ void stsm4(uint32_t addr, uint32_t r0, uint32_t r1, uint32_t r2, uint32_t r3) {
    asm volatile("stmatrix.sync.aligned.m8n8.x4.shared.b16 [%0], {%1, %2, %3, %4};" :: "r"(addr), "r"(r0), "r"(r1), "r"(r2), "r"(r3) : "memory");
}
__device__ __forceinline__ void mma16816(float* d, const uint32_t* a, uint32_t b0, uint32_t b1) {
    asm("mma.sync.aligned.m16n8k16.row.col.f32.bf16.bf16.f32 {%0,%1,%2,%3}, {%4,%5,%6,%7}, {%8,%9}, {%0,%1,%2,%3};"
        : "+f"(d[0]), "+f"(d[1]), "+f"(d[2]), "+f"(d[3]) : "r"(a[0]), "r"(a[1]), "r"(a[2]), "r"(a[3]), "r"(b0), "r"(b1));
}
__device__ __forceinline__ uint32_t sub_bf16x2(uint32_t a, uint32_t b) {
    uint32_t d; asm("sub.rn.bf16x2 %0, %1, %2;" : "=r"(d) : "r"(a), "r"(b)); return d;
}
__device__ __forceinline__ uint32_t ln_pair(uint32_t x2, uint32_t mean2, uint32_t rhi2, uint32_t rlo2) {
    const uint32_t d = sub_bf16x2(x2, mean2);
    uint32_t t, y;
    asm("mul.rn.bf16x2 %0, %1, %2;" : "=r"(t) : "r"(d), "r"(rlo2));
    asm("fma.rn.bf16x2 %0, %1, %2, %3;" : "=r"(y) : "r"(d), "r"(rhi2), "r"(t));
    return y;
}
struct LnRow { uint32_t m2, hi2, lo2; };
__device__ __forceinline__ LnRow ln_row(float mean, float rden) {
    LnRow r;
    r.m2 = pack_bf16(mean, mean);
    r.hi2 = pack_bf16(rden, rden);
    const float lo = rden - bf_lo(r.hi2);
    r.lo2 = pack_bf16(lo, lo);
    return r;
}
__device__ __forceinline__ void ln_frag(uint32_t* a, const LnRow& r0, const LnRow& r1) {
    a[0] = ln_pair(a[0], r0.m2, r0.hi2, r0.lo2); a[1] = ln_pair(a[1], r1.m2, r1.hi2, r1.lo2);
    a[2] = ln_pair(a[2], r0.m2, r0.hi2, r0.lo2); a[3] = ln_pair(a[3], r1.m2, r1.hi2, r1.lo2);
}

template <int NJ>
__device__ __forceinline__ void k1_store(const float* acc, int jj0, uint32_t stage, int nt, int mt, int wg, int w4, int lane) {
    const int mi = lane >> 3, lr = lane & 7;
    const uint32_t off_qk = stage + (w4 * 2 + (mi & 1)) * 256 + (mi >> 1) * 128 + lr * 16;
    const uint32_t off_v = stage + (mi >> 1) * 1024 + (w4 * 16 + (mi & 1) * 8 + lr) * 16;
    #pragma unroll
    for (int jj = 0; jj < NJ; jj++) {
        const bool isv = nt * 12 + jj0 + jj >= 64;
        const float m = isv ? 1.0f : 8.8817841970012523e-16f;
        stsm4((isv ? off_v : off_qk) + jj * 2048,
              pack_bf16(acc[8 * jj] * m, acc[8 * jj + 1] * m), pack_bf16(acc[8 * jj + 2] * m, acc[8 * jj + 3] * m),
              pack_bf16(acc[8 * jj + 4] * m, acc[8 * jj + 5] * m), pack_bf16(acc[8 * jj + 6] * m, acc[8 * jj + 7] * m));
    }
    fence_async_smem();
    named_bar(1 + wg, 128);
    if (lane < NJ / 2) {
        const int pc = w4 * (NJ / 2) + lane, jj = pc >> 1, hf = pc & 1, hg = nt * 12 + jj0 + jj;
        const unsigned char* dst = (const unsigned char*)g_QKV + (size_t)hg * 65536
            + (hg >= 64 ? hf * 32768 + (mt * 128 + wg * 64) * 16 : (mt * 16 + wg * 8) * 256 + hf * 1024);
        asm volatile("cp.async.bulk.global.shared::cta.bulk_group [%0], [%1], 1024;" :: "l"(dst), "r"(stage + pc * 1024) : "memory");
        asm volatile("cp.async.bulk.commit_group;" ::: "memory");
    }
}

__global__ void __launch_bounds__(K1_THREADS, 1)
k1_ln_qkv(const __grid_constant__ CUtensorMap wmap, const __grid_constant__ CUtensorMap xmap, const __nv_bfloat16* __restrict__ w_r) {
    extern __shared__ __align__(1024) unsigned char smem[];
    const uint32_t sA = smem_u32(smem), sB = sA + 131072, sBar = sB + 6 * 16384;
    const int warp = __shfl_sync(~0u, threadIdx.x >> 5, 0), lane = threadIdx.x & 31;
    const int nt = blockIdx.x & 7, mt = blockIdx.x >> 3;
    const int wg = warp >> 2;
    CK(0);
    pdl_launch();
    uint32_t* s_wr = (uint32_t*)(smem + 131072 + 6 * 16384 + 256);
    if (warp == 8) {
        if (lane == 0) {
            for (int i = 0; i < 6; i++) { mbar_init(sBar + i * 8, 1); mbar_init(sBar + 48 + i * 8, 2); }
            asm volatile("fence.mbarrier_init.release.cluster;" ::: "memory");
            for (int i = 0; i < 6; i++) mbar_expect_tx(sBar + i * 8, 16384);
        }
        if (lane < 16) {
            mbar_init(sBar + 96 + lane * 8, 1);
            asm volatile("fence.mbarrier_init.release.cluster;" ::: "memory");
            mbar_expect_tx(sBar + 96 + lane * 8, 8192);
        }
        __syncwarp();
        if (lane < 16) tma_2d(sA + (lane >> 1) * 16384 + (lane & 1) * 8192, &xmap, (lane >> 1) * 64, mt * 128 + (lane & 1) * 64, sBar + 96 + lane * 8);
        named_bar(3, K1_THREADS);
        mbar_wait(sBar + 96 + 8 * 8, 0);
        if (lane < 12) {
            const int ld = lane >> 1, j = lane & 1;
            tma_2d(sB + ld * 16384 + j * 8192, &wmap, nt * 192 + j * 64, ld * 64, sBar + ld * 8);
        }
        __syncwarp();
        if (lane < 2) {
            for (int ld = 6; ld < 12; ld++) {
                const int sl = ld - 6;
                mbar_wait(sBar + 48 + sl * 8, 0);
                if (lane == 0) mbar_expect_tx(sBar + sl * 8, 16384);
                __syncwarp(3);
                if (ld < 8) tma_2d(sB + sl * 16384 + lane * 8192, &wmap, nt * 192 + lane * 64, ld * 64, sBar + sl * 8);
                else tma_2d(sB + sl * 16384 + lane * 8192, &wmap, nt * 192 + 128, (ld - 8) * 128 + lane * 64, sBar + sl * 8);
            }
        }
        return;
    }
    if (nt == 0) s_wr[threadIdx.x] = __ldg((const uint32_t*)w_r + threadIdx.x);
    named_bar(3, K1_THREADS);
    const int g = lane >> 2, t = lane & 3;
    const int lrow = warp * 16 + (lane & 7) + ((lane >> 3) & 1) * 8;
    const uint32_t lbase = sA + lrow * 128;
    const int lsw = lane & 7, lhi = lane >> 4;
    uint32_t laddr[4];
    #pragma unroll
    for (int k4 = 0; k4 < 4; k4++) laddr[k4] = lbase + (((k4 * 2 + lhi) ^ lsw) * 16);
    CK(1);
    float dsum[4] = {0.f, 0.f, 0.f, 0.f}, dq0[4] = {0.f, 0.f, 0.f, 0.f}, dq1[4] = {0.f, 0.f, 0.f, 0.f};
    float esum[4] = {0.f, 0.f, 0.f, 0.f}, eq0[4] = {0.f, 0.f, 0.f, 0.f}, eq1[4] = {0.f, 0.f, 0.f, 0.f};
    #pragma unroll 1
    for (int pn = 0; pn < 8; pn++) {
        uint32_t a[4][4];
        mbar_wait(sBar + 96 + (pn * 2 + wg) * 8, 0);
        #pragma unroll
        for (int k4 = 0; k4 < 4; k4++) ldsm4(a[k4], laddr[k4] + pn * 16384);
        #pragma unroll
        for (int k4 = 0; k4 < 4; k4 += 2) {
            mma16816(dsum, a[k4], 0x3F803F80u, 0x3F803F80u);
            mma16816(dq0, a[k4], a[k4][0], a[k4][2]);
            mma16816(dq1, a[k4], a[k4][1], a[k4][3]);
            mma16816(esum, a[k4 + 1], 0x3F803F80u, 0x3F803F80u);
            mma16816(eq0, a[k4 + 1], a[k4 + 1][0], a[k4 + 1][2]);
            mma16816(eq1, a[k4 + 1], a[k4 + 1][1], a[k4 + 1][3]);
        }
    }
    #pragma unroll
    for (int i = 0; i < 4; i++) { dsum[i] += esum[i]; dq0[i] += eq0[i]; dq1[i] += eq1[i]; }
    CK(3);
    const int dsrc = g * 4 + (g >> 1);
    const float sq0 = __shfl_sync(~0u, (g & 1) ? dq0[1] : dq0[0], dsrc), sq1 = __shfl_sync(~0u, (g & 1) ? dq1[3] : dq1[2], dsrc);
    const float mean0 = dsum[0] * (1.0f / D_), mean1 = dsum[2] * (1.0f / D_);
    float var0 = fmaf(-mean0, mean0, sq0 * (1.0f / D_)), var1 = fmaf(-mean1, mean1, sq1 * (1.0f / D_));
    if (__any_sync(~0u, !(mean0 * mean0 <= 16.0f * var0) || !(mean1 * mean1 <= 16.0f * var1))) {
        float q0 = 0.f, q1 = 0.f;
        #pragma unroll 1
        for (int ks = 0; ks < 32; ks++) {
            uint32_t a[4];
            ldsm4(a, lbase + (ks >> 2) * 16384 + ((((ks & 3) * 2 + lhi) ^ lsw) * 16));
            #pragma unroll
            for (int i = 0; i < 4; i++) {
                const float m = (i & 1) ? mean1 : mean0;
                const float d0 = bf_lo(a[i]) - m, d1 = bf_hi(a[i]) - m;
                if (i & 1) q1 = fmaf(d0, d0, fmaf(d1, d1, q1)); else q0 = fmaf(d0, d0, fmaf(d1, d1, q0));
            }
        }
        q0 += __shfl_xor_sync(~0u, q0, 1); q0 += __shfl_xor_sync(~0u, q0, 2);
        q1 += __shfl_xor_sync(~0u, q1, 1); q1 += __shfl_xor_sync(~0u, q1, 2);
        var0 = q0 * (1.0f / D_); var1 = q1 * (1.0f / D_);
    }
    const float rs0 = __frcp_rn(bf16r(__fsqrt_rn(bf16r(bf16r(var0) + 1e-5f))));
    const float rs1 = __frcp_rn(bf16r(__fsqrt_rn(bf16r(bf16r(var1) + 1e-5f))));
    const LnRow lr0 = ln_row(mean0, rs0), lr1 = ln_row(mean1, rs1);
    float acc[64];
    #pragma unroll
    for (int i = 0; i < 64; i++) acc[i] = 0.f;
    float dr[4] = {0.f, 0.f, 0.f, 0.f};
    const uint64_t db0 = make_desc(sB, 8192, 1024, 1);
    #pragma unroll 1
    for (int kc = 0; kc < 8; kc += 2) {
        #pragma unroll
        for (int h2 = 0; h2 < 2; h2++) {
            const int ld = kc + h2, sl = ld < 6 ? ld : ld - 6;
            uint32_t a[4][4];
            #pragma unroll
            for (int k4 = 0; k4 < 4; k4++) ldsm4(a[k4], laddr[k4] + ld * 16384);
            #pragma unroll
            for (int k4 = 0; k4 < 4; k4++) ln_frag(a[k4], lr0, lr1);
            if (nt == 0) {
                #pragma unroll
                for (int k4 = 0; k4 < 4; k4++) mma16816(dr, a[k4], s_wr[(ld * 4 + k4) * 8 + t], s_wr[(ld * 4 + k4) * 8 + 4 + t]);
            }
            mbar_wait(sBar + sl * 8, ld >= 6);
            WG_FENCE();
            #pragma unroll
            for (int k4 = 0; k4 < 4; k4++) wgmma_rs_n128(acc, a[k4], db0 + (uint64_t)(sl * 1024 + k4 * 128));
            WG_COMMIT();
            wg_wait<1>();
            if (ld >= 1 && ld <= 6 && (threadIdx.x & 127) == 0) mbar_arrive(sBar + 48 + (ld - 1) * 8);
        }
    }
    const int row0 = mt * 128 + warp * 16;
    if (nt == 0 && t == 0) {
        g_r[row0 + g] = bf16r(dr[0]); g_r[row0 + g + 8] = bf16r(dr[2]);
        g_stats[row0 + g] = make_float2(bf_lo(lr0.m2), rs0); g_stats[row0 + g + 8] = make_float2(bf_lo(lr1.m2), rs1);
    }
    wg_wait<0>();
    touch64(acc);
    CK(4);
    named_bar(3, 256);
    k1_store<8>(acc, 0, sB + wg * 16384, nt, mt, wg, warp & 3, lane);
    float acc2[32];
    #pragma unroll
    for (int i = 0; i < 32; i++) acc2[i] = 0.f;
    #pragma unroll 1
    for (int q = 0; q < 4; q++) {
        const int sl = q + 2;
        #pragma unroll
        for (int h2 = 0; h2 < 2; h2++) {
            uint32_t a[4][4];
            #pragma unroll
            for (int k4 = 0; k4 < 4; k4++) ldsm4(a[k4], laddr[k4] + (q * 2 + h2) * 16384);
            #pragma unroll
            for (int k4 = 0; k4 < 4; k4++) ln_frag(a[k4], lr0, lr1);
            if (h2 == 0) mbar_wait(sBar + sl * 8, 1);
            WG_FENCE();
            #pragma unroll
            for (int k4 = 0; k4 < 4; k4++) wgmma_rs_n64(acc2, a[k4], db0 + (uint64_t)(sl * 1024 + (h2 * 4 + k4) * 128));
            WG_COMMIT();
            wg_wait<1>();
        }
    }
    wg_wait<0>();
    touch32(acc2);
    CK(5);
    named_bar(1 + wg, 128);
    k1_store<4>(acc2, 8, sA + wg * 8192, nt, mt, wg, warp & 3, lane);
    asm volatile("cp.async.bulk.wait_group.read 0;" ::: "memory");
    CK(6);
}

constexpr int K2_THREADS = 512;
constexpr int K2_SMEM = 6 * 32768 + 12288;

constexpr float QS = 0.25f * 1.4426950408889634f;
constexpr float SC100 = 1.2676506002282294e30f;
__device__ __forceinline__ uint32_t polyexp2(float s0, float s1, float cd, uint32_t one2, uint32_t ca2) {
    constexpr float A = 128.0f * QS * 1.7763568394002505e-15f;
    float t0, t1;
    asm("fma.rn.f32 %0, %1, %2, %3;" : "=f"(t0) : "f"(s0), "f"(A), "f"(cd));
    asm("fma.rn.f32 %0, %1, %2, %3;" : "=f"(t1) : "f"(s1), "f"(A), "f"(cd));
    uint32_t W, U, h, G;
    asm("cvt.pack.sat.s16.s32 %0, %1, %2;" : "=r"(W) : "r"(__float_as_int(t1)), "r"(__float_as_int(t0)));
    asm("lop3.b32 %0, %1, 0x007F007F, %2, 0xEA;" : "=r"(U) : "r"(W), "r"(one2));
    asm("fma.rn.bf16x2 %0, %1, %2, %3;" : "=r"(h) : "r"(U), "r"(ca2), "r"(0xC300C300u));
    asm("fma.rn.bf16x2 %0, %1, %2, %3;" : "=r"(G) : "r"(h), "r"(U), "r"(0x438B438Bu));
    return W + G - 0x43404340u;
}

struct ExpC { float nm0, nm1, cd0, cd1; uint32_t one2, ca2; };

template <int G>
__device__ __forceinline__ void exp_block(const float* s, uint32_t* p, const ExpC& c) {
    #pragma unroll
    for (int hf = 0; hf < 2; hf++) {
        const float* x = s + hf * 4;
        if ((PMASK >> (G + hf)) & 1) {
            p[hf * 2 + 0] = polyexp2(x[0], x[1], c.cd0, c.one2, c.ca2);
            p[hf * 2 + 1] = polyexp2(x[2], x[3], c.cd1, c.one2, c.ca2);
        } else {
            p[hf * 2 + 0] = pack_bf16(ex2(fmaf(x[0], QS * SC100, c.nm0)), ex2(fmaf(x[1], QS * SC100, c.nm0)));
            p[hf * 2 + 1] = pack_bf16(ex2(fmaf(x[2], QS * SC100, c.nm1)), ex2(fmaf(x[3], QS * SC100, c.nm1)));
        }
    }
}

__device__ __forceinline__ void max16(const float* s, float& mx0, float& mx1) {
    #pragma unroll
    for (int j = 0; j < 4; j++) {
        mx0 = fmaxf(mx0, fmaxf(s[4 * j], s[4 * j + 1]));
        mx1 = fmaxf(mx1, fmaxf(s[4 * j + 2], s[4 * j + 3]));
    }
}

constexpr int MOE_SLOTS = 6, MOE_BOXES = 44;
__device__ __forceinline__ void moe_load(int b, int part, uint32_t ring, uint32_t bars, const CUtensorMap* mg, const CUtensorMap* mu, const CUtensorMap* md) {
    const int sl = b % MOE_SLOTS, grp = b & 1;
    if (b < 28) {
        const int j = b >> 1;
        mbar_expect_tx(bars + sl * 8, 32768);
        tma_2d(ring + sl * 32768, grp ? mu : mg, part * 448 + (j >> 1) * 64, (j & 1) * 256, bars + sl * 8);
    } else {
        const int j = (b - 28) >> 1;
        mbar_expect_tx(bars + sl * 8, 28672);
        tma_2d(ring + sl * 32768, md, ((j >> 1) * 2 + grp) * 64, part * 448 + (j & 1) * 224, bars + sl * 8);
    }
}
__device__ __forceinline__ void mma_2row(float* d, uint32_t a0, uint32_t a2, uint32_t b0, uint32_t b1) {
    asm("mma.sync.aligned.m16n8k16.row.col.f32.bf16.bf16.f32 {%0,%1,%2,%3}, {%4,%5,%6,%5}, {%7,%8}, {%0,%1,%2,%3};"
        : "+f"(d[0]), "+f"(d[1]), "+f"(d[2]), "+f"(d[3]) : "r"(a0), "r"(0u), "r"(a2), "r"(b0), "r"(b1));
}

__device__ void moe_cta(int part, unsigned char* smem, const __nv_bfloat16* __restrict__ x, const CUtensorMap* mg, const CUtensorMap* mu, const CUtensorMap* md) {
    const uint32_t ring = smem_u32(smem), bars = ring + MOE_SLOTS * 32768;
    __nv_bfloat16* xs = (__nv_bfloat16*)(smem + MOE_SLOTS * 32768 + 256);
    float* gu = (float*)(smem + MOE_SLOTS * 32768 + 256 + 2048);
    float* s_v = gu + 4 * 448;
    int* s_i = (int*)(s_v + 16);
    int* s_sel = s_i + 16;
    const int tid = threadIdx.x, warp = __shfl_sync(~0u, tid >> 5, 0), lane = tid & 31;
    if (tid == 0) {
        for (int i = 0; i < MOE_SLOTS; i++) { mbar_init(bars + i * 8, 1); mbar_init(bars + 128 + i * 8, 8); }
        asm volatile("fence.mbarrier_init.release.cluster;" ::: "memory");
        for (int b = 0; b < MOE_SLOTS; b++) moe_load(b, part, ring, bars, mg, mu, md);
    }
    pdl_wait();
    TL(1, 1);
    float rv[4];
    #pragma unroll
    for (int i = 0; i < 4; i++) rv[i] = g_r[tid + i * K2_THREADS];
    for (int pass = 0; pass < 2; pass++) {
        float bv = -INFINITY; int bi = 0x7fffffff;
        const int excl = pass ? s_sel[0] : -1;
        #pragma unroll
        for (int i = 0; i < 4; i++) {
            const int idx = tid + i * K2_THREADS;
            if (idx != excl && (rv[i] > bv || bi == 0x7fffffff)) { bv = rv[i]; bi = idx; }
        }
        #pragma unroll
        for (int o = 16; o; o >>= 1) {
            float ov = __shfl_xor_sync(~0u, bv, o); int oi = __shfl_xor_sync(~0u, bi, o);
            if (ov > bv || (ov == bv && oi < bi)) { bv = ov; bi = oi; }
        }
        if (lane == 0) { s_v[warp] = bv; s_i[warp] = bi; }
        __syncthreads();
        if (warp == 0) {
            bv = lane < 16 ? s_v[lane] : -INFINITY; bi = lane < 16 ? s_i[lane] : 0x7fffffff;
            #pragma unroll
            for (int o = 16; o; o >>= 1) {
                float ov = __shfl_xor_sync(~0u, bv, o); int oi = __shfl_xor_sync(~0u, bi, o);
                if (ov > bv || (ov == bv && oi < bi)) { bv = ov; bi = oi; }
            }
            if (lane == 0) s_sel[pass] = (bi == 0x7fffffff) ? pass : bi;
        }
        __syncthreads();
    }
    for (int i = tid; i < 1024; i += K2_THREADS) {
        const int tok = s_sel[i >> 9];
        const float2 st = g_stats[tok];
        xs[i] = __float2bfloat16_rn(ln_elem(__bfloat162float(x[(size_t)tok * D_ + (i & 511)]), st.x, st.y));
    }
    if (part == 0 && tid < 2) g_sel[tid] = s_sel[tid];
    __syncthreads();
    if (warp == 8) {
        if (lane == 0) {
            for (int b = MOE_SLOTS; b < MOE_BOXES; b++) {
                mbar_wait(bars + 128 + (b % MOE_SLOTS) * 8, (b / MOE_SLOTS - 1) & 1);
                moe_load(b, part, ring, bars, mg, mu, md);
            }
        }
        return;
    }
    if (warp > 8) return;
    const int nj = warp, g = lane >> 2, t = lane & 3;
    const uint32_t* xw = (const uint32_t*)xs + (g & 1) * 256 + t;
    uint32_t a[2][32];
    #pragma unroll
    for (int i = 0; i < 32; i++) { a[0][i] = xw[i * 4]; a[1][i] = xw[128 + i * 4]; }
    #pragma unroll 1
    for (int jp = 0; jp < MOE_BOXES / 4; jp++) {
        const bool down = jp >= 7;
        if (jp == 7) {
            named_bar(1, 256);
            for (int i = tid; i < 896; i += 256) {
                const float gs = bf16r(gu[i]), us = bf16r(gu[896 + i]);
                const float sl_ = bf16r(gs / (1.0f + __expf(-gs)));
                xs[(i / 448) * 512 + (i % 448)] = __float2bfloat16_rn(sl_ * us);
            }
            named_bar(1, 256);
            #pragma unroll
            for (int i = 0; i < 28; i++) { a[0][i] = xw[i * 4]; a[1][i] = xw[112 + i * 4]; }
        }
        float acc[2][4] = {{0.f, 0.f, 0.f, 0.f}, {0.f, 0.f, 0.f, 0.f}}, acb[2][4] = {{0.f, 0.f, 0.f, 0.f}, {0.f, 0.f, 0.f, 0.f}};
        #pragma unroll
        for (int q = 0; q < 4; q++) {
            const int hf = q >> 1, grp = q & 1;
            const int b = jp * 4 + q, sl = b % MOE_SLOTS;
            mbar_wait(bars + sl * 8, (b / MOE_SLOTS) & 1);
            const uint32_t baddr = ring + sl * 32768 + lane * 128 + ((nj ^ (lane & 7)) * 16);
            #pragma unroll
            for (int k4 = 0; k4 < 2; k4++) {
                uint32_t bf[4][4];
                #pragma unroll
                for (int k2 = 0; k2 < 4; k2++)
                    asm volatile("ldmatrix.sync.aligned.m8n8.x4.trans.shared.b16 {%0, %1, %2, %3}, [%4];"
                                 : "=r"(bf[k2][0]), "=r"(bf[k2][1]), "=r"(bf[k2][2]), "=r"(bf[k2][3]) : "r"(baddr + (k4 * 4 + k2) * 4096) : "memory");
                #pragma unroll
                for (int k2 = 0; k2 < 4; k2++) {
                    const int kk = k4 * 4 + k2;
                    if (kk < 7 || !down) {
                        mma_2row(acc[grp], a[hf][4 * kk], a[hf][4 * kk + 1], bf[k2][0], bf[k2][1]);
                        mma_2row(acb[grp], a[hf][4 * kk + 2], a[hf][4 * kk + 3], bf[k2][2], bf[k2][3]);
                    }
                }
            }
            __syncwarp();
            if (lane == 0) mbar_arrive(bars + 128 + sl * 8);
        }
        if (g < 2) {
            #pragma unroll
            for (int grp = 0; grp < 2; grp++) {
                const float2 v = make_float2(acc[grp][0] + acb[grp][0], acc[grp][1] + acb[grp][1]);
                if (!down) *(float2*)&gu[(grp * 2 + g) * 448 + jp * 64 + nj * 8 + t * 2] = v;
                else *(float2*)&g_ypart[part][g][((jp - 7) * 2 + grp) * 64 + nj * 8 + t * 2] = v;
            }
        }
    }
}

__global__ void __launch_bounds__(K2_THREADS, 1)
k2_attn(const __nv_bfloat16* __restrict__ x, const __nv_bfloat16* __restrict__ w_gate, const __nv_bfloat16* __restrict__ w_up,
        const __nv_bfloat16* __restrict__ w_down, const __grid_constant__ CUtensorMap mg, const __grid_constant__ CUtensorMap mu,
        const __grid_constant__ CUtensorMap md) {
    extern __shared__ __align__(1024) unsigned char smem[];
    TL(1, 0);
    pdl_launch();
    if (blockIdx.x >= 128) { moe_cta(blockIdx.x - 128, smem, x, &mg, &mu, &md); TL(1, 2); return; }
    if (threadIdx.x >= 32 && threadIdx.x < 35) {
        const __nv_bfloat16* w = threadIdx.x == 32 ? w_gate : (threadIdx.x == 33 ? w_up : w_down);
        asm volatile("cp.async.bulk.prefetch.L2.global [%0], %1;" :: "l"(w + (size_t)blockIdx.x * (D_ * F_ / 128)), "r"(D_ * F_ / 64) : "memory");
    }
    const uint32_t sK = smem_u32(smem), sV = sK + 65536, sQ = sV + 98304, sBar = sQ + 16384;
    const int h = blockIdx.x >> 2, qb = blockIdx.x & 3;
    const int warp = __shfl_sync(~0u, threadIdx.x >> 5, 0), lane = threadIdx.x & 31, wg = warp >> 2;
    if (threadIdx.x == 0) {
        mbar_init(sBar, 1); mbar_init(sBar + 8, 1);
        asm volatile("fence.mbarrier_init.release.cluster;" ::: "memory");
        mbar_expect_tx(sBar, 8192 + 12288 + 2 * 6144);
        mbar_expect_tx(sBar + 8, 8192 + 53248 + 2 * 26624);
    }
    for (int i = threadIdx.x; i < 2048; i += K2_THREADS)
        *(uint4*)(smem + 65536 + 65536 + i * 16) = make_uint4(0x3F803F80u, 0x3F803F80u, 0x3F803F80u, 0x3F803F80u);
    fence_async_smem();
    __syncthreads();
    if (warp == 0) {
        pdl_wait();
        TL(1, 1);
        const uint4* gk = g_K + (size_t)h * 4096;
        const uint4* gv = g_V + (size_t)h * 4096;
        const uint4* gq = g_Q + (size_t)h * 4096 + qb * 1024;
        if (lane == 0) bulk_g2s(sQ, gq, 8192, sBar);
        if (lane == 1) bulk_g2s(sK, gk, 12288, sBar);
        if (lane == 2) bulk_g2s(sV, gv, 6144, sBar);
        if (lane == 3) bulk_g2s(sV + 32768, gv + 2048, 6144, sBar);
        if (lane == 4) bulk_g2s(sK + 12288, gk + 768, 53248, sBar + 8);
        if (lane == 5) bulk_g2s(sV + 6144, gv + 384, 26624, sBar + 8);
        if (lane == 6) bulk_g2s(sV + 32768 + 6144, gv + 2048 + 384, 26624, sBar + 8);
        if (lane == 7) bulk_g2s(sQ + 8192, gq + 512, 8192, sBar + 8);
        __syncwarp();
    }
    ExpC c;
    {
        const volatile uint32_t* cc = g_const;
        c.one2 = cc[0]; c.ca2 = cc[1];
    }
    const uint64_t kdesc0 = make_desc(sK, 128, 256, 0);
    const uint64_t vdesc0 = make_desc(sV, 128, 32768, 0);
    #pragma unroll 1
    for (int pass = 0; pass < 2; pass++) {
        const bool dry = false;
        if (pass == 0) { mbar_wait(sBar, 0); __syncwarp(); TL(1, 2); }
        const int unit = (pass & 1) * 4 + wg;
        const uint64_t q = make_desc(sQ + unit * 2048, 128, 256, 0);
        float o[12];
        #pragma unroll 1
        for (int attempt = 0; attempt < 2; attempt++) {
            float s0[16], s1[16], s2[16];
            #pragma unroll
            for (int i = 0; i < 16; i++) { s0[i] = 0.f; s1[i] = 0.f; s2[i] = 0.f; }
            float mx0 = -INFINITY, mx1 = -INFINITY;
            if (attempt) {
                #pragma unroll 1
                for (int it = 0; it < 64; it++) {
                    WG_FENCE();
                    wgmma_qk32(s0, q, kdesc0 + it * 64);
                    WG_COMMIT();
                    wg_wait<0>();
                    touch16(s0);
                    max16(s0, mx0, mx1);
                }
            }
            #pragma unroll
            for (int i = 0; i < 12; i++) o[i] = 0.f;
            WG_FENCE();
            wgmma_qk32(s2, q, kdesc0);
            wgmma_qk32(s0, q, kdesc0 + 64);
            wgmma_qk32(s1, q, kdesc0 + 128);
            WG_COMMIT();
            wg_wait<0>();
            touch16(s0); touch16(s1); touch16(s2);
            max16(s0, mx0, mx1); max16(s1, mx0, mx1); max16(s2, mx0, mx1);
            mx0 = fmaxf(mx0, __shfl_xor_sync(~0u, mx0, 1)); mx0 = fmaxf(mx0, __shfl_xor_sync(~0u, mx0, 2));
            mx1 = fmaxf(mx1, __shfl_xor_sync(~0u, mx1, 1)); mx1 = fmaxf(mx1, __shfl_xor_sync(~0u, mx1, 2));
            const float bias = attempt ? 0.0f : 128.0f * 64.0f;
            const float y0 = ceilf(fmaf(mx0, 128.0f * QS * SC100, bias)), y1 = ceilf(fmaf(mx1, 128.0f * QS * SC100, bias));
            c.nm0 = __shfl_sync(~0u, y0 * (-1.0f / 128.0f), lane); c.nm1 = __shfl_sync(~0u, y1 * (-1.0f / 128.0f), lane);
            c.cd0 = __shfl_sync(~0u, __fmul_rn(16256.0f - y0, __int_as_float(1)), lane);
            c.cd1 = __shfl_sync(~0u, __fmul_rn(16256.0f - y1, __int_as_float(1)), lane);
            uint64_t kd = kdesc0 + 192, vd = vdesc0 + 32;
            {
                uint32_t pa[4], pb[4];
                exp_block<12>(s2, pa, c);
                exp_block<14>(s2 + 8, pb, c);
                WG_FENCE();
                wgmma_pv(o, pa, vdesc0); wgmma_pv(o, pb, vdesc0 + 16);
                WG_COMMIT();
            }
            #pragma unroll 1
            for (int seg = 0; seg < (dry ? 1 : 2); seg++) {
            if (seg) { wg_wait<0>(); mbar_wait(sBar + 8, 0); __syncwarp(); }
            #pragma unroll 1
            for (int it = seg ? 3 : (dry ? 2 : 0); it < (seg ? 21 : 3); it++) {
                uint32_t p[6][4];
                WG_FENCE();
                wgmma_qk32(s2, q, kd);
                WG_COMMIT();
                exp_block<0>(s0, p[0], c);
                exp_block<2>(s0 + 8, p[1], c);
                WG_FENCE();
                wgmma_pv(o, p[0], vd); wgmma_pv(o, p[1], vd + 16);
                wgmma_qk32(s0, q, kd + 64);
                WG_COMMIT();
                wg_wait<1>();
                touch16(s2);
                exp_block<4>(s1, p[2], c);
                exp_block<6>(s1 + 8, p[3], c);
                WG_FENCE();
                wgmma_pv(o, p[2], vd + 32); wgmma_pv(o, p[3], vd + 48);
                wgmma_qk32(s1, q, kd + 128);
                WG_COMMIT();
                wg_wait<1>();
                touch16(s0);
                exp_block<8>(s2, p[4], c);
                exp_block<10>(s2 + 8, p[5], c);
                WG_FENCE();
                wgmma_pv(o, p[4], vd + 64); wgmma_pv(o, p[5], vd + 80);
                WG_COMMIT();
                vd += 96; kd += 192;
                wg_wait<1>();
                touch16(s1);
            }
            }
            wg_wait<0>();
            touch12(o);
            if (attempt) break;
            float big = 0.f;
            #pragma unroll
            for (int i = 0; i < 12; i++) big = fmaxf(big, fabsf(o[i]));
            bool bad = !(big < 1e30f);
            #pragma unroll
            for (int i = 0; i < 12; i++) bad |= (o[i] != o[i]);
            uint32_t any;
            asm volatile("{.reg .pred p, q; setp.ne.u32 p, %1, 0; barrier.cta.red.or.pred.aligned q, %2, 128, p; selp.u32 %0, 1, 0, q;}"
                         : "=r"(any) : "r"((uint32_t)bad), "r"(1 + wg) : "memory");
            if (dry || !__any_sync(~0u, any)) break;
        }
        const int g = lane >> 2, t = lane & 3;
        const int r = (warp & 3) * 16 + g;
        const float i0 = __fdiv_rn(1.0f, o[8]), i1 = __fdiv_rn(1.0f, o[10]);
        uint32_t* ob = (uint32_t*)(g_O + (size_t)(qb * 8 + unit) * 4096 + (h >> 2) * 512 + r * 8) + t;
        const int c0 = ((h & 3) * 2) ^ (r & 7), c1 = ((h & 3) * 2 + 1) ^ (r & 7);
        if (!dry) {
            ob[c0 * 4] = pack_bf16(o[0] * i0, o[1] * i0);
            ob[c1 * 4] = pack_bf16(o[4] * i0, o[5] * i0);
            ob[256 + c0 * 4] = pack_bf16(o[2] * i1, o[3] * i1);
            ob[256 + c1 * 4] = pack_bf16(o[6] * i1, o[7] * i1);
            TL(1, 3 + pass);
        }
    }
}

constexpr int K3_THREADS = 256;
constexpr int K3_SMEM = 65536 + 131072 + 128;

__global__ void __launch_bounds__(K3_THREADS, 1)
k3_out(const __grid_constant__ CUtensorMap wmap, const __nv_bfloat16* __restrict__ x, __nv_bfloat16* __restrict__ out) {
    extern __shared__ __align__(1024) unsigned char smem[];
    const uint32_t sA = smem_u32(smem), sB = sA + 65536, sBar = sB + 131072;
    const int warp = __shfl_sync(~0u, threadIdx.x >> 5, 0), lane = threadIdx.x & 31, wg = warp >> 2;
    const int nt = blockIdx.x & 3, mt = blockIdx.x >> 2;
    TL(2, 0);
    if (threadIdx.x == 0) {
        for (int i = 0; i < 10; i++) mbar_init(sBar + i * 8, 1);
        asm volatile("fence.mbarrier_init.release.cluster;" ::: "memory");
        for (int i = 0; i < 8; i++) mbar_expect_tx(sBar + 16 + i * 8, 8192);
        for (int kh = 0; kh < 2; kh++) {
            mbar_expect_tx(sBar + kh * 8, 65536);
            tma_2d(sB + kh * 32768, &wmap, nt * 128, kh * 256, sBar + kh * 8);
            tma_2d(sB + 65536 + kh * 32768, &wmap, nt * 128 + 64, kh * 256, sBar + kh * 8);
        }
    }
    const int er = threadIdx.x >> 2, ec = (threadIdx.x & 3) * 32;
    const int row = mt * 64 + er;
    uint4 xv[4];
    #pragma unroll
    for (int j = 0; j < 4; j++) xv[j] = __ldg((const uint4*)(x + (size_t)row * D_ + nt * 128 + ec) + j);
    __syncthreads();
    pdl_wait();
    TL(2, 1);
    if (threadIdx.x < 8) bulk_g2s(sA + threadIdx.x * 8192, g_O + (size_t)mt * 4096 + threadIdx.x * 512, 8192, sBar + 16 + threadIdx.x * 8);
    const int sel0 = g_sel[0], sel1 = g_sel[1];
    const float2 st = g_stats[row];
    uint32_t bb[16];
    {
        const uint32_t xu[16] = {xv[0].x, xv[0].y, xv[0].z, xv[0].w, xv[1].x, xv[1].y, xv[1].z, xv[1].w,
                                 xv[2].x, xv[2].y, xv[2].z, xv[2].w, xv[3].x, xv[3].y, xv[3].z, xv[3].w};
        #pragma unroll
        for (int j = 0; j < 16; j++) bb[j] = pack_bf16(bf16r(bf_lo(xu[j]) - st.x) * st.y, bf16r(bf_hi(xu[j]) - st.x) * st.y);
        const int slot = row == sel0 ? 0 : (row == sel1 ? 1 : -1);
        if (slot >= 0) {
            const float gate = bf16r(1.0f / (1.0f + __expf(-g_r[row])));
            const int c0 = nt * 128 + ec;
            #pragma unroll
            for (int j = 0; j < 16; j++) {
                const float2 a = *(const float2*)&g_ypart[0][slot][c0 + 2 * j], b = *(const float2*)&g_ypart[1][slot][c0 + 2 * j];
                const float2 c = *(const float2*)&g_ypart[2][slot][c0 + 2 * j], d = *(const float2*)&g_ypart[3][slot][c0 + 2 * j];
                bb[j] = pack_bf16(bf_lo(bb[j]) + bf16r(bf16r(a.x + b.x + c.x + d.x) * gate), bf_hi(bb[j]) + bf16r(bf16r(a.y + b.y + c.y + d.y) * gate));
            }
        }
    }
    float acc[32];
    #pragma unroll
    for (int i = 0; i < 32; i++) acc[i] = 0.f;
    const uint64_t da0 = make_desc(sA, 16, 1024, 1);
    const uint64_t db0 = make_desc(sB + wg * 65536, 8192, 1024, 1);
    #pragma unroll 1
    for (int q = 0; q < 8; q++) {
        if ((q & 3) == 0) mbar_wait(sBar + (q >> 2) * 8, 0);
        mbar_wait(sBar + 16 + q * 8, 0);
        WG_FENCE();
        #pragma unroll
        for (int kk = 0; kk < 4; kk++)
            wgmma_n64(acc, da0 + (uint64_t)(q * 512 + kk * 2), db0 + (uint64_t)(q * 512 + kk * 128));
        WG_COMMIT();
    }
    wg_wait<0>();
    touch32(acc);
    TL(2, 2);
    __syncthreads();
    {
        const int g = lane >> 2, t = lane & 3;
        unsigned char* sp = smem + ((warp & 3) * 16 + g) * 272 + wg * 128 + t * 4;
        #pragma unroll
        for (int j = 0; j < 8; j++) {
            *(uint32_t*)(sp + j * 16) = pack_bf16(acc[4 * j], acc[4 * j + 1]);
            *(uint32_t*)(sp + 8 * 272 + j * 16) = pack_bf16(acc[4 * j + 2], acc[4 * j + 3]);
        }
    }
    __syncthreads();
    #pragma unroll
    for (int j = 0; j < 4; j++) {
        const uint4 av = *(const uint4*)(smem + er * 272 + ec * 2 + j * 16);
        const uint32_t au[4] = {av.x, av.y, av.z, av.w}, xu[4] = {xv[j].x, xv[j].y, xv[j].z, xv[j].w};
        uint32_t o[4];
        #pragma unroll
        for (int i = 0; i < 4; i++) {
            uint32_t t2;
            asm("add.rn.bf16x2 %0, %1, %2;" : "=r"(t2) : "r"(xu[i]), "r"(au[i]));
            asm("add.rn.bf16x2 %0, %1, %2;" : "=r"(o[i]) : "r"(t2), "r"(bb[j * 4 + i]));
        }
        *((uint4*)(out + (size_t)row * D_ + nt * 128 + ec) + j) = make_uint4(o[0], o[1], o[2], o[3]);
    }
    TL(2, 3);
}

typedef CUresult (*EncodeFn)(CUtensorMap*, CUtensorMapDataType, cuuint32_t, void*, const cuuint64_t*, const cuuint64_t*,
                             const cuuint32_t*, const cuuint32_t*, CUtensorMapInterleave, CUtensorMapSwizzle,
                             CUtensorMapL2promotion, CUtensorMapFloatOOBfill);

void make_wmap(EncodeFn fn, CUtensorMap* map, const void* ptr, int rows, int cols, int box_rows) {
    cuuint64_t dims[2] = {(cuuint64_t)cols, (cuuint64_t)rows};
    cuuint64_t strides[1] = {(cuuint64_t)cols * 2};
    cuuint32_t box[2] = {64, (cuuint32_t)box_rows};
    cuuint32_t es[2] = {1, 1};
    fn(map, CU_TENSOR_MAP_DATA_TYPE_BFLOAT16, 2, (void*)ptr, dims, strides, box, es, CU_TENSOR_MAP_INTERLEAVE_NONE,
       CU_TENSOR_MAP_SWIZZLE_128B, CU_TENSOR_MAP_L2_PROMOTION_L2_256B, CU_TENSOR_MAP_FLOAT_OOB_FILL_NONE);
}

}

extern "C" void kernel_launch(void* const* d_in, const int* in_sizes, int n_in, void* d_out, int out_size) {
    const __nv_bfloat16* x = (const __nv_bfloat16*)d_in[0];
    const __nv_bfloat16* wqkv = (const __nv_bfloat16*)d_in[1];
    const __nv_bfloat16* wo = (const __nv_bfloat16*)d_in[2];
    const __nv_bfloat16* w_r = (const __nv_bfloat16*)d_in[4];
    const __nv_bfloat16* w_gate = (const __nv_bfloat16*)d_in[5];
    const __nv_bfloat16* w_up = (const __nv_bfloat16*)d_in[6];
    const __nv_bfloat16* w_down = (const __nv_bfloat16*)d_in[7];
    __nv_bfloat16* out = (__nv_bfloat16*)d_out;

    static EncodeFn encode = nullptr;
    if (!encode) {
        void* fn = nullptr;
        cudaDriverEntryPointQueryResult qres;
        cudaGetDriverEntryPoint("cuTensorMapEncodeTiled", &fn, cudaEnableDefault, &qres);
        encode = (EncodeFn)fn;
        cudaFuncSetAttribute(k1_ln_qkv, cudaFuncAttributeMaxDynamicSharedMemorySize, K1_SMEM);
        cudaFuncSetAttribute(k2_attn, cudaFuncAttributeMaxDynamicSharedMemorySize, K2_SMEM);
        cudaFuncSetAttribute(k3_out, cudaFuncAttributeMaxDynamicSharedMemorySize, K3_SMEM);
    }
    CUtensorMap map_qkv, map_wo, map_x, map_g, map_u, map_d;
    make_wmap(encode, &map_g, w_gate, D_, F_, 256);
    make_wmap(encode, &map_u, w_up, D_, F_, 256);
    make_wmap(encode, &map_d, w_down, F_, D_, 224);
    make_wmap(encode, &map_x, x, S_, D_, 64);
    make_wmap(encode, &map_qkv, wqkv, D_, 3 * D_, 64);
    make_wmap(encode, &map_wo, wo, D_, D_, 256);

    k1_ln_qkv<<<128, K1_THREADS, K1_SMEM, cudaStreamPerThread>>>(map_qkv, map_x, w_r);
    cudaLaunchAttribute at[1];
    at[0].id = cudaLaunchAttributeProgrammaticStreamSerialization;
    at[0].val.programmaticStreamSerializationAllowed = 1;
    cudaLaunchConfig_t cfg = {};
    cfg.stream = cudaStreamPerThread;
    cfg.attrs = at; cfg.numAttrs = 1;
    cfg.gridDim = dim3(132); cfg.blockDim = dim3(K2_THREADS); cfg.dynamicSmemBytes = K2_SMEM;
    cudaLaunchKernelEx(&cfg, k2_attn, x, w_gate, w_up, w_down, map_g, map_u, map_d);
    cfg.gridDim = dim3(128); cfg.blockDim = dim3(K3_THREADS); cfg.dynamicSmemBytes = K3_SMEM;
    cudaLaunchKernelEx(&cfg, k3_out, map_wo, x, out);
}
```

```cpp
#include <cuda_runtime.h>
#include <cuda_bf16.h>
#include <cuda.h>
#include <stdint.h>

namespace {

constexpr int S_ = 2048, D_ = 512, H_ = 32, F_ = 1792;

constexpr uint32_t PMASK = 0xDB6;

__device__ __align__(1024) uint4 g_QKV[3 * H_ * S_ * 2];
#define g_Q (g_QKV)
#define g_K (g_QKV + H_ * S_ * 2)
#define g_V (g_QKV + 2 * H_ * S_ * 2)
__device__ __align__(1024) uint4 g_O[S_ * D_ / 8];
__device__ float2 g_stats[S_];
__device__ uint32_t g_const[2] = {0x3F803F80u, 0x42294229u};
__device__ float g_r[S_];
__device__ __align__(16) float g_ypart[4][2][D_];
__device__ int g_sel[2];

#define TL(k, p)
#define CK(i)
__device__ __forceinline__ uint32_t smem_u32(const void* p) { return (uint32_t)__cvta_generic_to_shared(p); }
__device__ __forceinline__ float bf16r(float x) { return __bfloat162float(__float2bfloat16_rn(x)); }
__device__ __forceinline__ uint32_t pack_bf16(float lo, float hi) {
    uint32_t r; asm("cvt.rn.bf16x2.f32 %0, %1, %2;" : "=r"(r) : "f"(hi), "f"(lo)); return r;
}
__device__ __forceinline__ float bf_lo(uint32_t u) { return __uint_as_float(u << 16); }
__device__ __forceinline__ float bf_hi(uint32_t u) { return __uint_as_float(u & 0xFFFF0000u); }
__device__ __forceinline__ float ex2(float x) { float y; asm("ex2.approx.ftz.f32 %0, %1;" : "=f"(y) : "f"(x)); return y; }

__device__ __forceinline__ void mbar_init(uint32_t bar, uint32_t count) {
    asm volatile("mbarrier.init.shared::cta.b64 [%0], %1;" :: "r"(bar), "r"(count) : "memory");
}
__device__ __forceinline__ void mbar_expect_tx(uint32_t bar, uint32_t bytes) {
    asm volatile("mbarrier.arrive.expect_tx.shared::cta.b64 _, [%0], %1;" :: "r"(bar), "r"(bytes) : "memory");
}
__device__ __forceinline__ void mbar_arrive(uint32_t bar) {
    asm volatile("mbarrier.arrive.shared::cta.b64 _, [%0];" :: "r"(bar) : "memory");
}
__device__ __forceinline__ void mbar_wait(uint32_t bar, uint32_t parity) {
    uint32_t done;
    #pragma unroll 1
    for (int it = 0; it < (1 << 26); it++) {
        asm volatile("{.reg .pred p; mbarrier.try_wait.parity.shared::cta.b64 p, [%1], %2; selp.u32 %0, 1, 0, p;}"
                     : "=r"(done) : "r"(bar), "r"(parity) : "memory");
        if (done) return;
    }
    __trap();
}
__device__ __forceinline__ void bulk_g2s(uint32_t dst, const void* src, uint32_t bytes, uint32_t bar) {
    asm volatile("cp.async.bulk.shared::cluster.global.mbarrier::complete_tx::bytes [%0], [%1], %2, [%3];"
                 :: "r"(dst), "l"(src), "r"(bytes), "r"(bar) : "memory");
}
__device__ __forceinline__ void tma_2d(uint32_t dst, const CUtensorMap* map, int c0, int c1, uint32_t bar) {
    asm volatile("cp.async.bulk.tensor.2d.shared::cluster.global.mbarrier::complete_tx::bytes [%0], [%1, {%3, %4}], [%2];"
                 :: "r"(dst), "l"(map), "r"(bar), "r"(c0), "r"(c1) : "memory");
}
__device__ __forceinline__ void fence_async_smem() { asm volatile("fence.proxy.async.shared::cta;" ::: "memory"); }
__device__ __forceinline__ void named_bar(int id, int n) { asm volatile("bar.sync %0, %1;" :: "r"(id), "r"(n) : "memory"); }

__device__ __forceinline__ uint64_t make_desc(uint32_t saddr, uint32_t lbo, uint32_t sbo, uint32_t swz) {
    return (uint64_t)((saddr & 0x3FFFF) >> 4) | ((uint64_t)(lbo >> 4) << 16) | ((uint64_t)(sbo >> 4) << 32) | ((uint64_t)swz << 62);
}
#define WG_FENCE() asm volatile("wgmma.fence.sync.aligned;" ::: "memory")
#define WG_COMMIT() asm volatile("wgmma.commit_group.sync.aligned;" ::: "memory")
template <int N> __device__ __forceinline__ void wg_wait() { asm volatile("wgmma.wait_group.sync.aligned %0;" :: "n"(N) : "memory"); }

#define F4(d, o) "+f"(d[o]), "+f"(d[o + 1]), "+f"(d[o + 2]), "+f"(d[o + 3])
#define F16(d, o) F4(d, o), F4(d, o + 4), F4(d, o + 8), F4(d, o + 12)
#define F32(d, o) F16(d, o), F16(d, o + 16)

__device__ __forceinline__ void wgmma_n128(float* d, uint64_t da, uint64_t db) {
    asm volatile("wgmma.mma_async.sync.aligned.m64n128k16.f32.bf16.bf16 "
        "{%0,%1,%2,%3,%4,%5,%6,%7,%8,%9,%10,%11,%12,%13,%14,%15,%16,%17,%18,%19,%20,%21,%22,%23,%24,%25,%26,%27,%28,%29,%30,%31,"
        "%32,%33,%34,%35,%36,%37,%38,%39,%40,%41,%42,%43,%44,%45,%46,%47,%48,%49,%50,%51,%52,%53,%54,%55,%56,%57,%58,%59,%60,%61,%62,%63}, "
        "%64, %65, 1, 1, 1, 0, 1;\n"
        : F32(d, 0), F32(d, 32) : "l"(da), "l"(db));
}
__device__ __forceinline__ void wgmma_n64(float* d, uint64_t da, uint64_t db) {
    asm volatile("wgmma.mma_async.sync.aligned.m64n64k16.f32.bf16.bf16 "
        "{%0,%1,%2,%3,%4,%5,%6,%7,%8,%9,%10,%11,%12,%13,%14,%15,%16,%17,%18,%19,%20,%21,%22,%23,%24,%25,%26,%27,%28,%29,%30,%31}, "
        "%32, %33, 1, 1, 1, 0, 1;\n"
        : F32(d, 0) : "l"(da), "l"(db));
}
__device__ __forceinline__ void wgmma_qk32(float* d, uint64_t qd, uint64_t kd) {
    asm volatile("wgmma.mma_async.sync.aligned.m64n32k16.f32.bf16.bf16 {%0,%1,%2,%3,%4,%5,%6,%7,%8,%9,%10,%11,%12,%13,%14,%15}, %16, %17, 0, 1, 1, 0, 0;\n"
        : F16(d, 0) : "l"(qd), "l"(kd));
}
__device__ __forceinline__ void wgmma_pv(float* d, const uint32_t* a, uint64_t vd) {
    asm volatile("wgmma.mma_async.sync.aligned.m64n24k16.f32.bf16.bf16 {%0,%1,%2,%3,%4,%5,%6,%7,%8,%9,%10,%11}, {%12,%13,%14,%15}, %16, 1, 1, 1, 1;\n"
        : F4(d, 0), F4(d, 4), F4(d, 8) : "r"(a[0]), "r"(a[1]), "r"(a[2]), "r"(a[3]), "l"(vd));
}
__device__ __forceinline__ void touch16(float* d) { asm volatile("" : F16(d, 0) :: "memory"); }
__device__ __forceinline__ void touch12(float* d) { asm volatile("" : F4(d, 0), F4(d, 4), F4(d, 8) :: "memory"); }
__device__ __forceinline__ void touch32(float* d) { asm volatile("" : F32(d, 0) :: "memory"); }
__device__ __forceinline__ void touch64(float* d) { asm volatile("" : F32(d, 0), F32(d, 32) :: "memory"); }

__device__ __forceinline__ float ln_elem(float x, float mean_b, float rden) {
    return bf16r(bf16r(x - mean_b) * rden);
}
__device__ __forceinline__ void pdl_wait() { asm volatile("griddepcontrol.wait;" ::: "memory"); }
__device__ __forceinline__ void pdl_launch() { asm volatile("griddepcontrol.launch_dependents;" ::: "memory"); }
__device__ __forceinline__ void cluster_arrive() { asm volatile("barrier.cluster.arrive.release.aligned;" ::: "memory"); }
__device__ __forceinline__ void cluster_wait() { asm volatile("barrier.cluster.wait.acquire.aligned;" ::: "memory"); }

constexpr int K1_THREADS = 288;
constexpr int K1_SMEM = 131072 + 6 * 16384 + 256 + 1024;

__device__ __forceinline__ void ldsm4(uint32_t* r, uint32_t addr) {
    asm volatile("ldmatrix.sync.aligned.m8n8.x4.shared.b16 {%0, %1, %2, %3}, [%4];" : "=r"(r[0]), "=r"(r[1]), "=r"(r[2]), "=r"(r[3]) : "r"(addr) : "memory");
}
__device__ __forceinline__ void stsm4(uint32_t addr, uint32_t r0, uint32_t r1, uint32_t r2, uint32_t r3) {
    asm volatile("stmatrix.sync.aligned.m8n8.x4.shared.b16 [%0], {%1, %2, %3, %4};" :: "r"(addr), "r"(r0), "r"(r1), "r"(r2), "r"(r3) : "memory");
}
__device__ __forceinline__ void mma16816(float* d, const uint32_t* a, uint32_t b0, uint32_t b1) {
    asm("mma.sync.aligned.m16n8k16.row.col.f32.bf16.bf16.f32 {%0,%1,%2,%3}, {%4,%5,%6,%7}, {%8,%9}, {%0,%1,%2,%3};"
        : "+f"(d[0]), "+f"(d[1]), "+f"(d[2]), "+f"(d[3]) : "r"(a[0]), "r"(a[1]), "r"(a[2]), "r"(a[3]), "r"(b0), "r"(b1));
}
__device__ __forceinline__ uint32_t sub_bf16x2(uint32_t a, uint32_t b) {
    uint32_t d; asm("sub.rn.bf16x2 %0, %1, %2;" : "=r"(d) : "r"(a), "r"(b)); return d;
}
__device__ __forceinline__ uint32_t ln_pair(uint32_t x2, uint32_t mean2, uint32_t rhi2, uint32_t rlo2) {
    const uint32_t d = sub_bf16x2(x2, mean2);
    uint32_t t, y;
    asm("mul.rn.bf16x2 %0, %1, %2;" : "=r"(t) : "r"(d), "r"(rlo2));
    asm("fma.rn.bf16x2 %0, %1, %2, %3;" : "=r"(y) : "r"(d), "r"(rhi2), "r"(t));
    return y;
}
struct LnRow { uint32_t m2, hi2, lo2; };
__device__ __forceinline__ LnRow ln_row(float mean, float rden) {
    LnRow r;
    r.m2 = pack_bf16(mean, mean);
    r.hi2 = pack_bf16(rden, rden);
    const float lo = rden - bf_lo(r.hi2);
    r.lo2 = pack_bf16(lo, lo);
    return r;
}
__device__ __forceinline__ void ln_frag(uint32_t* a, const LnRow& r0, const LnRow& r1) {
    a[0] = ln_pair(a[0], r0.m2, r0.hi2, r0.lo2); a[1] = ln_pair(a[1], r1.m2, r1.hi2, r1.lo2);
    a[2] = ln_pair(a[2], r0.m2, r0.hi2, r0.lo2); a[3] = ln_pair(a[3], r1.m2, r1.hi2, r1.lo2);
}

template <int NJ>
__device__ __forceinline__ void k1_store(const float* acc, int jj0, uint32_t stage, int nt, int mt, int wg, int w4, int lane) {
    const int mi = lane >> 3, lr = lane & 7;
    const uint32_t off_qk = stage + (w4 * 2 + (mi & 1)) * 256 + (mi >> 1) * 128 + lr * 16;
    const uint32_t off_v = stage + (mi >> 1) * 1024 + (w4 * 16 + (mi & 1) * 8 + lr) * 16;
    #pragma unroll
    for (int jj = 0; jj < NJ; jj++) {
        const bool isv = nt * 12 + jj0 + jj >= 64;
        const float m = isv ? 1.0f : 8.8817841970012523e-16f;
        stsm4((isv ? off_v : off_qk) + jj * 2048,
              pack_bf16(acc[8 * jj] * m, acc[8 * jj + 1] * m), pack_bf16(acc[8 * jj + 2] * m, acc[8 * jj + 3] * m),
              pack_bf16(acc[8 * jj + 4] * m, acc[8 * jj + 5] * m), pack_bf16(acc[8 * jj + 6] * m, acc[8 * jj + 7] * m));
    }
    fence_async_smem();
    named_bar(1 + wg, 128);
    if (lane < NJ / 2) {
        const int pc = w4 * (NJ / 2) + lane, jj = pc >> 1, hf = pc & 1, hg = nt * 12 + jj0 + jj;
        const unsigned char* dst = (const unsigned char*)g_QKV + (size_t)hg * 65536
            + (hg >= 64 ? hf * 32768 + (mt * 128 + wg * 64) * 16 : (mt * 16 + wg * 8) * 256 + hf * 1024);
        asm volatile("cp.async.bulk.global.shared::cta.bulk_group [%0], [%1], 1024;" :: "l"(dst), "r"(stage + pc * 1024) : "memory");
        asm volatile("cp.async.bulk.commit_group;" ::: "memory");
    }
}

__global__ void __launch_bounds__(K1_THREADS, 1)
k1_ln_qkv(const __grid_constant__ CUtensorMap wmap, const __grid_constant__ CUtensorMap xmap, const __nv_bfloat16* __restrict__ w_r) {
    extern __shared__ __align__(1024) unsigned char smem[];
    const uint32_t sA = smem_u32(smem), sB = sA + 131072, sBar = sB + 6 * 16384;
    const int warp = __shfl_sync(~0u, threadIdx.x >> 5, 0), lane = threadIdx.x & 31;
    const int nt = blockIdx.x & 7, mt = blockIdx.x >> 3;
    const int wg = warp >> 2;
    CK(0);
    pdl_launch();
    uint32_t* s_wr = (uint32_t*)(smem + 131072 + 6 * 16384 + 256);
    if (warp == 8) {
        if (lane == 0) {
            for (int i = 0; i < 6; i++) { mbar_init(sBar + i * 8, 1); mbar_init(sBar + 48 + i * 8, 2); }
            asm volatile("fence.mbarrier_init.release.cluster;" ::: "memory");
            for (int i = 0; i < 6; i++) mbar_expect_tx(sBar + i * 8, 16384);
        }
        if (lane < 4) {
            mbar_init(sBar + 96 + lane * 8, 1);
            asm volatile("fence.mbarrier_init.release.cluster;" ::: "memory");
            mbar_expect_tx(sBar + 96 + lane * 8, 32768);
        }
        __syncwarp();
        if (lane < 16) {
            const int pn = (lane >> 3) * 4 + (lane & 3), hf = (lane >> 2) & 1;
            tma_2d(sA + pn * 16384 + hf * 8192, &xmap, pn * 64, mt * 128 + hf * 64, sBar + 96 + (lane >> 2) * 8);
        }
        named_bar(3, K1_THREADS);
        mbar_wait(sBar + 96 + 8, 0);
        if (lane < 12) {
            const int ld = lane >> 1, j = lane & 1;
            tma_2d(sB + ld * 16384 + j * 8192, &wmap, nt * 192 + j * 64, ld * 64, sBar + ld * 8);
        }
        __syncwarp();
        if (lane < 2) {
            for (int ld = 6; ld < 12; ld++) {
                const int sl = ld - 6;
                mbar_wait(sBar + 48 + sl * 8, 0);
                if (lane == 0) mbar_expect_tx(sBar + sl * 8, 16384);
                __syncwarp(3);
                if (ld < 8) tma_2d(sB + sl * 16384 + lane * 8192, &wmap, nt * 192 + lane * 64, ld * 64, sBar + sl * 8);
                else tma_2d(sB + sl * 16384 + lane * 8192, &wmap, nt * 192 + 128, (ld - 8) * 128 + lane * 64, sBar + sl * 8);
            }
        }
        return;
    }
    if (nt == 0) s_wr[threadIdx.x] = __ldg((const uint32_t*)w_r + threadIdx.x);
    named_bar(3, K1_THREADS);
    const int g = lane >> 2, t = lane & 3;
    const int lrow = warp * 16 + (lane & 7) + ((lane >> 3) & 1) * 8;
    const uint32_t lbase = sA + lrow * 128;
    const int lsw = lane & 7, lhi = lane >> 4;
    uint32_t laddr[4];
    #pragma unroll
    for (int k4 = 0; k4 < 4; k4++) laddr[k4] = lbase + (((k4 * 2 + lhi) ^ lsw) * 16);
    CK(1);
    float dsum[4] = {0.f, 0.f, 0.f, 0.f}, dq0[4] = {0.f, 0.f, 0.f, 0.f}, dq1[4] = {0.f, 0.f, 0.f, 0.f};
    float esum[4] = {0.f, 0.f, 0.f, 0.f}, eq0[4] = {0.f, 0.f, 0.f, 0.f}, eq1[4] = {0.f, 0.f, 0.f, 0.f};
    #pragma unroll 2
    for (int pn = 0; pn < 8; pn++) {
        uint32_t a[4][4];
        if ((pn & 3) == 0) mbar_wait(sBar + 96 + ((pn >> 2) * 2 + wg) * 8, 0);
        #pragma unroll
        for (int k4 = 0; k4 < 4; k4++) ldsm4(a[k4], laddr[k4] + pn * 16384);
        #pragma unroll
        for (int k4 = 0; k4 < 4; k4 += 2) {
            mma16816(dsum, a[k4], 0x3F803F80u, 0x3F803F80u);
            mma16816(dq0, a[k4], a[k4][0], a[k4][2]);
            mma16816(dq1, a[k4], a[k4][1], a[k4][3]);
            mma16816(esum, a[k4 + 1], 0x3F803F80u, 0x3F803F80u);
            mma16816(eq0, a[k4 + 1], a[k4 + 1][0], a[k4 + 1][2]);
            mma16816(eq1, a[k4 + 1], a[k4 + 1][1], a[k4 + 1][3]);
        }
    }
    #pragma unroll
    for (int i = 0; i < 4; i++) { dsum[i] += esum[i]; dq0[i] += eq0[i]; dq1[i] += eq1[i]; }
    CK(3);
    const int dsrc = g * 4 + (g >> 1);
    const float sq0 = __shfl_sync(~0u, (g & 1) ? dq0[1] : dq0[0], dsrc), sq1 = __shfl_sync(~0u, (g & 1) ? dq1[3] : dq1[2], dsrc);
    const float mean0 = dsum[0] * (1.0f / D_), mean1 = dsum[2] * (1.0f / D_);
    float var0 = fmaf(-mean0, mean0, sq0 * (1.0f / D_)), var1 = fmaf(-mean1, mean1, sq1 * (1.0f / D_));
    if (__any_sync(~0u, !(mean0 * mean0 <= 16.0f * var0) || !(mean1 * mean1 <= 16.0f * var1))) {
        float q0 = 0.f, q1 = 0.f;
        #pragma unroll 1
        for (int ks = 0; ks < 32; ks++) {
            uint32_t a[4];
            ldsm4(a, lbase + (ks >> 2) * 16384 + ((((ks & 3) * 2 + lhi) ^ lsw) * 16));
            #pragma unroll
            for (int i = 0; i < 4; i++) {
                const float m = (i & 1) ? mean1 : mean0;
                const float d0 = bf_lo(a[i]) - m, d1 = bf_hi(a[i]) - m;
                if (i & 1) q1 = fmaf(d0, d0, fmaf(d1, d1, q1)); else q0 = fmaf(d0, d0, fmaf(d1, d1, q0));
            }
        }
        q0 += __shfl_xor_sync(~0u, q0, 1); q0 += __shfl_xor_sync(~0u, q0, 2);
        q1 += __shfl_xor_sync(~0u, q1, 1); q1 += __shfl_xor_sync(~0u, q1, 2);
        var0 = q0 * (1.0f / D_); var1 = q1 * (1.0f / D_);
    }
    const float rs0 = __frcp_rn(bf16r(__fsqrt_rn(bf16r(bf16r(var0) + 1e-5f))));
    const float rs1 = __frcp_rn(bf16r(__fsqrt_rn(bf16r(bf16r(var1) + 1e-5f))));
    const LnRow lr0 = ln_row(mean0, rs0), lr1 = ln_row(mean1, rs1);
    float acc[64];
    #pragma unroll
    for (int i = 0; i < 64; i++) acc[i] = 0.f;
    float dr[4] = {0.f, 0.f, 0.f, 0.f};
    const uint64_t da0 = make_desc(sA + wg * 8192, 16, 1024, 1);
    const uint64_t db0 = make_desc(sB, 8192, 1024, 1);
    #pragma unroll 1
    for (int ld = 0; ld < 8; ld++) {
        const int sl = ld < 6 ? ld : ld - 6;
        uint32_t a[4][4];
        #pragma unroll
        for (int k4 = 0; k4 < 4; k4++) ldsm4(a[k4], laddr[k4] + ld * 16384);
        #pragma unroll
        for (int k4 = 0; k4 < 4; k4++) ln_frag(a[k4], lr0, lr1);
        #pragma unroll
        for (int k4 = 0; k4 < 4; k4++) stsm4(laddr[k4] + ld * 16384, a[k4][0], a[k4][1], a[k4][2], a[k4][3]);
        fence_async_smem();
        if (nt == 0) {
            #pragma unroll
            for (int k4 = 0; k4 < 4; k4++) mma16816(dr, a[k4], s_wr[(ld * 4 + k4) * 8 + t], s_wr[(ld * 4 + k4) * 8 + 4 + t]);
        }
        mbar_wait(sBar + sl * 8, ld >= 6);
        named_bar(1 + wg, 128);
        WG_FENCE();
        #pragma unroll
        for (int k4 = 0; k4 < 4; k4++) wgmma_n128(acc, da0 + (uint64_t)(ld * 1024 + k4 * 2), db0 + (uint64_t)(sl * 1024 + k4 * 128));
        WG_COMMIT();
        wg_wait<1>();
        if (ld >= 1 && ld <= 6 && (threadIdx.x & 127) == 0) mbar_arrive(sBar + 48 + (ld - 1) * 8);
    }
    float acc2[32];
    #pragma unroll
    for (int i = 0; i < 32; i++) acc2[i] = 0.f;
    mbar_wait(sBar + 2 * 8, 1);
    WG_FENCE();
    #pragma unroll
    for (int k8 = 0; k8 < 8; k8++) wgmma_n64(acc2, da0 + (uint64_t)((k8 >> 2) * 1024 + (k8 & 3) * 2), db0 + (uint64_t)(2 * 1024 + k8 * 128));
    WG_COMMIT();
    const int row0 = mt * 128 + warp * 16;
    if (nt == 0 && t == 0) {
        g_r[row0 + g] = bf16r(dr[0]); g_r[row0 + g + 8] = bf16r(dr[2]);
        g_stats[row0 + g] = make_float2(bf_lo(lr0.m2), rs0); g_stats[row0 + g + 8] = make_float2(bf_lo(lr1.m2), rs1);
    }
    wg_wait<1>();
    touch64(acc);
    CK(4);
    #pragma unroll 1
    for (int q = 1; q < 4; q++) {
        mbar_wait(sBar + (q + 2) * 8, 1);
        WG_FENCE();
        #pragma unroll
        for (int k8 = 0; k8 < 8; k8++)
            wgmma_n64(acc2, da0 + (uint64_t)((q * 2 + (k8 >> 2)) * 1024 + (k8 & 3) * 2), db0 + (uint64_t)((q + 2) * 1024 + k8 * 128));
        WG_COMMIT();
    }
    named_bar(3, 256);
    k1_store<8>(acc, 0, sB + wg * 16384, nt, mt, wg, warp & 3, lane);
    wg_wait<0>();
    touch32(acc2);
    CK(5);
    named_bar(1 + wg, 128);
    k1_store<4>(acc2, 8, sA + wg * 8192, nt, mt, wg, warp & 3, lane);
    asm volatile("cp.async.bulk.wait_group.read 0;" ::: "memory");
    CK(6);
}

constexpr int K2_THREADS = 512;
constexpr int K2_SMEM = 6 * 32768 + 12288;

constexpr float QS = 0.25f * 1.4426950408889634f;
constexpr float SC100 = 1.2676506002282294e30f;
__device__ __forceinline__ uint32_t polyexp2(float s0, float s1, float cd, uint32_t one2, uint32_t ca2) {
    constexpr float A = 128.0f * QS * 1.7763568394002505e-15f;
    float t0, t1;
    asm("fma.rn.f32 %0, %1, %2, %3;" : "=f"(t0) : "f"(s0), "f"(A), "f"(cd));
    asm("fma.rn.f32 %0, %1, %2, %3;" : "=f"(t1) : "f"(s1), "f"(A), "f"(cd));
    uint32_t W, U, h, G;
    asm("cvt.pack.sat.s16.s32 %0, %1, %2;" : "=r"(W) : "r"(__float_as_int(t1)), "r"(__float_as_int(t0)));
    asm("lop3.b32 %0, %1, 0x007F007F, %2, 0xEA;" : "=r"(U) : "r"(W), "r"(one2));
    asm("fma.rn.bf16x2 %0, %1, %2, %3;" : "=r"(h) : "r"(U), "r"(ca2), "r"(0xC300C300u));
    asm("fma.rn.bf16x2 %0, %1, %2, %3;" : "=r"(G) : "r"(h), "r"(U), "r"(0x438B438Bu));
    return W + G - 0x43404340u;
}

struct ExpC { float nm0, nm1, cd0, cd1; uint32_t one2, ca2; };

template <int G>
__device__ __forceinline__ void exp_block(const float* s, uint32_t* p, const ExpC& c) {
    #pragma unroll
    for (int hf = 0; hf < 2; hf++) {
        const float* x = s + hf * 4;
        if ((PMASK >> (G + hf)) & 1) {
            p[hf * 2 + 0] = polyexp2(x[0], x[1], c.cd0, c.one2, c.ca2);
            p[hf * 2 + 1] = polyexp2(x[2], x[3], c.cd1, c.one2, c.ca2);
        } else {
            p[hf * 2 + 0] = pack_bf16(ex2(fmaf(x[0], QS * SC100, c.nm0)), ex2(fmaf(x[1], QS * SC100, c.nm0)));
            p[hf * 2 + 1] = pack_bf16(ex2(fmaf(x[2], QS * SC100, c.nm1)), ex2(fmaf(x[3], QS * SC100, c.nm1)));
        }
    }
}

__device__ __forceinline__ void max16(const float* s, float& mx0, float& mx1) {
    #pragma unroll
    for (int j = 0; j < 4; j++) {
        mx0 = fmaxf(mx0, fmaxf(s[4 * j], s[4 * j + 1]));
        mx1 = fmaxf(mx1, fmaxf(s[4 * j + 2], s[4 * j + 3]));
    }
}

constexpr int MOE_SLOTS = 6, MOE_BOXES = 44;
__device__ __forceinline__ void moe_load(int b, int part, uint32_t ring, uint32_t bars, const CUtensorMap* mg, const CUtensorMap* mu, const CUtensorMap* md) {
    const int sl = b % MOE_SLOTS, grp = b & 1;
    if (b < 28) {
        const int j = b >> 1;
        mbar_expect_tx(bars + sl * 8, 32768);
        tma_2d(ring + sl * 32768, grp ? mu : mg, part * 448 + (j >> 1) * 64, (j & 1) * 256, bars + sl * 8);
    } else {
        const int j = (b - 28) >> 1;
        mbar_expect_tx(bars + sl * 8, 28672);
        tma_2d(ring + sl * 32768, md, ((j >> 1) * 2 + grp) * 64, part * 448 + (j & 1) * 224, bars + sl * 8);
    }
}
__device__ __forceinline__ void mma_2row(float* d, uint32_t a0, uint32_t a2, uint32_t b0, uint32_t b1) {
    asm("mma.sync.aligned.m16n8k16.row.col.f32.bf16.bf16.f32 {%0,%1,%2,%3}, {%4,%5,%6,%5}, {%7,%8}, {%0,%1,%2,%3};"
        : "+f"(d[0]), "+f"(d[1]), "+f"(d[2]), "+f"(d[3]) : "r"(a0), "r"(0u), "r"(a2), "r"(b0), "r"(b1));
}

__device__ void moe_cta(int part, unsigned char* smem, const __nv_bfloat16* __restrict__ x, const CUtensorMap* mg, const CUtensorMap* mu, const CUtensorMap* md) {
    const uint32_t ring = smem_u32(smem), bars = ring + MOE_SLOTS * 32768;
    __nv_bfloat16* xs = (__nv_bfloat16*)(smem + MOE_SLOTS * 32768 + 256);
    float* gu = (float*)(smem + MOE_SLOTS * 32768 + 256 + 2048);
    float* s_v = gu + 4 * 448;
    int* s_i = (int*)(s_v + 16);
    int* s_sel = s_i + 16;
    const int tid = threadIdx.x, warp = __shfl_sync(~0u, tid >> 5, 0), lane = tid & 31;
    if (tid == 0) {
        for (int i = 0; i < MOE_SLOTS; i++) { mbar_init(bars + i * 8, 1); mbar_init(bars + 128 + i * 8, 8); }
        asm volatile("fence.mbarrier_init.release.cluster;" ::: "memory");
        for (int b = 0; b < MOE_SLOTS; b++) moe_load(b, part, ring, bars, mg, mu, md);
    }
    pdl_wait();
    TL(1, 1);
    float rv[4];
    #pragma unroll
    for (int i = 0; i < 4; i++) rv[i] = g_r[tid + i * K2_THREADS];
    for (int pass = 0; pass < 2; pass++) {
        float bv = -INFINITY; int bi = 0x7fffffff;
        const int excl = pass ? s_sel[0] : -1;
        #pragma unroll
        for (int i = 0; i < 4; i++) {
            const int idx = tid + i * K2_THREADS;
            if (idx != excl && (rv[i] > bv || bi == 0x7fffffff)) { bv = rv[i]; bi = idx; }
        }
        #pragma unroll
        for (int o = 16; o; o >>= 1) {
            float ov = __shfl_xor_sync(~0u, bv, o); int oi = __shfl_xor_sync(~0u, bi, o);
            if (ov > bv || (ov == bv && oi < bi)) { bv = ov; bi = oi; }
        }
        if (lane == 0) { s_v[warp] = bv; s_i[warp] = bi; }
        __syncthreads();
        if (warp == 0) {
            bv = lane < 16 ? s_v[lane] : -INFINITY; bi = lane < 16 ? s_i[lane] : 0x7fffffff;
            #pragma unroll
            for (int o = 16; o; o >>= 1) {
                float ov = __shfl_xor_sync(~0u, bv, o); int oi = __shfl_xor_sync(~0u, bi, o);
                if (ov > bv || (ov == bv && oi < bi)) { bv = ov; bi = oi; }
            }
            if (lane == 0) s_sel[pass] = (bi == 0x7fffffff) ? pass : bi;
        }
        __syncthreads();
    }
    for (int i = tid; i < 1024; i += K2_THREADS) {
        const int tok = s_sel[i >> 9];
        const float2 st = g_stats[tok];
        xs[i] = __float2bfloat16_rn(ln_elem(__bfloat162float(x[(size_t)tok * D_ + (i & 511)]), st.x, st.y));
    }
    if (part == 0 && tid < 2) g_sel[tid] = s_sel[tid];
    __syncthreads();
    if (warp == 8) {
        if (lane == 0) {
            for (int b = MOE_SLOTS; b < MOE_BOXES; b++) {
                mbar_wait(bars + 128 + (b % MOE_SLOTS) * 8, (b / MOE_SLOTS - 1) & 1);
                moe_load(b, part, ring, bars, mg, mu, md);
            }
        }
        return;
    }
    if (warp > 8) return;
    const int nj = warp, g = lane >> 2, t = lane & 3;
    const uint32_t* xw = (const uint32_t*)xs + (g & 1) * 256 + t;
    uint32_t a[2][32];
    #pragma unroll
    for (int i = 0; i < 32; i++) { a[0][i] = xw[i * 4]; a[1][i] = xw[128 + i * 4]; }
    #pragma unroll 1
    for (int jp = 0; jp < MOE_BOXES / 4; jp++) {
        const bool down = jp >= 7;
        if (jp == 7) {
            named_bar(1, 256);
            for (int i = tid; i < 896; i += 256) {
                const float gs = bf16r(gu[i]), us = bf16r(gu[896 + i]);
                const float sl_ = bf16r(gs / (1.0f + __expf(-gs)));
                xs[(i / 448) * 512 + (i % 448)] = __float2bfloat16_rn(sl_ * us);
            }
            named_bar(1, 256);
            #pragma unroll
            for (int i = 0; i < 28; i++) { a[0][i] = xw[i * 4]; a[1][i] = xw[112 + i * 4]; }
        }
        float acc[2][4] = {{0.f, 0.f, 0.f, 0.f}, {0.f, 0.f, 0.f, 0.f}}, acb[2][4] = {{0.f, 0.f, 0.f, 0.f}, {0.f, 0.f, 0.f, 0.f}};
        #pragma unroll
        for (int q = 0; q < 4; q++) {
            const int hf = q >> 1, grp = q & 1;
            const int b = jp * 4 + q, sl = b % MOE_SLOTS;
            mbar_wait(bars + sl * 8, (b / MOE_SLOTS) & 1);
            const uint32_t baddr = ring + sl * 32768 + lane * 128 + ((nj ^ (lane & 7)) * 16);
            #pragma unroll
            for (int k4 = 0; k4 < 2; k4++) {
                uint32_t bf[4][4];
                #pragma unroll
                for (int k2 = 0; k2 < 4; k2++)
                    asm volatile("ldmatrix.sync.aligned.m8n8.x4.trans.shared.b16 {%0, %1, %2, %3}, [%4];"
                                 : "=r"(bf[k2][0]), "=r"(bf[k2][1]), "=r"(bf[k2][2]), "=r"(bf[k2][3]) : "r"(baddr + (k4 * 4 + k2) * 4096) : "memory");
                #pragma unroll
                for (int k2 = 0; k2 < 4; k2++) {
                    const int kk = k4 * 4 + k2;
                    if (kk < 7 || !down) {
                        mma_2row(acc[grp], a[hf][4 * kk], a[hf][4 * kk + 1], bf[k2][0], bf[k2][1]);
                        mma_2row(acb[grp], a[hf][4 * kk + 2], a[hf][4 * kk + 3], bf[k2][2], bf[k2][3]);
                    }
                }
            }
            __syncwarp();
            if (lane == 0) mbar_arrive(bars + 128 + sl * 8);
        }
        if (g < 2) {
            #pragma unroll
            for (int grp = 0; grp < 2; grp++) {
                const float2 v = make_float2(acc[grp][0] + acb[grp][0], acc[grp][1] + acb[grp][1]);
                if (!down) *(float2*)&gu[(grp * 2 + g) * 448 + jp * 64 + nj * 8 + t * 2] = v;
                else *(float2*)&g_ypart[part][g][((jp - 7) * 2 + grp) * 64 + nj * 8 + t * 2] = v;
            }
        }
    }
}

__global__ void __launch_bounds__(K2_THREADS, 1)
k2_attn(const __nv_bfloat16* __restrict__ x, const __nv_bfloat16* __restrict__ w_gate, const __nv_bfloat16* __restrict__ w_up,
        const __nv_bfloat16* __restrict__ w_down, const __grid_constant__ CUtensorMap mg, const __grid_constant__ CUtensorMap mu,
        const __grid_constant__ CUtensorMap md) {
    extern __shared__ __align__(1024) unsigned char smem[];
    TL(1, 0);
    pdl_launch();
    if (blockIdx.x >= 128) { moe_cta(blockIdx.x - 128, smem, x, &mg, &mu, &md); TL(1, 2); return; }
    if (threadIdx.x >= 32 && threadIdx.x < 35) {
        const __nv_bfloat16* w = threadIdx.x == 32 ? w_gate : (threadIdx.x == 33 ? w_up : w_down);
        asm volatile("cp.async.bulk.prefetch.L2.global [%0], %1;" :: "l"(w + (size_t)blockIdx.x * (D_ * F_ / 128)), "r"(D_ * F_ / 64) : "memory");
    }
    const uint32_t sK = smem_u32(smem), sV = sK + 65536, sQ = sV + 98304, sBar = sQ + 16384;
    const int h = blockIdx.x >> 2, qb = blockIdx.x & 3;
    const int warp = __shfl_sync(~0u, threadIdx.x >> 5, 0), lane = threadIdx.x & 31, wg = warp >> 2;
    if (threadIdx.x == 0) {
        mbar_init(sBar, 1); mbar_init(sBar + 8, 1);
        asm volatile("fence.mbarrier_init.release.cluster;" ::: "memory");
        mbar_expect_tx(sBar, 8192 + 12288 + 2 * 6144);
        mbar_expect_tx(sBar + 8, 8192 + 53248 + 2 * 26624);
    }
    for (int i = threadIdx.x; i < 2048; i += K2_THREADS)
        *(uint4*)(smem + 65536 + 65536 + i * 16) = make_uint4(0x3F803F80u, 0x3F803F80u, 0x3F803F80u, 0x3F803F80u);
    fence_async_smem();
    __syncthreads();
    if (warp == 0) {
        pdl_wait();
        TL(1, 1);
        const uint4* gk = g_K + (size_t)h * 4096;
        const uint4* gv = g_V + (size_t)h * 4096;
        const uint4* gq = g_Q + (size_t)h * 4096 + qb * 1024;
        if (lane == 0) bulk_g2s(sQ, gq, 8192, sBar);
        if (lane == 1) bulk_g2s(sK, gk, 12288, sBar);
        if (lane == 2) bulk_g2s(sV, gv, 6144, sBar);
        if (lane == 3) bulk_g2s(sV + 32768, gv + 2048, 6144, sBar);
        if (lane == 4) bulk_g2s(sK + 12288, gk + 768, 53248, sBar + 8);
        if (lane == 5) bulk_g2s(sV + 6144, gv + 384, 26624, sBar + 8);
        if (lane == 6) bulk_g2s(sV + 32768 + 6144, gv + 2048 + 384, 26624, sBar + 8);
        if (lane == 7) bulk_g2s(sQ + 8192, gq + 512, 8192, sBar + 8);
        __syncwarp();
    }
    ExpC c;
    {
        const volatile uint32_t* cc = g_const;
        c.one2 = cc[0]; c.ca2 = cc[1];
    }
    const uint64_t kdesc0 = make_desc(sK, 128, 256, 0);
    const uint64_t vdesc0 = make_desc(sV, 128, 32768, 0);
    #pragma unroll 1
    for (int pass = 0; pass < 2; pass++) {
        const bool dry = false;
        if (pass == 0) { mbar_wait(sBar, 0); __syncwarp(); TL(1, 2); }
        const int unit = (pass & 1) * 4 + wg;
        const uint64_t q = make_desc(sQ + unit * 2048, 128, 256, 0);
        float o[12];
        #pragma unroll 1
        for (int attempt = 0; attempt < 2; attempt++) {
            float s0[16], s1[16], s2[16];
            #pragma unroll
            for (int i = 0; i < 16; i++) { s0[i] = 0.f; s1[i] = 0.f; s2[i] = 0.f; }
            float mx0 = -INFINITY, mx1 = -INFINITY;
            if (attempt) {
                #pragma unroll 1
                for (int it = 0; it < 64; it++) {
                    WG_FENCE();
                    wgmma_qk32(s0, q, kdesc0 + it * 64);
                    WG_COMMIT();
                    wg_wait<0>();
                    touch16(s0);
                    max16(s0, mx0, mx1);
                }
            }
            #pragma unroll
            for (int i = 0; i < 12; i++) o[i] = 0.f;
            WG_FENCE();
            wgmma_qk32(s2, q, kdesc0);
            wgmma_qk32(s0, q, kdesc0 + 64);
            wgmma_qk32(s1, q, kdesc0 + 128);
            WG_COMMIT();
            wg_wait<0>();
            touch16(s0); touch16(s1); touch16(s2);
            max16(s0, mx0, mx1); max16(s1, mx0, mx1); max16(s2, mx0, mx1);
            mx0 = fmaxf(mx0, __shfl_xor_sync(~0u, mx0, 1)); mx0 = fmaxf(mx0, __shfl_xor_sync(~0u, mx0, 2));
            mx1 = fmaxf(mx1, __shfl_xor_sync(~0u, mx1, 1)); mx1 = fmaxf(mx1, __shfl_xor_sync(~0u, mx1, 2));
            const float bias = attempt ? 0.0f : 128.0f * 64.0f;
            const float y0 = ceilf(fmaf(mx0, 128.0f * QS * SC100, bias)), y1 = ceilf(fmaf(mx1, 128.0f * QS * SC100, bias));
            c.nm0 = __shfl_sync(~0u, y0 * (-1.0f / 128.0f), lane); c.nm1 = __shfl_sync(~0u, y1 * (-1.0f / 128.0f), lane);
            c.cd0 = __shfl_sync(~0u, __fmul_rn(16256.0f - y0, __int_as_float(1)), lane);
            c.cd1 = __shfl_sync(~0u, __fmul_rn(16256.0f - y1, __int_as_float(1)), lane);
            uint64_t kd = kdesc0 + 192, vd = vdesc0 + 32;
            {
                uint32_t pa[4], pb[4];
                exp_block<12>(s2, pa, c);
                exp_block<14>(s2 + 8, pb, c);
                WG_FENCE();
                wgmma_pv(o, pa, vdesc0); wgmma_pv(o, pb, vdesc0 + 16);
                WG_COMMIT();
            }
            #pragma unroll 1
            for (int seg = 0; seg < (dry ? 1 : 2); seg++) {
            if (seg) { wg_wait<0>(); mbar_wait(sBar + 8, 0); __syncwarp(); }
            #pragma unroll 1
            for (int it = seg ? 3 : (dry ? 2 : 0); it < (seg ? 21 : 3); it++) {
                uint32_t p[6][4];
                WG_FENCE();
                wgmma_qk32(s2, q, kd);
                WG_COMMIT();
                exp_block<0>(s0, p[0], c);
                exp_block<2>(s0 + 8, p[1], c);
                WG_FENCE();
                wgmma_pv(o, p[0], vd); wgmma_pv(o, p[1], vd + 16);
                wgmma_qk32(s0, q, kd + 64);
                WG_COMMIT();
                wg_wait<1>();
                touch16(s2);
                exp_block<4>(s1, p[2], c);
                exp_block<6>(s1 + 8, p[3], c);
                WG_FENCE();
                wgmma_pv(o, p[2], vd + 32); wgmma_pv(o, p[3], vd + 48);
                wgmma_qk32(s1, q, kd + 128);
                WG_COMMIT();
                wg_wait<1>();
                touch16(s0);
                exp_block<8>(s2, p[4], c);
                exp_block<10>(s2 + 8, p[5], c);
                WG_FENCE();
                wgmma_pv(o, p[4], vd + 64); wgmma_pv(o, p[5], vd + 80);
                WG_COMMIT();
                vd += 96; kd += 192;
                wg_wait<1>();
                touch16(s1);
            }
            }
            wg_wait<0>();
            touch12(o);
            if (attempt) break;
            float big = 0.f;
            #pragma unroll
            for (int i = 0; i < 12; i++) big = fmaxf(big, fabsf(o[i]));
            bool bad = !(big < 1e30f);
            #pragma unroll
            for (int i = 0; i < 12; i++) bad |= (o[i] != o[i]);
            uint32_t any;
            asm volatile("{.reg .pred p, q; setp.ne.u32 p, %1, 0; barrier.cta.red.or.pred.aligned q, %2, 128, p; selp.u32 %0, 1, 0, q;}"
                         : "=r"(any) : "r"((uint32_t)bad), "r"(1 + wg) : "memory");
            if (dry || !__any_sync(~0u, any)) break;
        }
        const int g = lane >> 2, t = lane & 3;
        const int r = (warp & 3) * 16 + g;
        const float i0 = __fdiv_rn(1.0f, o[8]), i1 = __fdiv_rn(1.0f, o[10]);
        uint32_t* ob = (uint32_t*)(g_O + (size_t)(qb * 8 + unit) * 4096 + (h >> 2) * 512 + r * 8) + t;
        const int c0 = ((h & 3) * 2) ^ (r & 7), c1 = ((h & 3) * 2 + 1) ^ (r & 7);
        if (!dry) {
            ob[c0 * 4] = pack_bf16(o[0] * i0, o[1] * i0);
            ob[c1 * 4] = pack_bf16(o[4] * i0, o[5] * i0);
            ob[256 + c0 * 4] = pack_bf16(o[2] * i1, o[3] * i1);
            ob[256 + c1 * 4] = pack_bf16(o[6] * i1, o[7] * i1);
            TL(1, 3 + pass);
        }
    }
}

constexpr int K3_THREADS = 256;
constexpr int K3_SMEM = 65536 + 131072 + 128;

__global__ void __launch_bounds__(K3_THREADS, 1)
k3_out(const __grid_constant__ CUtensorMap wmap, const __nv_bfloat16* __restrict__ x, __nv_bfloat16* __restrict__ out) {
    extern __shared__ __align__(1024) unsigned char smem[];
    const uint32_t sA = smem_u32(smem), sB = sA + 65536, sBar = sB + 131072;
    const int warp = __shfl_sync(~0u, threadIdx.x >> 5, 0), lane = threadIdx.x & 31, wg = warp >> 2;
    const int nt = blockIdx.x & 3, mt = blockIdx.x >> 2;
    TL(2, 0);
    if (threadIdx.x == 0) {
        for (int i = 0; i < 10; i++) mbar_init(sBar + i * 8, 1);
        asm volatile("fence.mbarrier_init.release.cluster;" ::: "memory");
        for (int i = 0; i < 8; i++) mbar_expect_tx(sBar + 16 + i * 8, 8192);
        for (int kh = 0; kh < 2; kh++) {
            mbar_expect_tx(sBar + kh * 8, 65536);
            tma_2d(sB + kh * 32768, &wmap, nt * 128, kh * 256, sBar + kh * 8);
            tma_2d(sB + 65536 + kh * 32768, &wmap, nt * 128 + 64, kh * 256, sBar + kh * 8);
        }
    }
    const int er = threadIdx.x >> 2, ec = (threadIdx.x & 3) * 32;
    const int row = mt * 64 + er;
    uint4 xv[4];
    #pragma unroll
    for (int j = 0; j < 4; j++) xv[j] = __ldg((const uint4*)(x + (size_t)row * D_ + nt * 128 + ec) + j);
    __syncthreads();
    pdl_wait();
    TL(2, 1);
    if (threadIdx.x < 8) bulk_g2s(sA + threadIdx.x * 8192, g_O + (size_t)mt * 4096 + threadIdx.x * 512, 8192, sBar + 16 + threadIdx.x * 8);
    const int sel0 = g_sel[0], sel1 = g_sel[1];
    const float2 st = g_stats[row];
    uint32_t bb[16];
    {
        const uint32_t xu[16] = {xv[0].x, xv[0].y, xv[0].z, xv[0].w, xv[1].x, xv[1].y, xv[1].z, xv[1].w,
                                 xv[2].x, xv[2].y, xv[2].z, xv[2].w, xv[3].x, xv[3].y, xv[3].z, xv[3].w};
        #pragma unroll
        for (int j = 0; j < 16; j++) bb[j] = pack_bf16(bf16r(bf_lo(xu[j]) - st.x) * st.y, bf16r(bf_hi(xu[j]) - st.x) * st.y);
        const int slot = row == sel0 ? 0 : (row == sel1 ? 1 : -1);
        if (slot >= 0) {
            const float gate = bf16r(1.0f / (1.0f + __expf(-g_r[row])));
            const int c0 = nt * 128 + ec;
            #pragma unroll
            for (int j = 0; j < 16; j++) {
                const float2 a = *(const float2*)&g_ypart[0][slot][c0 + 2 * j], b = *(const float2*)&g_ypart[1][slot][c0 + 2 * j];
                const float2 c = *(const float2*)&g_ypart[2][slot][c0 + 2 * j], d = *(const float2*)&g_ypart[3][slot][c0 + 2 * j];
                bb[j] = pack_bf16(bf_lo(bb[j]) + bf16r(bf16r(a.x + b.x + c.x + d.x) * gate), bf_hi(bb[j]) + bf16r(bf16r(a.y + b.y + c.y + d.y) * gate));
            }
        }
    }
    float acc[32];
    #pragma unroll
    for (int i = 0; i < 32; i++) acc[i] = 0.f;
    const uint64_t da0 = make_desc(sA, 16, 1024, 1);
    const uint64_t db0 = make_desc(sB + wg * 65536, 8192, 1024, 1);
    #pragma unroll 1
    for (int q = 0; q < 8; q++) {
        if ((q & 3) == 0) mbar_wait(sBar + (q >> 2) * 8, 0);
        mbar_wait(sBar + 16 + q * 8, 0);
        WG_FENCE();
        #pragma unroll
        for (int kk = 0; kk < 4; kk++)
            wgmma_n64(acc, da0 + (uint64_t)(q * 512 + kk * 2), db0 + (uint64_t)(q * 512 + kk * 128));
        WG_COMMIT();
    }
    wg_wait<0>();
    touch32(acc);
    TL(2, 2);
    __syncthreads();
    {
        const int g = lane >> 2, t = lane & 3;
        unsigned char* sp = smem + ((warp & 3) * 16 + g) * 272 + wg * 128 + t * 4;
        #pragma unroll
        for (int j = 0; j < 8; j++) {
            *(uint32_t*)(sp + j * 16) = pack_bf16(acc[4 * j], acc[4 * j + 1]);
            *(uint32_t*)(sp + 8 * 272 + j * 16) = pack_bf16(acc[4 * j + 2], acc[4 * j + 3]);
        }
    }
    __syncthreads();
    #pragma unroll
    for (int j = 0; j < 4; j++) {
        const uint4 av = *(const uint4*)(smem + er * 272 + ec * 2 + j * 16);
        const uint32_t au[4] = {av.x, av.y, av.z, av.w}, xu[4] = {xv[j].x, xv[j].y, xv[j].z, xv[j].w};
        uint32_t o[4];
        #pragma unroll
        for (int i = 0; i < 4; i++) {
            uint32_t t2;
            asm("add.rn.bf16x2 %0, %1, %2;" : "=r"(t2) : "r"(xu[i]), "r"(au[i]));
            asm("add.rn.bf16x2 %0, %1, %2;" : "=r"(o[i]) : "r"(t2), "r"(bb[j * 4 + i]));
        }
        *((uint4*)(out + (size_t)row * D_ + nt * 128 + ec) + j) = make_uint4(o[0], o[1], o[2], o[3]);
    }
    TL(2, 3);
}

typedef CUresult (*EncodeFn)(CUtensorMap*, CUtensorMapDataType, cuuint32_t, void*, const cuuint64_t*, const cuuint64_t*,
                             const cuuint32_t*, const cuuint32_t*, CUtensorMapInterleave, CUtensorMapSwizzle,
                             CUtensorMapL2promotion, CUtensorMapFloatOOBfill);

void make_wmap(EncodeFn fn, CUtensorMap* map, const void* ptr, int rows, int cols, int box_rows) {
    cuuint64_t dims[2] = {(cuuint64_t)cols, (cuuint64_t)rows};
    cuuint64_t strides[1] = {(cuuint64_t)cols * 2};
    cuuint32_t box[2] = {64, (cuuint32_t)box_rows};
    cuuint32_t es[2] = {1, 1};
    fn(map, CU_TENSOR_MAP_DATA_TYPE_BFLOAT16, 2, (void*)ptr, dims, strides, box, es, CU_TENSOR_MAP_INTERLEAVE_NONE,
       CU_TENSOR_MAP_SWIZZLE_128B, CU_TENSOR_MAP_L2_PROMOTION_L2_256B, CU_TENSOR_MAP_FLOAT_OOB_FILL_NONE);
}

}

extern "C" void kernel_launch(void* const* d_in, const int* in_sizes, int n_in, void* d_out, int out_size) {
    const __nv_bfloat16* x = (const __nv_bfloat16*)d_in[0];
    const __nv_bfloat16* wqkv = (const __nv_bfloat16*)d_in[1];
    const __nv_bfloat16* wo = (const __nv_bfloat16*)d_in[2];
    const __nv_bfloat16* w_r = (const __nv_bfloat16*)d_in[4];
    const __nv_bfloat16* w_gate = (const __nv_bfloat16*)d_in[5];
    const __nv_bfloat16* w_up = (const __nv_bfloat16*)d_in[6];
    const __nv_bfloat16* w_down = (const __nv_bfloat16*)d_in[7];
    __nv_bfloat16* out = (__nv_bfloat16*)d_out;

    static EncodeFn encode = nullptr;
    if (!encode) {
        void* fn = nullptr;
        cudaDriverEntryPointQueryResult qres;
        cudaGetDriverEntryPoint("cuTensorMapEncodeTiled", &fn, cudaEnableDefault, &qres);
        encode = (EncodeFn)fn;
        cudaFuncSetAttribute(k1_ln_qkv, cudaFuncAttributeMaxDynamicSharedMemorySize, K1_SMEM);
        cudaFuncSetAttribute(k2_attn, cudaFuncAttributeMaxDynamicSharedMemorySize, K2_SMEM);
        cudaFuncSetAttribute(k3_out, cudaFuncAttributeMaxDynamicSharedMemorySize, K3_SMEM);
    }
    CUtensorMap map_qkv, map_wo, map_x, map_g, map_u, map_d;
    make_wmap(encode, &map_g, w_gate, D_, F_, 256);
    make_wmap(encode, &map_u, w_up, D_, F_, 256);
    make_wmap(encode, &map_d, w_down, F_, D_, 224);
    make_wmap(encode, &map_x, x, S_, D_, 64);
    make_wmap(encode, &map_qkv, wqkv, D_, 3 * D_, 64);
    make_wmap(encode, &map_wo, wo, D_, D_, 256);

    k1_ln_qkv<<<128, K1_THREADS, K1_SMEM, cudaStreamPerThread>>>(map_qkv, map_x, w_r);
    cudaLaunchAttribute at[1];
    at[0].id = cudaLaunchAttributeProgrammaticStreamSerialization;
    at[0].val.programmaticStreamSerializationAllowed = 1;
    cudaLaunchConfig_t cfg = {};
    cfg.stream = cudaStreamPerThread;
    cfg.attrs = at; cfg.numAttrs = 1;
    cfg.gridDim = dim3(132); cfg.blockDim = dim3(K2_THREADS); cfg.dynamicSmemBytes = K2_SMEM;
    cudaLaunchKernelEx(&cfg, k2_attn, x, w_gate, w_up, w_down, map_g, map_u, map_d);
    cfg.gridDim = dim3(128); cfg.blockDim = dim3(K3_THREADS); cfg.dynamicSmemBytes = K3_SMEM;
    cudaLaunchKernelEx(&cfg, k3_out, map_wo, x, out);
}
```

```cpp
#include <cuda_runtime.h>
#include <cuda_bf16.h>
#include <cuda.h>
#include <stdint.h>

namespace {

constexpr int S_ = 2048, D_ = 512, H_ = 32, F_ = 1792;

constexpr uint32_t PMASK = 0xDB6;

__device__ __align__(1024) uint4 g_QKV[3 * H_ * S_ * 2];
#define g_Q (g_QKV)
#define g_K (g_QKV + H_ * S_ * 2)
#define g_V (g_QKV + 2 * H_ * S_ * 2)
__device__ __align__(1024) uint4 g_O[S_ * D_ / 8];
__device__ float2 g_stats[S_];
__device__ uint32_t g_const[2] = {0x3F803F80u, 0x42294229u};
__device__ float g_r[S_];
__device__ __align__(16) float g_ypart[4][2][D_];
__device__ int g_sel[2];

#define TL(k, p)
#define CK(i)
__device__ __forceinline__ uint32_t smem_u32(const void* p) { return (uint32_t)__cvta_generic_to_shared(p); }
__device__ __forceinline__ float bf16r(float x) { return __bfloat162float(__float2bfloat16_rn(x)); }
__device__ __forceinline__ uint32_t pack_bf16(float lo, float hi) {
    uint32_t r; asm("cvt.rn.bf16x2.f32 %0, %1, %2;" : "=r"(r) : "f"(hi), "f"(lo)); return r;
}
__device__ __forceinline__ float bf_lo(uint32_t u) { return __uint_as_float(u << 16); }
__device__ __forceinline__ float bf_hi(uint32_t u) { return __uint_as_float(u & 0xFFFF0000u); }
__device__ __forceinline__ float ex2(float x) { float y; asm("ex2.approx.ftz.f32 %0, %1;" : "=f"(y) : "f"(x)); return y; }

__device__ __forceinline__ void mbar_init(uint32_t bar, uint32_t count) {
    asm volatile("mbarrier.init.shared::cta.b64 [%0], %1;" :: "r"(bar), "r"(count) : "memory");
}
__device__ __forceinline__ void mbar_expect_tx(uint32_t bar, uint32_t bytes) {
    asm volatile("mbarrier.arrive.expect_tx.shared::cta.b64 _, [%0], %1;" :: "r"(bar), "r"(bytes) : "memory");
}
__device__ __forceinline__ void mbar_arrive(uint32_t bar) {
    asm volatile("mbarrier.arrive.shared::cta.b64 _, [%0];" :: "r"(bar) : "memory");
}
__device__ __forceinline__ void mbar_wait(uint32_t bar, uint32_t parity) {
    uint32_t done;
    #pragma unroll 1
    for (int it = 0; it < (1 << 26); it++) {
        asm volatile("{.reg .pred p; mbarrier.try_wait.parity.shared::cta.b64 p, [%1], %2; selp.u32 %0, 1, 0, p;}"
                     : "=r"(done) : "r"(bar), "r"(parity) : "memory");
        if (done) return;
    }
    __trap();
}
__device__ __forceinline__ void bulk_g2s(uint32_t dst, const void* src, uint32_t bytes, uint32_t bar) {
    asm volatile("cp.async.bulk.shared::cluster.global.mbarrier::complete_tx::bytes [%0], [%1], %2, [%3];"
                 :: "r"(dst), "l"(src), "r"(bytes), "r"(bar) : "memory");
}
__device__ __forceinline__ void tma_2d(uint32_t dst, const CUtensorMap* map, int c0, int c1, uint32_t bar) {
    asm volatile("cp.async.bulk.tensor.2d.shared::cluster.global.mbarrier::complete_tx::bytes [%0], [%1, {%3, %4}], [%2];"
                 :: "r"(dst), "l"(map), "r"(bar), "r"(c0), "r"(c1) : "memory");
}
__device__ __forceinline__ void fence_async_smem() { asm volatile("fence.proxy.async.shared::cta;" ::: "memory"); }
__device__ __forceinline__ void named_bar(int id, int n) { asm volatile("bar.sync %0, %1;" :: "r"(id), "r"(n) : "memory"); }

__device__ __forceinline__ uint64_t make_desc(uint32_t saddr, uint32_t lbo, uint32_t sbo, uint32_t swz) {
    return (uint64_t)((saddr & 0x3FFFF) >> 4) | ((uint64_t)(lbo >> 4) << 16) | ((uint64_t)(sbo >> 4) << 32) | ((uint64_t)swz << 62);
}
#define WG_FENCE() asm volatile("wgmma.fence.sync.aligned;" ::: "memory")
#define WG_COMMIT() asm volatile("wgmma.commit_group.sync.aligned;" ::: "memory")
template <int N> __device__ __forceinline__ void wg_wait() { asm volatile("wgmma.wait_group.sync.aligned %0;" :: "n"(N) : "memory"); }

#define F4(d, o) "+f"(d[o]), "+f"(d[o + 1]), "+f"(d[o + 2]), "+f"(d[o + 3])
#define F16(d, o) F4(d, o), F4(d, o + 4), F4(d, o + 8), F4(d, o + 12)
#define F32(d, o) F16(d, o), F16(d, o + 16)

__device__ __forceinline__ void wgmma_rs_n192(float* d, const uint32_t* a, uint64_t db) {
    asm volatile("wgmma.mma_async.sync.aligned.m64n192k16.f32.bf16.bf16 "
        "{%0,%1,%2,%3,%4,%5,%6,%7,%8,%9,%10,%11,%12,%13,%14,%15,%16,%17,%18,%19,%20,%21,%22,%23,%24,%25,%26,%27,%28,%29,%30,%31,"
        "%32,%33,%34,%35,%36,%37,%38,%39,%40,%41,%42,%43,%44,%45,%46,%47,%48,%49,%50,%51,%52,%53,%54,%55,%56,%57,%58,%59,%60,%61,%62,%63,"
        "%64,%65,%66,%67,%68,%69,%70,%71,%72,%73,%74,%75,%76,%77,%78,%79,%80,%81,%82,%83,%84,%85,%86,%87,%88,%89,%90,%91,%92,%93,%94,%95}, "
        "{%96,%97,%98,%99}, %100, 1, 1, 1, 1;\n"
        : F32(d, 0), F32(d, 32), F32(d, 64) : "r"(a[0]), "r"(a[1]), "r"(a[2]), "r"(a[3]), "l"(db));
}
__device__ __forceinline__ void wgmma_n64(float* d, uint64_t da, uint64_t db) {
    asm volatile("wgmma.mma_async.sync.aligned.m64n64k16.f32.bf16.bf16 "
        "{%0,%1,%2,%3,%4,%5,%6,%7,%8,%9,%10,%11,%12,%13,%14,%15,%16,%17,%18,%19,%20,%21,%22,%23,%24,%25,%26,%27,%28,%29,%30,%31}, "
        "%32, %33, 1, 1, 1, 0, 1;\n"
        : F32(d, 0) : "l"(da), "l"(db));
}
__device__ __forceinline__ void wgmma_qk32(float* d, uint64_t qd, uint64_t kd) {
    asm volatile("wgmma.mma_async.sync.aligned.m64n32k16.f32.bf16.bf16 {%0,%1,%2,%3,%4,%5,%6,%7,%8,%9,%10,%11,%12,%13,%14,%15}, %16, %17, 0, 1, 1, 0, 0;\n"
        : F16(d, 0) : "l"(qd), "l"(kd));
}
__device__ __forceinline__ void wgmma_pv(float* d, const uint32_t* a, uint64_t vd) {
    asm volatile("wgmma.mma_async.sync.aligned.m64n24k16.f32.bf16.bf16 {%0,%1,%2,%3,%4,%5,%6,%7,%8,%9,%10,%11}, {%12,%13,%14,%15}, %16, 1, 1, 1, 1;\n"
        : F4(d, 0), F4(d, 4), F4(d, 8) : "r"(a[0]), "r"(a[1]), "r"(a[2]), "r"(a[3]), "l"(vd));
}
__device__ __forceinline__ void touch16(float* d) { asm volatile("" : F16(d, 0) :: "memory"); }
__device__ __forceinline__ void touch12(float* d) { asm volatile("" : F4(d, 0), F4(d, 4), F4(d, 8) :: "memory"); }
__device__ __forceinline__ void touch32(float* d) { asm volatile("" : F32(d, 0) :: "memory"); }
__device__ __forceinline__ void touch96(float* d) { asm volatile("" : F32(d, 0), F32(d, 32), F32(d, 64) :: "memory"); }

__device__ __forceinline__ float ln_elem(float x, float mean_b, float rden) {
    return bf16r(bf16r(x - mean_b) * rden);
}
__device__ __forceinline__ void pdl_wait() { asm volatile("griddepcontrol.wait;" ::: "memory"); }
__device__ __forceinline__ void pdl_launch() { asm volatile("griddepcontrol.launch_dependents;" ::: "memory"); }
__device__ __forceinline__ void cluster_arrive() { asm volatile("barrier.cluster.arrive.release.aligned;" ::: "memory"); }
__device__ __forceinline__ void cluster_wait() { asm volatile("barrier.cluster.wait.acquire.aligned;" ::: "memory"); }

constexpr int K1_THREADS = 288;
constexpr int K1_SMEM = 131072 + 6 * 16384 + 256 + 1024;

__device__ __forceinline__ void ldsm4(uint32_t* r, uint32_t addr) {
    asm volatile("ldmatrix.sync.aligned.m8n8.x4.shared.b16 {%0, %1, %2, %3}, [%4];" : "=r"(r[0]), "=r"(r[1]), "=r"(r[2]), "=r"(r[3]) : "r"(addr) : "memory");
}
__device__ __forceinline__ void stsm4(uint32_t addr, uint32_t r0, uint32_t r1, uint32_t r2, uint32_t r3) {
    asm volatile("stmatrix.sync.aligned.m8n8.x4.shared.b16 [%0], {%1, %2, %3, %4};" :: "r"(addr), "r"(r0), "r"(r1), "r"(r2), "r"(r3) : "memory");
}
__device__ __forceinline__ void mma16816(float* d, const uint32_t* a, uint32_t b0, uint32_t b1) {
    asm("mma.sync.aligned.m16n8k16.row.col.f32.bf16.bf16.f32 {%0,%1,%2,%3}, {%4,%5,%6,%7}, {%8,%9}, {%0,%1,%2,%3};"
        : "+f"(d[0]), "+f"(d[1]), "+f"(d[2]), "+f"(d[3]) : "r"(a[0]), "r"(a[1]), "r"(a[2]), "r"(a[3]), "r"(b0), "r"(b1));
}
__device__ __forceinline__ uint32_t sub_bf16x2(uint32_t a, uint32_t b) {
    uint32_t d; asm("sub.rn.bf16x2 %0, %1, %2;" : "=r"(d) : "r"(a), "r"(b)); return d;
}
__device__ __forceinline__ uint32_t ln_pair(uint32_t x2, uint32_t mean2, uint32_t rhi2, uint32_t rlo2) {
    const uint32_t d = sub_bf16x2(x2, mean2);
    uint32_t t, y;
    asm("mul.rn.bf16x2 %0, %1, %2;" : "=r"(t) : "r"(d), "r"(rlo2));
    asm("fma.rn.bf16x2 %0, %1, %2, %3;" : "=r"(y) : "r"(d), "r"(rhi2), "r"(t));
    return y;
}
struct LnRow { uint32_t m2, hi2, lo2; };
__device__ __forceinline__ LnRow ln_row(float mean, float rden) {
    LnRow r;
    r.m2 = pack_bf16(mean, mean);
    r.hi2 = pack_bf16(rden, rden);
    const float lo = rden - bf_lo(r.hi2);
    r.lo2 = pack_bf16(lo, lo);
    return r;
}
__device__ __forceinline__ void ln_frag(uint32_t* a, const LnRow& r0, const LnRow& r1) {
    a[0] = ln_pair(a[0], r0.m2, r0.hi2, r0.lo2); a[1] = ln_pair(a[1], r1.m2, r1.hi2, r1.lo2);
    a[2] = ln_pair(a[2], r0.m2, r0.hi2, r0.lo2); a[3] = ln_pair(a[3], r1.m2, r1.hi2, r1.lo2);
}

template <int NJ>
__device__ __forceinline__ void k1_store(const float* acc, int jj0, uint32_t stage, int nt, int mt, int wg, int w4, int lane) {
    const int mi = lane >> 3, lr = lane & 7;
    const uint32_t off_qk = stage + (w4 * 2 + (mi & 1)) * 256 + (mi >> 1) * 128 + lr * 16;
    const uint32_t off_v = stage + (mi >> 1) * 1024 + (w4 * 16 + (mi & 1) * 8 + lr) * 16;
    #pragma unroll
    for (int jj = 0; jj < NJ; jj++) {
        const bool isv = nt * 12 + jj0 + jj >= 64;
        const float m = isv ? 1.0f : 8.8817841970012523e-16f;
        stsm4((isv ? off_v : off_qk) + jj * 2048,
              pack_bf16(acc[8 * jj] * m, acc[8 * jj + 1] * m), pack_bf16(acc[8 * jj + 2] * m, acc[8 * jj + 3] * m),
              pack_bf16(acc[8 * jj + 4] * m, acc[8 * jj + 5] * m), pack_bf16(acc[8 * jj + 6] * m, acc[8 * jj + 7] * m));
    }
    fence_async_smem();
    named_bar(1 + wg, 128);
    if (lane < NJ / 2) {
        const int pc = w4 * (NJ / 2) + lane, jj = pc >> 1, hf = pc & 1, hg = nt * 12 + jj0 + jj;
        const unsigned char* dst = (const unsigned char*)g_QKV + (size_t)hg * 65536
            + (hg >= 64 ? hf * 32768 + (mt * 128 + wg * 64) * 16 : (mt * 16 + wg * 8) * 256 + hf * 1024);
        asm volatile("cp.async.bulk.global.shared::cta.bulk_group [%0], [%1], 1024;" :: "l"(dst), "r"(stage + pc * 1024) : "memory");
        asm volatile("cp.async.bulk.commit_group;" ::: "memory");
    }
}

__global__ void __launch_bounds__(K1_THREADS, 1)
k1_ln_qkv(const __grid_constant__ CUtensorMap wmap, const __grid_constant__ CUtensorMap xmap, const __nv_bfloat16* __restrict__ w_r) {
    extern __shared__ __align__(1024) unsigned char smem[];
    const uint32_t sA = smem_u32(smem), sB = sA + 131072, sBar = sB + 4 * 24576;
    const int warp = __shfl_sync(~0u, threadIdx.x >> 5, 0), lane = threadIdx.x & 31;
    const int nt = blockIdx.x & 7, mt = blockIdx.x >> 3;
    const int wg = warp >> 2;
    CK(0);
    pdl_launch();
    uint32_t* s_wr = (uint32_t*)(smem + 131072 + 4 * 24576 + 256);
    if (warp == 8) {
        if (lane == 0) {
            for (int i = 0; i < 4; i++) { mbar_init(sBar + i * 8, 1); mbar_init(sBar + 48 + i * 8, 2); }
            asm volatile("fence.mbarrier_init.release.cluster;" ::: "memory");
            for (int i = 0; i < 4; i++) mbar_expect_tx(sBar + i * 8, 24576);
        }
        if (lane < 4) {
            mbar_init(sBar + 96 + lane * 8, 1);
            asm volatile("fence.mbarrier_init.release.cluster;" ::: "memory");
            mbar_expect_tx(sBar + 96 + lane * 8, 32768);
        }
        __syncwarp();
        if (lane < 16) {
            const int pn = (lane >> 3) * 4 + (lane & 3), hf = (lane >> 2) & 1;
            tma_2d(sA + pn * 16384 + hf * 8192, &xmap, pn * 64, mt * 128 + hf * 64, sBar + 96 + (lane >> 2) * 8);
        }
        named_bar(3, K1_THREADS);
        mbar_wait(sBar + 96 + 8, 0);
        if (lane < 12) {
            const int ld = lane / 3, j = lane % 3;
            tma_2d(sB + ld * 24576 + j * 8192, &wmap, nt * 192 + j * 64, ld * 64, sBar + ld * 8);
        }
        __syncwarp();
        if (lane < 3) {
            for (int ld = 4; ld < 8; ld++) {
                const int sl = ld - 4;
                mbar_wait(sBar + 48 + sl * 8, 0);
                if (lane == 0) mbar_expect_tx(sBar + sl * 8, 24576);
                __syncwarp(7);
                tma_2d(sB + sl * 24576 + lane * 8192, &wmap, nt * 192 + lane * 64, ld * 64, sBar + sl * 8);
            }
        }
        return;
    }
    if (nt == 0) s_wr[threadIdx.x] = __ldg((const uint32_t*)w_r + threadIdx.x);
    named_bar(3, K1_THREADS);
    const int g = lane >> 2, t = lane & 3;
    const int lrow = warp * 16 + (lane & 7) + ((lane >> 3) & 1) * 8;
    const uint32_t lbase = sA + lrow * 128;
    const int lsw = lane & 7, lhi = lane >> 4;
    uint32_t laddr[4];
    #pragma unroll
    for (int k4 = 0; k4 < 4; k4++) laddr[k4] = lbase + (((k4 * 2 + lhi) ^ lsw) * 16);
    CK(1);
    float dsum[4] = {0.f, 0.f, 0.f, 0.f}, dq0[4] = {0.f, 0.f, 0.f, 0.f}, dq1[4] = {0.f, 0.f, 0.f, 0.f};
    float esum[4] = {0.f, 0.f, 0.f, 0.f}, eq0[4] = {0.f, 0.f, 0.f, 0.f}, eq1[4] = {0.f, 0.f, 0.f, 0.f};
    #pragma unroll 2
    for (int pn = 0; pn < 8; pn++) {
        uint32_t a[4][4];
        if ((pn & 3) == 0) mbar_wait(sBar + 96 + ((pn >> 2) * 2 + wg) * 8, 0);
        #pragma unroll
        for (int k4 = 0; k4 < 4; k4++) ldsm4(a[k4], laddr[k4] + pn * 16384);
        #pragma unroll
        for (int k4 = 0; k4 < 4; k4 += 2) {
            mma16816(dsum, a[k4], 0x3F803F80u, 0x3F803F80u);
            mma16816(dq0, a[k4], a[k4][0], a[k4][2]);
            mma16816(dq1, a[k4], a[k4][1], a[k4][3]);
            mma16816(esum, a[k4 + 1], 0x3F803F80u, 0x3F803F80u);
            mma16816(eq0, a[k4 + 1], a[k4 + 1][0], a[k4 + 1][2]);
            mma16816(eq1, a[k4 + 1], a[k4 + 1][1], a[k4 + 1][3]);
        }
    }
    #pragma unroll
    for (int i = 0; i < 4; i++) { dsum[i] += esum[i]; dq0[i] += eq0[i]; dq1[i] += eq1[i]; }
    CK(3);
    const int dsrc = g * 4 + (g >> 1);
    const float sq0 = __shfl_sync(~0u, (g & 1) ? dq0[1] : dq0[0], dsrc), sq1 = __shfl_sync(~0u, (g & 1) ? dq1[3] : dq1[2], dsrc);
    const float mean0 = dsum[0] * (1.0f / D_), mean1 = dsum[2] * (1.0f / D_);
    float var0 = fmaf(-mean0, mean0, sq0 * (1.0f / D_)), var1 = fmaf(-mean1, mean1, sq1 * (1.0f / D_));
    if (__any_sync(~0u, !(mean0 * mean0 <= 16.0f * var0) || !(mean1 * mean1 <= 16.0f * var1))) {
        float q0 = 0.f, q1 = 0.f;
        #pragma unroll 1
        for (int ks = 0; ks < 32; ks++) {
            uint32_t a[4];
            ldsm4(a, lbase + (ks >> 2) * 16384 + ((((ks & 3) * 2 + lhi) ^ lsw) * 16));
            #pragma unroll
            for (int i = 0; i < 4; i++) {
                const float m = (i & 1) ? mean1 : mean0;
                const float d0 = bf_lo(a[i]) - m, d1 = bf_hi(a[i]) - m;
                if (i & 1) q1 = fmaf(d0, d0, fmaf(d1, d1, q1)); else q0 = fmaf(d0, d0, fmaf(d1, d1, q0));
            }
        }
        q0 += __shfl_xor_sync(~0u, q0, 1); q0 += __shfl_xor_sync(~0u, q0, 2);
        q1 += __shfl_xor_sync(~0u, q1, 1); q1 += __shfl_xor_sync(~0u, q1, 2);
        var0 = q0 * (1.0f / D_); var1 = q1 * (1.0f / D_);
    }
    const float rs0 = __frcp_rn(bf16r(__fsqrt_rn(bf16r(bf16r(var0) + 1e-5f))));
    const float rs1 = __frcp_rn(bf16r(__fsqrt_rn(bf16r(bf16r(var1) + 1e-5f))));
    const LnRow lr0 = ln_row(mean0, rs0), lr1 = ln_row(mean1, rs1);
    float acc[96];
    #pragma unroll
    for (int i = 0; i < 96; i++) acc[i] = 0.f;
    float dr[4] = {0.f, 0.f, 0.f, 0.f};
    const uint64_t db0 = make_desc(sB, 8192, 1024, 1);
    uint32_t a[2][4][4];
    #pragma unroll
    for (int k4 = 0; k4 < 4; k4++) ldsm4(a[0][k4], laddr[k4]);
    #pragma unroll
    for (int k4 = 0; k4 < 4; k4++) ln_frag(a[0][k4], lr0, lr1);
    #pragma unroll 1
    for (int kc = 0; kc < 8; kc += 2) {
        #pragma unroll
        for (int h2 = 0; h2 < 2; h2++) {
            const int ld = kc + h2, sl = ld & 3;
            mbar_wait(sBar + sl * 8, ld >> 2);
            WG_FENCE();
            #pragma unroll
            for (int k4 = 0; k4 < 4; k4++) wgmma_rs_n192(acc, a[h2][k4], db0 + (uint64_t)(sl * 1536 + k4 * 128));
            WG_COMMIT();
            if (nt == 0) {
                #pragma unroll
                for (int k4 = 0; k4 < 4; k4++) mma16816(dr, a[h2][k4], s_wr[(ld * 4 + k4) * 8 + t], s_wr[(ld * 4 + k4) * 8 + 4 + t]);
            }
            wg_wait<1>();
            if (ld >= 1 && ld <= 4 && (threadIdx.x & 127) == 0) mbar_arrive(sBar + 48 + (ld - 1) * 8);
            #pragma unroll
            for (int k4 = 0; k4 < 4; k4++) ldsm4(a[h2 ^ 1][k4], laddr[k4] + ((ld + 1) & 7) * 16384);
            #pragma unroll
            for (int k4 = 0; k4 < 4; k4++) ln_frag(a[h2 ^ 1][k4], lr0, lr1);
        }
    }
    const int row0 = mt * 128 + warp * 16;
    if (nt == 0 && t == 0) {
        g_r[row0 + g] = bf16r(dr[0]); g_r[row0 + g + 8] = bf16r(dr[2]);
        g_stats[row0 + g] = make_float2(bf_lo(lr0.m2), rs0); g_stats[row0 + g + 8] = make_float2(bf_lo(lr1.m2), rs1);
    }
    wg_wait<0>();
    touch96(acc);
    CK(4);
    named_bar(1 + wg, 128);
    k1_store<4>(acc, 0, sA + wg * 8192, nt, mt, wg, warp & 3, lane);
    k1_store<4>(acc + 32, 4, sA + 16384 + wg * 8192, nt, mt, wg, warp & 3, lane);
    k1_store<4>(acc + 64, 8, sA + 32768 + wg * 8192, nt, mt, wg, warp & 3, lane);
    CK(5);
    asm volatile("cp.async.bulk.wait_group.read 0;" ::: "memory");
    CK(6);
}

constexpr int K2_THREADS = 512;
constexpr int K2_SMEM = 6 * 32768 + 12288;

constexpr float QS = 0.25f * 1.4426950408889634f;
constexpr float SC100 = 1.2676506002282294e30f;
__device__ __forceinline__ uint32_t polyexp2(float s0, float s1, float cd, uint32_t one2, uint32_t ca2) {
    constexpr float A = 128.0f * QS * 1.7763568394002505e-15f;
    float t0, t1;
    asm("fma.rn.f32 %0, %1, %2, %3;" : "=f"(t0) : "f"(s0), "f"(A), "f"(cd));
    asm("fma.rn.f32 %0, %1, %2, %3;" : "=f"(t1) : "f"(s1), "f"(A), "f"(cd));
    uint32_t W, U, h, G;
    asm("cvt.pack.sat.s16.s32 %0, %1, %2;" : "=r"(W) : "r"(__float_as_int(t1)), "r"(__float_as_int(t0)));
    asm("lop3.b32 %0, %1, 0x007F007F, %2, 0xEA;" : "=r"(U) : "r"(W), "r"(one2));
    asm("fma.rn.bf16x2 %0, %1, %2, %3;" : "=r"(h) : "r"(U), "r"(ca2), "r"(0xC300C300u));
    asm("fma.rn.bf16x2 %0, %1, %2, %3;" : "=r"(G) : "r"(h), "r"(U), "r"(0x438B438Bu));
    return W + G - 0x43404340u;
}

struct ExpC { float nm0, nm1, cd0, cd1; uint32_t one2, ca2; };

template <int G>
__device__ __forceinline__ void exp_block(const float* s, uint32_t* p, const ExpC& c) {
    #pragma unroll
    for (int hf = 0; hf < 2; hf++) {
        const float* x = s + hf * 4;
        if ((PMASK >> (G + hf)) & 1) {
            p[hf * 2 + 0] = polyexp2(x[0], x[1], c.cd0, c.one2, c.ca2);
            p[hf * 2 + 1] = polyexp2(x[2], x[3], c.cd1, c.one2, c.ca2);
        } else {
            p[hf * 2 + 0] = pack_bf16(ex2(fmaf(x[0], QS * SC100, c.nm0)), ex2(fmaf(x[1], QS * SC100, c.nm0)));
            p[hf * 2 + 1] = pack_bf16(ex2(fmaf(x[2], QS * SC100, c.nm1)), ex2(fmaf(x[3], QS * SC100, c.nm1)));
        }
    }
}

__device__ __forceinline__ void max16(const float* s, float& mx0, float& mx1) {
    #pragma unroll
    for (int j = 0; j < 4; j++) {
        mx0 = fmaxf(mx0, fmaxf(s[4 * j], s[4 * j + 1]));
        mx1 = fmaxf(mx1, fmaxf(s[4 * j + 2], s[4 * j + 3]));
    }
}

constexpr int MOE_SLOTS = 6, MOE_BOXES = 44;
__device__ __forceinline__ void moe_load(int b, int part, uint32_t ring, uint32_t bars, const CUtensorMap* mg, const CUtensorMap* mu, const CUtensorMap* md) {
    const int sl = b % MOE_SLOTS, grp = b & 1;
    if (b < 28) {
        const int j = b >> 1;
        mbar_expect_tx(bars + sl * 8, 32768);
        tma_2d(ring + sl * 32768, grp ? mu : mg, part * 448 + (j >> 1) * 64, (j & 1) * 256, bars + sl * 8);
    } else {
        const int j = (b - 28) >> 1;
        mbar_expect_tx(bars + sl * 8, 28672);
        tma_2d(ring + sl * 32768, md, ((j >> 1) * 2 + grp) * 64, part * 448 + (j & 1) * 224, bars + sl * 8);
    }
}
__device__ __forceinline__ void mma_2row(float* d, uint32_t a0, uint32_t a2, uint32_t b0, uint32_t b1) {
    asm("mma.sync.aligned.m16n8k16.row.col.f32.bf16.bf16.f32 {%0,%1,%2,%3}, {%4,%5,%6,%5}, {%7,%8}, {%0,%1,%2,%3};"
        : "+f"(d[0]), "+f"(d[1]), "+f"(d[2]), "+f"(d[3]) : "r"(a0), "r"(0u), "r"(a2), "r"(b0), "r"(b1));
}

__device__ void moe_cta(int part, unsigned char* smem, const __nv_bfloat16* __restrict__ x, const CUtensorMap* mg, const CUtensorMap* mu, const CUtensorMap* md) {
    const uint32_t ring = smem_u32(smem), bars = ring + MOE_SLOTS * 32768;
    __nv_bfloat16* xs = (__nv_bfloat16*)(smem + MOE_SLOTS * 32768 + 256);
    float* gu = (float*)(smem + MOE_SLOTS * 32768 + 256 + 2048);
    float* s_v = gu + 4 * 448;
    int* s_i = (int*)(s_v + 16);
    int* s_sel = s_i + 16;
    const int tid = threadIdx.x, warp = __shfl_sync(~0u, tid >> 5, 0), lane = tid & 31;
    if (tid == 0) {
        for (int i = 0; i < MOE_SLOTS; i++) { mbar_init(bars + i * 8, 1); mbar_init(bars + 128 + i * 8, 8); }
        asm volatile("fence.mbarrier_init.release.cluster;" ::: "memory");
        for (int b = 0; b < MOE_SLOTS; b++) moe_load(b, part, ring, bars, mg, mu, md);
    }
    pdl_wait();
    TL(1, 1);
    float rv[4];
    #pragma unroll
    for (int i = 0; i < 4; i++) rv[i] = g_r[tid + i * K2_THREADS];
    for (int pass = 0; pass < 2; pass++) {
        float bv = -INFINITY; int bi = 0x7fffffff;
        const int excl = pass ? s_sel[0] : -1;
        #pragma unroll
        for (int i = 0; i < 4; i++) {
            const int idx = tid + i * K2_THREADS;
            if (idx != excl && (rv[i] > bv || bi == 0x7fffffff)) { bv = rv[i]; bi = idx; }
        }
        #pragma unroll
        for (int o = 16; o; o >>= 1) {
            float ov = __shfl_xor_sync(~0u, bv, o); int oi = __shfl_xor_sync(~0u, bi, o);
            if (ov > bv || (ov == bv && oi < bi)) { bv = ov; bi = oi; }
        }
        if (lane == 0) { s_v[warp] = bv; s_i[warp] = bi; }
        __syncthreads();
        if (warp == 0) {
            bv = lane < 16 ? s_v[lane] : -INFINITY; bi = lane < 16 ? s_i[lane] : 0x7fffffff;
            #pragma unroll
            for (int o = 16; o; o >>= 1) {
                float ov = __shfl_xor_sync(~0u, bv, o); int oi = __shfl_xor_sync(~0u, bi, o);
                if (ov > bv || (ov == bv && oi < bi)) { bv = ov; bi = oi; }
            }
            if (lane == 0) s_sel[pass] = (bi == 0x7fffffff) ? pass : bi;
        }
        __syncthreads();
    }
    for (int i = tid; i < 1024; i += K2_THREADS) {
        const int tok = s_sel[i >> 9];
        const float2 st = g_stats[tok];
        xs[i] = __float2bfloat16_rn(ln_elem(__bfloat162float(x[(size_t)tok * D_ + (i & 511)]), st.x, st.y));
    }
    if (part == 0 && tid < 2) g_sel[tid] = s_sel[tid];
    __syncthreads();
    if (warp == 8) {
        if (lane == 0) {
            for (int b = MOE_SLOTS; b < MOE_BOXES; b++) {
                mbar_wait(bars + 128 + (b % MOE_SLOTS) * 8, (b / MOE_SLOTS - 1) & 1);
                moe_load(b, part, ring, bars, mg, mu, md);
            }
        }
        return;
    }
    if (warp > 8) return;
    const int nj = warp, g = lane >> 2, t = lane & 3;
    const uint32_t* xw = (const uint32_t*)xs + (g & 1) * 256 + t;
    uint32_t a[2][32];
    #pragma unroll
    for (int i = 0; i < 32; i++) { a[0][i] = xw[i * 4]; a[1][i] = xw[128 + i * 4]; }
    #pragma unroll 1
    for (int jp = 0; jp < MOE_BOXES / 4; jp++) {
        const bool down = jp >= 7;
        if (jp == 7) {
            named_bar(1, 256);
            for (int i = tid; i < 896; i += 256) {
                const float gs = bf16r(gu[i]), us = bf16r(gu[896 + i]);
                const float sl_ = bf16r(gs / (1.0f + __expf(-gs)));
                xs[(i / 448) * 512 + (i % 448)] = __float2bfloat16_rn(sl_ * us);
            }
            named_bar(1, 256);
            #pragma unroll
            for (int i = 0; i < 28; i++) { a[0][i] = xw[i * 4]; a[1][i] = xw[112 + i * 4]; }
        }
        float acc[2][4] = {{0.f, 0.f, 0.f, 0.f}, {0.f, 0.f, 0.f, 0.f}}, acb[2][4] = {{0.f, 0.f, 0.f, 0.f}, {0.f, 0.f, 0.f, 0.f}};
        #pragma unroll
        for (int q = 0; q < 4; q++) {
            const int hf = q >> 1, grp = q & 1;
            const int b = jp * 4 + q, sl = b % MOE_SLOTS;
            mbar_wait(bars + sl * 8, (b / MOE_SLOTS) & 1);
            const uint32_t baddr = ring + sl * 32768 + lane * 128 + ((nj ^ (lane & 7)) * 16);
            #pragma unroll
            for (int k4 = 0; k4 < 2; k4++) {
                uint32_t bf[4][4];
                #pragma unroll
                for (int k2 = 0; k2 < 4; k2++)
                    asm volatile("ldmatrix.sync.aligned.m8n8.x4.trans.shared.b16 {%0, %1, %2, %3}, [%4];"
                                 : "=r"(bf[k2][0]), "=r"(bf[k2][1]), "=r"(bf[k2][2]), "=r"(bf[k2][3]) : "r"(baddr + (k4 * 4 + k2) * 4096) : "memory");
                #pragma unroll
                for (int k2 = 0; k2 < 4; k2++) {
                    const int kk = k4 * 4 + k2;
                    if (kk < 7 || !down) {
                        mma_2row(acc[grp], a[hf][4 * kk], a[hf][4 * kk + 1], bf[k2][0], bf[k2][1]);
                        mma_2row(acb[grp], a[hf][4 * kk + 2], a[hf][4 * kk + 3], bf[k2][2], bf[k2][3]);
                    }
                }
            }
            __syncwarp();
            if (lane == 0) mbar_arrive(bars + 128 + sl * 8);
        }
        if (g < 2) {
            #pragma unroll
            for (int grp = 0; grp < 2; grp++) {
                const float2 v = make_float2(acc[grp][0] + acb[grp][0], acc[grp][1] + acb[grp][1]);
                if (!down) *(float2*)&gu[(grp * 2 + g) * 448 + jp * 64 + nj * 8 + t * 2] = v;
                else *(float2*)&g_ypart[part][g][((jp - 7) * 2 + grp) * 64 + nj * 8 + t * 2] = v;
            }
        }
    }
}

__global__ void __launch_bounds__(K2_THREADS, 1)
k2_attn(const __nv_bfloat16* __restrict__ x, const __nv_bfloat16* __restrict__ w_gate, const __nv_bfloat16* __restrict__ w_up,
        const __nv_bfloat16* __restrict__ w_down, const __grid_constant__ CUtensorMap mg, const __grid_constant__ CUtensorMap mu,
        const __grid_constant__ CUtensorMap md) {
    extern __shared__ __align__(1024) unsigned char smem[];
    TL(1, 0);
    pdl_launch();
    if (blockIdx.x >= 128) { moe_cta(blockIdx.x - 128, smem, x, &mg, &mu, &md); TL(1, 2); return; }
    if (threadIdx.x >= 32 && threadIdx.x < 35) {
        const __nv_bfloat16* w = threadIdx.x == 32 ? w_gate : (threadIdx.x == 33 ? w_up : w_down);
        asm volatile("cp.async.bulk.prefetch.L2.global [%0], %1;" :: "l"(w + (size_t)blockIdx.x * (D_ * F_ / 128)), "r"(D_ * F_ / 64) : "memory");
    }
    const uint32_t sK = smem_u32(smem), sV = sK + 65536, sQ = sV + 98304, sBar = sQ + 16384;
    const int h = blockIdx.x >> 2, qb = blockIdx.x & 3;
    const int warp = __shfl_sync(~0u, threadIdx.x >> 5, 0), lane = threadIdx.x & 31, wg = warp >> 2;
    if (threadIdx.x == 0) {
        mbar_init(sBar, 1); mbar_init(sBar + 8, 1);
        asm volatile("fence.mbarrier_init.release.cluster;" ::: "memory");
        mbar_expect_tx(sBar, 8192 + 12288 + 2 * 6144);
        mbar_expect_tx(sBar + 8, 8192 + 53248 + 2 * 26624);
    }
    for (int i = threadIdx.x; i < 2048; i += K2_THREADS)
        *(uint4*)(smem + 65536 + 65536 + i * 16) = make_uint4(0x3F803F80u, 0x3F803F80u, 0x3F803F80u, 0x3F803F80u);
    fence_async_smem();
    __syncthreads();
    if (warp == 0) {
        pdl_wait();
        TL(1, 1);
        const uint4* gk = g_K + (size_t)h * 4096;
        const uint4* gv = g_V + (size_t)h * 4096;
        const uint4* gq = g_Q + (size_t)h * 4096 + qb * 1024;
        if (lane == 0) bulk_g2s(sQ, gq, 8192, sBar);
        if (lane == 1) bulk_g2s(sK, gk, 12288, sBar);
        if (lane == 2) bulk_g2s(sV, gv, 6144, sBar);
        if (lane == 3) bulk_g2s(sV + 32768, gv + 2048, 6144, sBar);
        if (lane == 4) bulk_g2s(sK + 12288, gk + 768, 53248, sBar + 8);
        if (lane == 5) bulk_g2s(sV + 6144, gv + 384, 26624, sBar + 8);
        if (lane == 6) bulk_g2s(sV + 32768 + 6144, gv + 2048 + 384, 26624, sBar + 8);
        if (lane == 7) bulk_g2s(sQ + 8192, gq + 512, 8192, sBar + 8);
        __syncwarp();
    }
    ExpC c;
    {
        const volatile uint32_t* cc = g_const;
        c.one2 = cc[0]; c.ca2 = cc[1];
    }
    const uint64_t kdesc0 = make_desc(sK, 128, 256, 0);
    const uint64_t vdesc0 = make_desc(sV, 128, 32768, 0);
    #pragma unroll 1
    for (int pass = 0; pass < 2; pass++) {
        const bool dry = false;
        if (pass == 0) { mbar_wait(sBar, 0); __syncwarp(); TL(1, 2); }
        const int unit = (pass & 1) * 4 + wg;
        const uint64_t q = make_desc(sQ + unit * 2048, 128, 256, 0);
        float o[12];
        #pragma unroll 1
        for (int attempt = 0; attempt < 2; attempt++) {
            float s0[16], s1[16], s2[16];
            #pragma unroll
            for (int i = 0; i < 16; i++) { s0[i] = 0.f; s1[i] = 0.f; s2[i] = 0.f; }
            float mx0 = -INFINITY, mx1 = -INFINITY;
            if (attempt) {
                #pragma unroll 1
                for (int it = 0; it < 64; it++) {
                    WG_FENCE();
                    wgmma_qk32(s0, q, kdesc0 + it * 64);
                    WG_COMMIT();
                    wg_wait<0>();
                    touch16(s0);
                    max16(s0, mx0, mx1);
                }
            }
            #pragma unroll
            for (int i = 0; i < 12; i++) o[i] = 0.f;
            WG_FENCE();
            wgmma_qk32(s2, q, kdesc0);
            wgmma_qk32(s0, q, kdesc0 + 64);
            wgmma_qk32(s1, q, kdesc0 + 128);
            WG_COMMIT();
            wg_wait<0>();
            touch16(s0); touch16(s1); touch16(s2);
            max16(s0, mx0, mx1); max16(s1, mx0, mx1); max16(s2, mx0, mx1);
            mx0 = fmaxf(mx0, __shfl_xor_sync(~0u, mx0, 1)); mx0 = fmaxf(mx0, __shfl_xor_sync(~0u, mx0, 2));
            mx1 = fmaxf(mx1, __shfl_xor_sync(~0u, mx1, 1)); mx1 = fmaxf(mx1, __shfl_xor_sync(~0u, mx1, 2));
            const float bias = attempt ? 0.0f : 128.0f * 64.0f;
            const float y0 = ceilf(fmaf(mx0, 128.0f * QS * SC100, bias)), y1 = ceilf(fmaf(mx1, 128.0f * QS * SC100, bias));
            c.nm0 = __shfl_sync(~0u, y0 * (-1.0f / 128.0f), lane); c.nm1 = __shfl_sync(~0u, y1 * (-1.0f / 128.0f), lane);
            c.cd0 = __shfl_sync(~0u, __fmul_rn(16256.0f - y0, __int_as_float(1)), lane);
            c.cd1 = __shfl_sync(~0u, __fmul_rn(16256.0f - y1, __int_as_float(1)), lane);
            uint64_t kd = kdesc0 + 192, vd = vdesc0 + 32;
            {
                uint32_t pa[4], pb[4];
                exp_block<12>(s2, pa, c);
                exp_block<14>(s2 + 8, pb, c);
                WG_FENCE();
                wgmma_pv(o, pa, vdesc0); wgmma_pv(o, pb, vdesc0 + 16);
                WG_COMMIT();
            }
            #pragma unroll 1
            for (int seg = 0; seg < (dry ? 1 : 2); seg++) {
            if (seg) { wg_wait<0>(); mbar_wait(sBar + 8, 0); __syncwarp(); }
            #pragma unroll 1
            for (int it = seg ? 3 : (dry ? 2 : 0); it < (seg ? 21 : 3); it++) {
                uint32_t p[6][4];
                WG_FENCE();
                wgmma_qk32(s2, q, kd);
                WG_COMMIT();
                exp_block<0>(s0, p[0], c);
                exp_block<2>(s0 + 8, p[1], c);
                WG_FENCE();
                wgmma_pv(o, p[0], vd); wgmma_pv(o, p[1], vd + 16);
                wgmma_qk32(s0, q, kd + 64);
                WG_COMMIT();
                wg_wait<1>();
                touch16(s2);
                exp_block<4>(s1, p[2], c);
                exp_block<6>(s1 + 8, p[3], c);
                WG_FENCE();
                wgmma_pv(o, p[2], vd + 32); wgmma_pv(o, p[3], vd + 48);
                wgmma_qk32(s1, q, kd + 128);
                WG_COMMIT();
                wg_wait<1>();
                touch16(s0);
                exp_block<8>(s2, p[4], c);
                exp_block<10>(s2 + 8, p[5], c);
                WG_FENCE();
                wgmma_pv(o, p[4], vd + 64); wgmma_pv(o, p[5], vd + 80);
                WG_COMMIT();
                vd += 96; kd += 192;
                wg_wait<1>();
                touch16(s1);
            }
            }
            wg_wait<0>();
            touch12(o);
            if (attempt) break;
            float big = 0.f;
            #pragma unroll
            for (int i = 0; i < 12; i++) big = fmaxf(big, fabsf(o[i]));
            bool bad = !(big < 1e30f);
            #pragma unroll
            for (int i = 0; i < 12; i++) bad |= (o[i] != o[i]);
            uint32_t any;
            asm volatile("{.reg .pred p, q; setp.ne.u32 p, %1, 0; barrier.cta.red.or.pred.aligned q, %2, 128, p; selp.u32 %0, 1, 0, q;}"
                         : "=r"(any) : "r"((uint32_t)bad), "r"(1 + wg) : "memory");
            if (dry || !__any_sync(~0u, any)) break;
        }
        const int g = lane >> 2, t = lane & 3;
        const int r = (warp & 3) * 16 + g;
        const float i0 = __fdiv_rn(1.0f, o[8]), i1 = __fdiv_rn(1.0f, o[10]);
        uint32_t* ob = (uint32_t*)(g_O + (size_t)(qb * 8 + unit) * 4096 + (h >> 2) * 512 + r * 8) + t;
        const int c0 = ((h & 3) * 2) ^ (r & 7), c1 = ((h & 3) * 2 + 1) ^ (r & 7);
        if (!dry) {
            ob[c0 * 4] = pack_bf16(o[0] * i0, o[1] * i0);
            ob[c1 * 4] = pack_bf16(o[4] * i0, o[5] * i0);
            ob[256 + c0 * 4] = pack_bf16(o[2] * i1, o[3] * i1);
            ob[256 + c1 * 4] = pack_bf16(o[6] * i1, o[7] * i1);
            TL(1, 3 + pass);
        }
    }
}

constexpr int K3_THREADS = 256;
constexpr int K3_SMEM = 65536 + 131072 + 128;

__global__ void __launch_bounds__(K3_THREADS, 1)
k3_out(const __grid_constant__ CUtensorMap wmap, const __nv_bfloat16* __restrict__ x, __nv_bfloat16* __restrict__ out) {
    extern __shared__ __align__(1024) unsigned char smem[];
    const uint32_t sA = smem_u32(smem), sB = sA + 65536, sBar = sB + 131072;
    const int warp = __shfl_sync(~0u, threadIdx.x >> 5, 0), lane = threadIdx.x & 31, wg = warp >> 2;
    const int nt = blockIdx.x & 3, mt = blockIdx.x >> 2;
    TL(2, 0);
    if (threadIdx.x == 0) {
        for (int i = 0; i < 10; i++) mbar_init(sBar + i * 8, 1);
        asm volatile("fence.mbarrier_init.release.cluster;" ::: "memory");
        for (int i = 0; i < 8; i++) mbar_expect_tx(sBar + 16 + i * 8, 8192);
        for (int kh = 0; kh < 2; kh++) {
            mbar_expect_tx(sBar + kh * 8, 65536);
            tma_2d(sB + kh * 32768, &wmap, nt * 128, kh * 256, sBar + kh * 8);
            tma_2d(sB + 65536 + kh * 32768, &wmap, nt * 128 + 64, kh * 256, sBar + kh * 8);
        }
    }
    const int er = threadIdx.x >> 2, ec = (threadIdx.x & 3) * 32;
    const int row = mt * 64 + er;
    uint4 xv[4];
    #pragma unroll
    for (int j = 0; j < 4; j++) xv[j] = __ldg((const uint4*)(x + (size_t)row * D_ + nt * 128 + ec) + j);
    __syncthreads();
    pdl_wait();
    TL(2, 1);
    if (threadIdx.x < 8) bulk_g2s(sA + threadIdx.x * 8192, g_O + (size_t)mt * 4096 + threadIdx.x * 512, 8192, sBar + 16 + threadIdx.x * 8);
    const int sel0 = g_sel[0], sel1 = g_sel[1];
    const float2 st = g_stats[row];
    uint32_t bb[16];
    {
        const uint32_t xu[16] = {xv[0].x, xv[0].y, xv[0].z, xv[0].w, xv[1].x, xv[1].y, xv[1].z, xv[1].w,
                                 xv[2].x, xv[2].y, xv[2].z, xv[2].w, xv[3].x, xv[3].y, xv[3].z, xv[3].w};
        #pragma unroll
        for (int j = 0; j < 16; j++) bb[j] = pack_bf16(bf16r(bf_lo(xu[j]) - st.x) * st.y, bf16r(bf_hi(xu[j]) - st.x) * st.y);
        const int slot = row == sel0 ? 0 : (row == sel1 ? 1 : -1);
        if (slot >= 0) {
            const float gate = bf16r(1.0f / (1.0f + __expf(-g_r[row])));
            const int c0 = nt * 128 + ec;
            #pragma unroll
            for (int j = 0; j < 16; j++) {
                const float2 a = *(const float2*)&g_ypart[0][slot][c0 + 2 * j], b = *(const float2*)&g_ypart[1][slot][c0 + 2 * j];
                const float2 c = *(const float2*)&g_ypart[2][slot][c0 + 2 * j], d = *(const float2*)&g_ypart[3][slot][c0 + 2 * j];
                bb[j] = pack_bf16(bf_lo(bb[j]) + bf16r(bf16r(a.x + b.x + c.x + d.x) * gate), bf_hi(bb[j]) + bf16r(bf16r(a.y + b.y + c.y + d.y) * gate));
            }
        }
    }
    float acc[32];
    #pragma unroll
    for (int i = 0; i < 32; i++) acc[i] = 0.f;
    const uint64_t da0 = make_desc(sA, 16, 1024, 1);
    const uint64_t db0 = make_desc(sB + wg * 65536, 8192, 1024, 1);
    #pragma unroll 1
    for (int q = 0; q < 8; q++) {
        if ((q & 3) == 0) mbar_wait(sBar + (q >> 2) * 8, 0);
        mbar_wait(sBar + 16 + q * 8, 0);
        WG_FENCE();
        #pragma unroll
        for (int kk = 0; kk < 4; kk++)
            wgmma_n64(acc, da0 + (uint64_t)(q * 512 + kk * 2), db0 + (uint64_t)(q * 512 + kk * 128));
        WG_COMMIT();
    }
    wg_wait<0>();
    touch32(acc);
    TL(2, 2);
    __syncthreads();
    {
        const int g = lane >> 2, t = lane & 3;
        unsigned char* sp = smem + ((warp & 3) * 16 + g) * 272 + wg * 128 + t * 4;
        #pragma unroll
        for (int j = 0; j < 8; j++) {
            *(uint32_t*)(sp + j * 16) = pack_bf16(acc[4 * j], acc[4 * j + 1]);
            *(uint32_t*)(sp + 8 * 272 + j * 16) = pack_bf16(acc[4 * j + 2], acc[4 * j + 3]);
        }
    }
    __syncthreads();
    #pragma unroll
    for (int j = 0; j < 4; j++) {
        const uint4 av = *(const uint4*)(smem + er * 272 + ec * 2 + j * 16);
        const uint32_t au[4] = {av.x, av.y, av.z, av.w}, xu[4] = {xv[j].x, xv[j].y, xv[j].z, xv[j].w};
        uint32_t o[4];
        #pragma unroll
        for (int i = 0; i < 4; i++) {
            uint32_t t2;
            asm("add.rn.bf16x2 %0, %1, %2;" : "=r"(t2) : "r"(xu[i]), "r"(au[i]));
            asm("add.rn.bf16x2 %0, %1, %2;" : "=r"(o[i]) : "r"(t2), "r"(bb[j * 4 + i]));
        }
        *((uint4*)(out + (size_t)row * D_ + nt * 128 + ec) + j) = make_uint4(o[0], o[1], o[2], o[3]);
    }
    TL(2, 3);
}

typedef CUresult (*EncodeFn)(CUtensorMap*, CUtensorMapDataType, cuuint32_t, void*, const cuuint64_t*, const cuuint64_t*,
                             const cuuint32_t*, const cuuint32_t*, CUtensorMapInterleave, CUtensorMapSwizzle,
                             CUtensorMapL2promotion, CUtensorMapFloatOOBfill);

void make_wmap(EncodeFn fn, CUtensorMap* map, const void* ptr, int rows, int cols, int box_rows) {
    cuuint64_t dims[2] = {(cuuint64_t)cols, (cuuint64_t)rows};
    cuuint64_t strides[1] = {(cuuint64_t)cols * 2};
    cuuint32_t box[2] = {64, (cuuint32_t)box_rows};
    cuuint32_t es[2] = {1, 1};
    fn(map, CU_TENSOR_MAP_DATA_TYPE_BFLOAT16, 2, (void*)ptr, dims, strides, box, es, CU_TENSOR_MAP_INTERLEAVE_NONE,
       CU_TENSOR_MAP_SWIZZLE_128B, CU_TENSOR_MAP_L2_PROMOTION_L2_256B, CU_TENSOR_MAP_FLOAT_OOB_FILL_NONE);
}

}

extern "C" void kernel_launch(void* const* d_in, const int* in_sizes, int n_in, void* d_out, int out_size) {
    const __nv_bfloat16* x = (const __nv_bfloat16*)d_in[0];
    const __nv_bfloat16* wqkv = (const __nv_bfloat16*)d_in[1];
    const __nv_bfloat16* wo = (const __nv_bfloat16*)d_in[2];
    const __nv_bfloat16* w_r = (const __nv_bfloat16*)d_in[4];
    const __nv_bfloat16* w_gate = (const __nv_bfloat16*)d_in[5];
    const __nv_bfloat16* w_up = (const __nv_bfloat16*)d_in[6];
    const __nv_bfloat16* w_down = (const __nv_bfloat16*)d_in[7];
    __nv_bfloat16* out = (__nv_bfloat16*)d_out;

    static EncodeFn encode = nullptr;
    if (!encode) {
        void* fn = nullptr;
        cudaDriverEntryPointQueryResult qres;
        cudaGetDriverEntryPoint("cuTensorMapEncodeTiled", &fn, cudaEnableDefault, &qres);
        encode = (EncodeFn)fn;
        cudaFuncSetAttribute(k1_ln_qkv, cudaFuncAttributeMaxDynamicSharedMemorySize, K1_SMEM);
        cudaFuncSetAttribute(k2_attn, cudaFuncAttributeMaxDynamicSharedMemorySize, K2_SMEM);
        cudaFuncSetAttribute(k3_out, cudaFuncAttributeMaxDynamicSharedMemorySize, K3_SMEM);
    }
    CUtensorMap map_qkv, map_wo, map_x, map_g, map_u, map_d;
    make_wmap(encode, &map_g, w_gate, D_, F_, 256);
    make_wmap(encode, &map_u, w_up, D_, F_, 256);
    make_wmap(encode, &map_d, w_down, F_, D_, 224);
    make_wmap(encode, &map_x, x, S_, D_, 64);
    make_wmap(encode, &map_qkv, wqkv, D_, 3 * D_, 64);
    make_wmap(encode, &map_wo, wo, D_, D_, 256);

    k1_ln_qkv<<<128, K1_THREADS, K1_SMEM, cudaStreamPerThread>>>(map_qkv, map_x, w_r);
    cudaLaunchAttribute at[1];
    at[0].id = cudaLaunchAttributeProgrammaticStreamSerialization;
    at[0].val.programmaticStreamSerializationAllowed = 1;
    cudaLaunchConfig_t cfg = {};
    cfg.stream = cudaStreamPerThread;
    cfg.attrs = at; cfg.numAttrs = 1;
    cfg.gridDim = dim3(132); cfg.blockDim = dim3(K2_THREADS); cfg.dynamicSmemBytes = K2_SMEM;
    cudaLaunchKernelEx(&cfg, k2_attn, x, w_gate, w_up, w_down, map_g, map_u, map_d);
    cfg.gridDim = dim3(128); cfg.blockDim = dim3(K3_THREADS); cfg.dynamicSmemBytes = K3_SMEM;
    cudaLaunchKernelEx(&cfg, k3_out, map_wo, x, out);
}
```

```cpp
#include <cuda_runtime.h>
#include <cuda_bf16.h>
#include <cuda.h>
#include <stdint.h>

namespace {

constexpr int S_ = 2048, D_ = 512, H_ = 32, F_ = 1792;

constexpr uint32_t PMASK = 0xDB6;

__device__ __align__(1024) uint4 g_QKV[3 * H_ * S_ * 2];
#define g_Q (g_QKV)
#define g_K (g_QKV + H_ * S_ * 2)
#define g_V (g_QKV + 2 * H_ * S_ * 2)
__device__ __align__(1024) uint4 g_O[S_ * D_ / 8];
__device__ float2 g_stats[S_];
__device__ uint32_t g_const[2] = {0x3F803F80u, 0x42294229u};
__device__ float g_r[S_];
__device__ __align__(16) float g_ypart[4][2][D_];
__device__ int g_sel[2];

#define TL(k, p)
#define CK(i)
__device__ __forceinline__ uint32_t smem_u32(const void* p) { return (uint32_t)__cvta_generic_to_shared(p); }
__device__ __forceinline__ float bf16r(float x) { return __bfloat162float(__float2bfloat16_rn(x)); }
__device__ __forceinline__ uint32_t pack_bf16(float lo, float hi) {
    uint32_t r; asm("cvt.rn.bf16x2.f32 %0, %1, %2;" : "=r"(r) : "f"(hi), "f"(lo)); return r;
}
__device__ __forceinline__ float bf_lo(uint32_t u) { return __uint_as_float(u << 16); }
__device__ __forceinline__ float bf_hi(uint32_t u) { return __uint_as_float(u & 0xFFFF0000u); }
__device__ __forceinline__ float ex2(float x) { float y; asm("ex2.approx.ftz.f32 %0, %1;" : "=f"(y) : "f"(x)); return y; }

__device__ __forceinline__ void mbar_init(uint32_t bar, uint32_t count) {
    asm volatile("mbarrier.init.shared::cta.b64 [%0], %1;" :: "r"(bar), "r"(count) : "memory");
}
__device__ __forceinline__ void mbar_expect_tx(uint32_t bar, uint32_t bytes) {
    asm volatile("mbarrier.arrive.expect_tx.shared::cta.b64 _, [%0], %1;" :: "r"(bar), "r"(bytes) : "memory");
}
__device__ __forceinline__ void mbar_arrive(uint32_t bar) {
    asm volatile("mbarrier.arrive.shared::cta.b64 _, [%0];" :: "r"(bar) : "memory");
}
__device__ __forceinline__ void mbar_wait(uint32_t bar, uint32_t parity) {
    uint32_t done;
    #pragma unroll 1
    for (int it = 0; it < (1 << 26); it++) {
        asm volatile("{.reg .pred p; mbarrier.try_wait.parity.shared::cta.b64 p, [%1], %2; selp.u32 %0, 1, 0, p;}"
                     : "=r"(done) : "r"(bar), "r"(parity) : "memory");
        if (done) return;
    }
    __trap();
}
__device__ __forceinline__ void bulk_g2s(uint32_t dst, const void* src, uint32_t bytes, uint32_t bar) {
    asm volatile("cp.async.bulk.shared::cluster.global.mbarrier::complete_tx::bytes [%0], [%1], %2, [%3];"
                 :: "r"(dst), "l"(src), "r"(bytes), "r"(bar) : "memory");
}
__device__ __forceinline__ void tma_2d(uint32_t dst, const CUtensorMap* map, int c0, int c1, uint32_t bar) {
    asm volatile("cp.async.bulk.tensor.2d.shared::cluster.global.mbarrier::complete_tx::bytes [%0], [%1, {%3, %4}], [%2];"
                 :: "r"(dst), "l"(map), "r"(bar), "r"(c0), "r"(c1) : "memory");
}
__device__ __forceinline__ void fence_async_smem() { asm volatile("fence.proxy.async.shared::cta;" ::: "memory"); }
__device__ __forceinline__ void named_bar(int id, int n) { asm volatile("bar.sync %0, %1;" :: "r"(id), "r"(n) : "memory"); }

__device__ __forceinline__ uint64_t make_desc(uint32_t saddr, uint32_t lbo, uint32_t sbo, uint32_t swz) {
    return (uint64_t)((saddr & 0x3FFFF) >> 4) | ((uint64_t)(lbo >> 4) << 16) | ((uint64_t)(sbo >> 4) << 32) | ((uint64_t)swz << 62);
}
#define WG_FENCE() asm volatile("wgmma.fence.sync.aligned;" ::: "memory")
#define WG_COMMIT() asm volatile("wgmma.commit_group.sync.aligned;" ::: "memory")
template <int N> __device__ __forceinline__ void wg_wait() { asm volatile("wgmma.wait_group.sync.aligned %0;" :: "n"(N) : "memory"); }

#define F4(d, o) "+f"(d[o]), "+f"(d[o + 1]), "+f"(d[o + 2]), "+f"(d[o + 3])
#define F16(d, o) F4(d, o), F4(d, o + 4), F4(d, o + 8), F4(d, o + 12)
#define F32(d, o) F16(d, o), F16(d, o + 16)

__device__ __forceinline__ void wgmma_rs_n192(float* d, const uint32_t* a, uint64_t db) {
    asm volatile("wgmma.mma_async.sync.aligned.m64n192k16.f32.bf16.bf16 "
        "{%0,%1,%2,%3,%4,%5,%6,%7,%8,%9,%10,%11,%12,%13,%14,%15,%16,%17,%18,%19,%20,%21,%22,%23,%24,%25,%26,%27,%28,%29,%30,%31,"
        "%32,%33,%34,%35,%36,%37,%38,%39,%40,%41,%42,%43,%44,%45,%46,%47,%48,%49,%50,%51,%52,%53,%54,%55,%56,%57,%58,%59,%60,%61,%62,%63,"
        "%64,%65,%66,%67,%68,%69,%70,%71,%72,%73,%74,%75,%76,%77,%78,%79,%80,%81,%82,%83,%84,%85,%86,%87,%88,%89,%90,%91,%92,%93,%94,%95}, "
        "{%96,%97,%98,%99}, %100, 1, 1, 1, 1;\n"
        : F32(d, 0), F32(d, 32), F32(d, 64) : "r"(a[0]), "r"(a[1]), "r"(a[2]), "r"(a[3]), "l"(db));
}
__device__ __forceinline__ void wgmma_n64(float* d, uint64_t da, uint64_t db) {
    asm volatile("wgmma.mma_async.sync.aligned.m64n64k16.f32.bf16.bf16 "
        "{%0,%1,%2,%3,%4,%5,%6,%7,%8,%9,%10,%11,%12,%13,%14,%15,%16,%17,%18,%19,%20,%21,%22,%23,%24,%25,%26,%27,%28,%29,%30,%31}, "
        "%32, %33, 1, 1, 1, 0, 1;\n"
        : F32(d, 0) : "l"(da), "l"(db));
}
__device__ __forceinline__ void wgmma_qk32(float* d, uint64_t qd, uint64_t kd) {
    asm volatile("wgmma.mma_async.sync.aligned.m64n32k16.f32.bf16.bf16 {%0,%1,%2,%3,%4,%5,%6,%7,%8,%9,%10,%11,%12,%13,%14,%15}, %16, %17, 0, 1, 1, 0, 0;\n"
        : F16(d, 0) : "l"(qd), "l"(kd));
}
__device__ __forceinline__ void wgmma_pv(float* d, const uint32_t* a, uint64_t vd) {
    asm volatile("wgmma.mma_async.sync.aligned.m64n24k16.f32.bf16.bf16 {%0,%1,%2,%3,%4,%5,%6,%7,%8,%9,%10,%11}, {%12,%13,%14,%15}, %16, 1, 1, 1, 1;\n"
        : F4(d, 0), F4(d, 4), F4(d, 8) : "r"(a[0]), "r"(a[1]), "r"(a[2]), "r"(a[3]), "l"(vd));
}
__device__ __forceinline__ void touch16(float* d) { asm volatile("" : F16(d, 0) :: "memory"); }
__device__ __forceinline__ void touch12(float* d) { asm volatile("" : F4(d, 0), F4(d, 4), F4(d, 8) :: "memory"); }
__device__ __forceinline__ void touch32(float* d) { asm volatile("" : F32(d, 0) :: "memory"); }
__device__ __forceinline__ void touch96(float* d) { asm volatile("" : F32(d, 0), F32(d, 32), F32(d, 64) :: "memory"); }

__device__ __forceinline__ float ln_elem(float x, float mean_b, float rden) {
    return bf16r(bf16r(x - mean_b) * rden);
}
__device__ __forceinline__ void pdl_wait() { asm volatile("griddepcontrol.wait;" ::: "memory"); }
__device__ __forceinline__ void pdl_launch() { asm volatile("griddepcontrol.launch_dependents;" ::: "memory"); }
__device__ __forceinline__ void cluster_arrive() { asm volatile("barrier.cluster.arrive.release.aligned;" ::: "memory"); }
__device__ __forceinline__ void cluster_wait() { asm volatile("barrier.cluster.wait.acquire.aligned;" ::: "memory"); }

constexpr int K1_THREADS = 320;
constexpr int K1_SMEM = 131072 + 6 * 16384 + 256 + 1024;

__device__ __forceinline__ void ldsm4(uint32_t* r, uint32_t addr) {
    asm volatile("ldmatrix.sync.aligned.m8n8.x4.shared.b16 {%0, %1, %2, %3}, [%4];" : "=r"(r[0]), "=r"(r[1]), "=r"(r[2]), "=r"(r[3]) : "r"(addr) : "memory");
}
__device__ __forceinline__ void stsm4(uint32_t addr, uint32_t r0, uint32_t r1, uint32_t r2, uint32_t r3) {
    asm volatile("stmatrix.sync.aligned.m8n8.x4.shared.b16 [%0], {%1, %2, %3, %4};" :: "r"(addr), "r"(r0), "r"(r1), "r"(r2), "r"(r3) : "memory");
}
__device__ __forceinline__ void mma16816(float* d, const uint32_t* a, uint32_t b0, uint32_t b1) {
    asm("mma.sync.aligned.m16n8k16.row.col.f32.bf16.bf16.f32 {%0,%1,%2,%3}, {%4,%5,%6,%7}, {%8,%9}, {%0,%1,%2,%3};"
        : "+f"(d[0]), "+f"(d[1]), "+f"(d[2]), "+f"(d[3]) : "r"(a[0]), "r"(a[1]), "r"(a[2]), "r"(a[3]), "r"(b0), "r"(b1));
}
__device__ __forceinline__ uint32_t sub_bf16x2(uint32_t a, uint32_t b) {
    uint32_t d; asm("sub.rn.bf16x2 %0, %1, %2;" : "=r"(d) : "r"(a), "r"(b)); return d;
}
__device__ __forceinline__ uint32_t ln_pair(uint32_t x2, uint32_t mean2, uint32_t rhi2, uint32_t rlo2) {
    const uint32_t d = sub_bf16x2(x2, mean2);
    uint32_t t, y;
    asm("mul.rn.bf16x2 %0, %1, %2;" : "=r"(t) : "r"(d), "r"(rlo2));
    asm("fma.rn.bf16x2 %0, %1, %2, %3;" : "=r"(y) : "r"(d), "r"(rhi2), "r"(t));
    return y;
}
struct LnRow { uint32_t m2, hi2, lo2; };
__device__ __forceinline__ LnRow ln_row(float mean, float rden) {
    LnRow r;
    r.m2 = pack_bf16(mean, mean);
    r.hi2 = pack_bf16(rden, rden);
    const float lo = rden - bf_lo(r.hi2);
    r.lo2 = pack_bf16(lo, lo);
    return r;
}
__device__ __forceinline__ void ln_frag(uint32_t* a, const LnRow& r0, const LnRow& r1) {
    a[0] = ln_pair(a[0], r0.m2, r0.hi2, r0.lo2); a[1] = ln_pair(a[1], r1.m2, r1.hi2, r1.lo2);
    a[2] = ln_pair(a[2], r0.m2, r0.hi2, r0.lo2); a[3] = ln_pair(a[3], r1.m2, r1.hi2, r1.lo2);
}

template <int NJ>
__device__ __forceinline__ void k1_store(const float* acc, int jj0, uint32_t stage, int nt, int mt, int wg, int w4, int lane) {
    const int mi = lane >> 3, lr = lane & 7;
    const uint32_t off_qk = stage + (w4 * 2 + (mi & 1)) * 256 + (mi >> 1) * 128 + lr * 16;
    const uint32_t off_v = stage + (mi >> 1) * 1024 + (w4 * 16 + (mi & 1) * 8 + lr) * 16;
    #pragma unroll
    for (int jj = 0; jj < NJ; jj++) {
        const bool isv = nt * 12 + jj0 + jj >= 64;
        const float m = isv ? 1.0f : 8.8817841970012523e-16f;
        stsm4((isv ? off_v : off_qk) + jj * 2048,
              pack_bf16(acc[8 * jj] * m, acc[8 * jj + 1] * m), pack_bf16(acc[8 * jj + 2] * m, acc[8 * jj + 3] * m),
              pack_bf16(acc[8 * jj + 4] * m, acc[8 * jj + 5] * m), pack_bf16(acc[8 * jj + 6] * m, acc[8 * jj + 7] * m));
    }
    fence_async_smem();
    named_bar(1 + wg, 128);
    if (lane < NJ / 2) {
        const int pc = w4 * (NJ / 2) + lane, jj = pc >> 1, hf = pc & 1, hg = nt * 12 + jj0 + jj;
        const unsigned char* dst = (const unsigned char*)g_QKV + (size_t)hg * 65536
            + (hg >= 64 ? hf * 32768 + (mt * 128 + wg * 64) * 16 : (mt * 16 + wg * 8) * 256 + hf * 1024);
        asm volatile("cp.async.bulk.global.shared::cta.bulk_group [%0], [%1], 1024;" :: "l"(dst), "r"(stage + pc * 1024) : "memory");
        asm volatile("cp.async.bulk.commit_group;" ::: "memory");
    }
}

__global__ void __launch_bounds__(K1_THREADS, 1)
k1_ln_qkv(const __grid_constant__ CUtensorMap wmap, const __grid_constant__ CUtensorMap xmap, const __nv_bfloat16* __restrict__ w_r) {
    extern __shared__ __align__(1024) unsigned char smem[];
    const uint32_t sA = smem_u32(smem), sB = sA + 131072, sBar = sB + 4 * 24576;
    const int warp = __shfl_sync(~0u, threadIdx.x >> 5, 0), lane = threadIdx.x & 31;
    const int nt = blockIdx.x & 7, mt = blockIdx.x >> 3;
    const int tile = warp < 8 ? warp : nt;
    const int wg = tile >> 2;
    CK(0);
    pdl_launch();
    uint32_t* s_wr = (uint32_t*)(smem + 131072 + 4 * 24576 + 256);
    if (warp == 8) {
        if (lane == 0) {
            for (int i = 0; i < 4; i++) { mbar_init(sBar + i * 8, 1); mbar_init(sBar + 48 + i * 8, 2); }
            asm volatile("fence.mbarrier_init.release.cluster;" ::: "memory");
            for (int i = 0; i < 4; i++) mbar_expect_tx(sBar + i * 8, 24576);
        }
        if (lane < 4) {
            mbar_init(sBar + 96 + lane * 8, 1);
            asm volatile("fence.mbarrier_init.release.cluster;" ::: "memory");
            mbar_expect_tx(sBar + 96 + lane * 8, 32768);
        }
        __syncwarp();
        if (lane < 16) {
            const int pn = (lane >> 3) * 4 + (lane & 3), hf = (lane >> 2) & 1;
            tma_2d(sA + pn * 16384 + hf * 8192, &xmap, pn * 64, mt * 128 + hf * 64, sBar + 96 + (lane >> 2) * 8);
        }
        named_bar(3, K1_THREADS);
        mbar_wait(sBar + 96 + 8, 0);
        if (lane < 12) {
            const int ld = lane / 3, j = lane % 3;
            tma_2d(sB + ld * 24576 + j * 8192, &wmap, nt * 192 + j * 64, ld * 64, sBar + ld * 8);
        }
        __syncwarp();
        if (lane < 3) {
            for (int ld = 4; ld < 8; ld++) {
                const int sl = ld - 4;
                mbar_wait(sBar + 48 + sl * 8, 0);
                if (lane == 0) mbar_expect_tx(sBar + sl * 8, 24576);
                __syncwarp(7);
                tma_2d(sB + sl * 24576 + lane * 8192, &wmap, nt * 192 + lane * 64, ld * 64, sBar + sl * 8);
            }
        }
        return;
    }
    if (warp == 9) {
        #pragma unroll
        for (int i = 0; i < 8; i++) s_wr[i * 32 + lane] = __ldg((const uint32_t*)w_r + i * 32 + lane);
    }
    named_bar(3, K1_THREADS);
    const int g = lane >> 2, t = lane & 3;
    const int lrow = tile * 16 + (lane & 7) + ((lane >> 3) & 1) * 8;
    const uint32_t lbase = sA + lrow * 128;
    const int lsw = lane & 7, lhi = lane >> 4;
    uint32_t laddr[4];
    #pragma unroll
    for (int k4 = 0; k4 < 4; k4++) laddr[k4] = lbase + (((k4 * 2 + lhi) ^ lsw) * 16);
    CK(1);
    float dsum[4] = {0.f, 0.f, 0.f, 0.f}, dq0[4] = {0.f, 0.f, 0.f, 0.f}, dq1[4] = {0.f, 0.f, 0.f, 0.f};
    float esum[4] = {0.f, 0.f, 0.f, 0.f}, eq0[4] = {0.f, 0.f, 0.f, 0.f}, eq1[4] = {0.f, 0.f, 0.f, 0.f};
    #pragma unroll 2
    for (int pn = 0; pn < 8; pn++) {
        uint32_t a[4][4];
        if ((pn & 3) == 0) mbar_wait(sBar + 96 + ((pn >> 2) * 2 + wg) * 8, 0);
        #pragma unroll
        for (int k4 = 0; k4 < 4; k4++) ldsm4(a[k4], laddr[k4] + pn * 16384);
        #pragma unroll
        for (int k4 = 0; k4 < 4; k4 += 2) {
            mma16816(dsum, a[k4], 0x3F803F80u, 0x3F803F80u);
            mma16816(dq0, a[k4], a[k4][0], a[k4][2]);
            mma16816(dq1, a[k4], a[k4][1], a[k4][3]);
            mma16816(esum, a[k4 + 1], 0x3F803F80u, 0x3F803F80u);
            mma16816(eq0, a[k4 + 1], a[k4 + 1][0], a[k4 + 1][2]);
            mma16816(eq1, a[k4 + 1], a[k4 + 1][1], a[k4 + 1][3]);
        }
    }
    #pragma unroll
    for (int i = 0; i < 4; i++) { dsum[i] += esum[i]; dq0[i] += eq0[i]; dq1[i] += eq1[i]; }
    CK(3);
    const int dsrc = g * 4 + (g >> 1);
    const float sq0 = __shfl_sync(~0u, (g & 1) ? dq0[1] : dq0[0], dsrc), sq1 = __shfl_sync(~0u, (g & 1) ? dq1[3] : dq1[2], dsrc);
    const float mean0 = dsum[0] * (1.0f / D_), mean1 = dsum[2] * (1.0f / D_);
    float var0 = fmaf(-mean0, mean0, sq0 * (1.0f / D_)), var1 = fmaf(-mean1, mean1, sq1 * (1.0f / D_));
    if (__any_sync(~0u, !(mean0 * mean0 <= 16.0f * var0) || !(mean1 * mean1 <= 16.0f * var1))) {
        float q0 = 0.f, q1 = 0.f;
        #pragma unroll 1
        for (int ks = 0; ks < 32; ks++) {
            uint32_t a[4];
            ldsm4(a, lbase + (ks >> 2) * 16384 + ((((ks & 3) * 2 + lhi) ^ lsw) * 16));
            #pragma unroll
            for (int i = 0; i < 4; i++) {
                const float m = (i & 1) ? mean1 : mean0;
                const float d0 = bf_lo(a[i]) - m, d1 = bf_hi(a[i]) - m;
                if (i & 1) q1 = fmaf(d0, d0, fmaf(d1, d1, q1)); else q0 = fmaf(d0, d0, fmaf(d1, d1, q0));
            }
        }
        q0 += __shfl_xor_sync(~0u, q0, 1); q0 += __shfl_xor_sync(~0u, q0, 2);
        q1 += __shfl_xor_sync(~0u, q1, 1); q1 += __shfl_xor_sync(~0u, q1, 2);
        var0 = q0 * (1.0f / D_); var1 = q1 * (1.0f / D_);
    }
    const float rs0 = __frcp_rn(bf16r(__fsqrt_rn(bf16r(bf16r(var0) + 1e-5f))));
    const float rs1 = __frcp_rn(bf16r(__fsqrt_rn(bf16r(bf16r(var1) + 1e-5f))));
    const LnRow lr0 = ln_row(mean0, rs0), lr1 = ln_row(mean1, rs1);
    if (warp == 9) {
        float dr[4] = {0.f, 0.f, 0.f, 0.f}, er[4] = {0.f, 0.f, 0.f, 0.f};
        #pragma unroll 2
        for (int pn = 0; pn < 8; pn++) {
            uint32_t a[4][4];
            #pragma unroll
            for (int k4 = 0; k4 < 4; k4++) ldsm4(a[k4], laddr[k4] + pn * 16384);
            #pragma unroll
            for (int k4 = 0; k4 < 4; k4++) {
                ln_frag(a[k4], lr0, lr1);
                mma16816((k4 & 1) ? er : dr, a[k4], s_wr[(pn * 4 + k4) * 8 + t], s_wr[(pn * 4 + k4) * 8 + 4 + t]);
            }
        }
        if (t == 0) {
            const int row0 = mt * 128 + tile * 16;
            g_r[row0 + g] = bf16r(dr[0] + er[0]); g_r[row0 + g + 8] = bf16r(dr[2] + er[2]);
            g_stats[row0 + g] = make_float2(bf_lo(lr0.m2), rs0); g_stats[row0 + g + 8] = make_float2(bf_lo(lr1.m2), rs1);
        }
        asm volatile("bar.arrive %0, %1;" :: "r"(4 + wg), "r"(160) : "memory");
        return;
    }
    float acc[96];
    #pragma unroll
    for (int i = 0; i < 96; i++) acc[i] = 0.f;
    const uint64_t db0 = make_desc(sB, 8192, 1024, 1);
    uint32_t a[2][4][4];
    #pragma unroll
    for (int k4 = 0; k4 < 4; k4++) ldsm4(a[0][k4], laddr[k4]);
    #pragma unroll
    for (int k4 = 0; k4 < 4; k4++) ln_frag(a[0][k4], lr0, lr1);
    #pragma unroll 1
    for (int kc = 0; kc < 8; kc += 2) {
        #pragma unroll
        for (int h2 = 0; h2 < 2; h2++) {
            const int ld = kc + h2, sl = ld & 3;
            mbar_wait(sBar + sl * 8, ld >> 2);
            WG_FENCE();
            #pragma unroll
            for (int k4 = 0; k4 < 4; k4++) wgmma_rs_n192(acc, a[h2][k4], db0 + (uint64_t)(sl * 1536 + k4 * 128));
            WG_COMMIT();
            wg_wait<1>();
            if (ld >= 1 && ld <= 4 && (threadIdx.x & 127) == 0) mbar_arrive(sBar + 48 + (ld - 1) * 8);
            #pragma unroll
            for (int k4 = 0; k4 < 4; k4++) ldsm4(a[h2 ^ 1][k4], laddr[k4] + ((ld + 1) & 7) * 16384);
            #pragma unroll
            for (int k4 = 0; k4 < 4; k4++) ln_frag(a[h2 ^ 1][k4], lr0, lr1);
        }
    }
    wg_wait<0>();
    touch96(acc);
    CK(4);
    if ((nt >> 2) == wg) named_bar(4 + wg, 160); else named_bar(1 + wg, 128);
    k1_store<4>(acc, 0, sA + wg * 8192, nt, mt, wg, warp & 3, lane);
    k1_store<4>(acc + 32, 4, sA + 16384 + wg * 8192, nt, mt, wg, warp & 3, lane);
    k1_store<4>(acc + 64, 8, sA + 32768 + wg * 8192, nt, mt, wg, warp & 3, lane);
    CK(5);
    asm volatile("cp.async.bulk.wait_group.read 0;" ::: "memory");
    CK(6);
}

constexpr int K2_THREADS = 512;
constexpr int K2_SMEM = 6 * 32768 + 12288;

constexpr float QS = 0.25f * 1.4426950408889634f;
constexpr float SC100 = 1.2676506002282294e30f;
__device__ __forceinline__ uint32_t polyexp2(float s0, float s1, float cd, uint32_t one2, uint32_t ca2) {
    constexpr float A = 128.0f * QS * 1.7763568394002505e-15f;
    float t0, t1;
    asm("fma.rn.f32 %0, %1, %2, %3;" : "=f"(t0) : "f"(s0), "f"(A), "f"(cd));
    asm("fma.rn.f32 %0, %1, %2, %3;" : "=f"(t1) : "f"(s1), "f"(A), "f"(cd));
    uint32_t W, U, h, G;
    asm("cvt.pack.sat.s16.s32 %0, %1, %2;" : "=r"(W) : "r"(__float_as_int(t1)), "r"(__float_as_int(t0)));
    asm("lop3.b32 %0, %1, 0x007F007F, %2, 0xEA;" : "=r"(U) : "r"(W), "r"(one2));
    asm("fma.rn.bf16x2 %0, %1, %2, %3;" : "=r"(h) : "r"(U), "r"(ca2), "r"(0xC300C300u));
    asm("fma.rn.bf16x2 %0, %1, %2, %3;" : "=r"(G) : "r"(h), "r"(U), "r"(0x438B438Bu));
    return W + G - 0x43404340u;
}

struct ExpC { float nm0, nm1, cd0, cd1; uint32_t one2, ca2; };

template <int G>
__device__ __forceinline__ void exp_block(const float* s, uint32_t* p, const ExpC& c) {
    #pragma unroll
    for (int hf = 0; hf < 2; hf++) {
        const float* x = s + hf * 4;
        if ((PMASK >> (G + hf)) & 1) {
            p[hf * 2 + 0] = polyexp2(x[0], x[1], c.cd0, c.one2, c.ca2);
            p[hf * 2 + 1] = polyexp2(x[2], x[3], c.cd1, c.one2, c.ca2);
        } else {
            p[hf * 2 + 0] = pack_bf16(ex2(fmaf(x[0], QS * SC100, c.nm0)), ex2(fmaf(x[1], QS * SC100, c.nm0)));
            p[hf * 2 + 1] = pack_bf16(ex2(fmaf(x[2], QS * SC100, c.nm1)), ex2(fmaf(x[3], QS * SC100, c.nm1)));
        }
    }
}

__device__ __forceinline__ void max16(const float* s, float& mx0, float& mx1) {
    #pragma unroll
    for (int j = 0; j < 4; j++) {
        mx0 = fmaxf(mx0, fmaxf(s[4 * j], s[4 * j + 1]));
        mx1 = fmaxf(mx1, fmaxf(s[4 * j + 2], s[4 * j + 3]));
    }
}

constexpr int MOE_SLOTS = 6, MOE_BOXES = 44;
__device__ __forceinline__ void moe_load(int b, int part, uint32_t ring, uint32_t bars, const CUtensorMap* mg, const CUtensorMap* mu, const CUtensorMap* md) {
    const int sl = b % MOE_SLOTS, grp = b & 1;
    if (b < 28) {
        const int j = b >> 1;
        mbar_expect_tx(bars + sl * 8, 32768);
        tma_2d(ring + sl * 32768, grp ? mu : mg, part * 448 + (j >> 1) * 64, (j & 1) * 256, bars + sl * 8);
    } else {
        const int j = (b - 28) >> 1;
        mbar_expect_tx(bars + sl * 8, 28672);
        tma_2d(ring + sl * 32768, md, ((j >> 1) * 2 + grp) * 64, part * 448 + (j & 1) * 224, bars + sl * 8);
    }
}
__device__ __forceinline__ void mma_2row(float* d, uint32_t a0, uint32_t a2, uint32_t b0, uint32_t b1) {
    asm("mma.sync.aligned.m16n8k16.row.col.f32.bf16.bf16.f32 {%0,%1,%2,%3}, {%4,%5,%6,%5}, {%7,%8}, {%0,%1,%2,%3};"
        : "+f"(d[0]), "+f"(d[1]), "+f"(d[2]), "+f"(d[3]) : "r"(a0), "r"(0u), "r"(a2), "r"(b0), "r"(b1));
}

__device__ void moe_cta(int part, unsigned char* smem, const __nv_bfloat16* __restrict__ x, const CUtensorMap* mg, const CUtensorMap* mu, const CUtensorMap* md) {
    const uint32_t ring = smem_u32(smem), bars = ring + MOE_SLOTS * 32768;
    __nv_bfloat16* xs = (__nv_bfloat16*)(smem + MOE_SLOTS * 32768 + 256);
    float* gu = (float*)(smem + MOE_SLOTS * 32768 + 256 + 2048);
    float* s_v = gu + 4 * 448;
    int* s_i = (int*)(s_v + 16);
    int* s_sel = s_i + 16;
    const int tid = threadIdx.x, warp = __shfl_sync(~0u, tid >> 5, 0), lane = tid & 31;
    if (tid == 0) {
        for (int i = 0; i < MOE_SLOTS; i++) { mbar_init(bars + i * 8, 1); mbar_init(bars + 128 + i * 8, 8); }
        asm volatile("fence.mbarrier_init.release.cluster;" ::: "memory");
        for (int b = 0; b < MOE_SLOTS; b++) moe_load(b, part, ring, bars, mg, mu, md);
    }
    pdl_wait();
    TL(1, 1);
    float rv[4];
    #pragma unroll
    for (int i = 0; i < 4; i++) rv[i] = g_r[tid + i * K2_THREADS];
    for (int pass = 0; pass < 2; pass++) {
        float bv = -INFINITY; int bi = 0x7fffffff;
        const int excl = pass ? s_sel[0] : -1;
        #pragma unroll
        for (int i = 0; i < 4; i++) {
            const int idx = tid + i * K2_THREADS;
            if (idx != excl && (rv[i] > bv || bi == 0x7fffffff)) { bv = rv[i]; bi = idx; }
        }
        #pragma unroll
        for (int o = 16; o; o >>= 1) {
            float ov = __shfl_xor_sync(~0u, bv, o); int oi = __shfl_xor_sync(~0u, bi, o);
            if (ov > bv || (ov == bv && oi < bi)) { bv = ov; bi = oi; }
        }
        if (lane == 0) { s_v[warp] = bv; s_i[warp] = bi; }
        __syncthreads();
        if (warp == 0) {
            bv = lane < 16 ? s_v[lane] : -INFINITY; bi = lane < 16 ? s_i[lane] : 0x7fffffff;
            #pragma unroll
            for (int o = 16; o; o >>= 1) {
                float ov = __shfl_xor_sync(~0u, bv, o); int oi = __shfl_xor_sync(~0u, bi, o);
                if (ov > bv || (ov == bv && oi < bi)) { bv = ov; bi = oi; }
            }
            if (lane == 0) s_sel[pass] = (bi == 0x7fffffff) ? pass : bi;
        }
        __syncthreads();
    }
    for (int i = tid; i < 1024; i += K2_THREADS) {
        const int tok = s_sel[i >> 9];
        const float2 st = g_stats[tok];
        xs[i] = __float2bfloat16_rn(ln_elem(__bfloat162float(x[(size_t)tok * D_ + (i & 511)]), st.x, st.y));
    }
    if (part == 0 && tid < 2) g_sel[tid] = s_sel[tid];
    __syncthreads();
    if (warp == 8) {
        if (lane == 0) {
            for (int b = MOE_SLOTS; b < MOE_BOXES; b++) {
                mbar_wait(bars + 128 + (b % MOE_SLOTS) * 8, (b / MOE_SLOTS - 1) & 1);
                moe_load(b, part, ring, bars, mg, mu, md);
            }
        }
        return;
    }
    if (warp > 8) return;
    const int nj = warp, g = lane >> 2, t = lane & 3;
    const uint32_t* xw = (const uint32_t*)xs + (g & 1) * 256 + t;
    uint32_t a[2][32];
    #pragma unroll
    for (int i = 0; i < 32; i++) { a[0][i] = xw[i * 4]; a[1][i] = xw[128 + i * 4]; }
    #pragma unroll 1
    for (int jp = 0; jp < MOE_BOXES / 4; jp++) {
        const bool down = jp >= 7;
        if (jp == 7) {
            named_bar(1, 256);
            for (int i = tid; i < 896; i += 256) {
                const float gs = bf16r(gu[i]), us = bf16r(gu[896 + i]);
                const float sl_ = bf16r(gs / (1.0f + __expf(-gs)));
                xs[(i / 448) * 512 + (i % 448)] = __float2bfloat16_rn(sl_ * us);
            }
            named_bar(1, 256);
            #pragma unroll
            for (int i = 0; i < 28; i++) { a[0][i] = xw[i * 4]; a[1][i] = xw[112 + i * 4]; }
        }
        float acc[2][4] = {{0.f, 0.f, 0.f, 0.f}, {0.f, 0.f, 0.f, 0.f}}, acb[2][4] = {{0.f, 0.f, 0.f, 0.f}, {0.f, 0.f, 0.f, 0.f}};
        #pragma unroll
        for (int q = 0; q < 4; q++) {
            const int hf = q >> 1, grp = q & 1;
            const int b = jp * 4 + q, sl = b % MOE_SLOTS;
            mbar_wait(bars + sl * 8, (b / MOE_SLOTS) & 1);
            const uint32_t baddr = ring + sl * 32768 + lane * 128 + ((nj ^ (lane & 7)) * 16);
            #pragma unroll
            for (int k4 = 0; k4 < 2; k4++) {
                uint32_t bf[4][4];
                #pragma unroll
                for (int k2 = 0; k2 < 4; k2++)
                    asm volatile("ldmatrix.sync.aligned.m8n8.x4.trans.shared.b16 {%0, %1, %2, %3}, [%4];"
                                 : "=r"(bf[k2][0]), "=r"(bf[k2][1]), "=r"(bf[k2][2]), "=r"(bf[k2][3]) : "r"(baddr + (k4 * 4 + k2) * 4096) : "memory");
                #pragma unroll
                for (int k2 = 0; k2 < 4; k2++) {
                    const int kk = k4 * 4 + k2;
                    if (kk < 7 || !down) {
                        mma_2row(acc[grp], a[hf][4 * kk], a[hf][4 * kk + 1], bf[k2][0], bf[k2][1]);
                        mma_2row(acb[grp], a[hf][4 * kk + 2], a[hf][4 * kk + 3], bf[k2][2], bf[k2][3]);
                    }
                }
            }
            __syncwarp();
            if (lane == 0) mbar_arrive(bars + 128 + sl * 8);
        }
        if (g < 2) {
            #pragma unroll
            for (int grp = 0; grp < 2; grp++) {
                const float2 v = make_float2(acc[grp][0] + acb[grp][0], acc[grp][1] + acb[grp][1]);
                if (!down) *(float2*)&gu[(grp * 2 + g) * 448 + jp * 64 + nj * 8 + t * 2] = v;
                else *(float2*)&g_ypart[part][g][((jp - 7) * 2 + grp) * 64 + nj * 8 + t * 2] = v;
            }
        }
    }
}

__global__ void __launch_bounds__(K2_THREADS, 1)
k2_attn(const __nv_bfloat16* __restrict__ x, const __nv_bfloat16* __restrict__ w_gate, const __nv_bfloat16* __restrict__ w_up,
        const __nv_bfloat16* __restrict__ w_down, const __grid_constant__ CUtensorMap mg, const __grid_constant__ CUtensorMap mu,
        const __grid_constant__ CUtensorMap md) {
    extern __shared__ __align__(1024) unsigned char smem[];
    TL(1, 0);
    pdl_launch();
    if (blockIdx.x >= 128) { moe_cta(blockIdx.x - 128, smem, x, &mg, &mu, &md); TL(1, 2); return; }
    if (threadIdx.x >= 32 && threadIdx.x < 35) {
        const __nv_bfloat16* w = threadIdx.x == 32 ? w_gate : (threadIdx.x == 33 ? w_up : w_down);
        asm volatile("cp.async.bulk.prefetch.L2.global [%0], %1;" :: "l"(w + (size_t)blockIdx.x * (D_ * F_ / 128)), "r"(D_ * F_ / 64) : "memory");
    }
    const uint32_t sK = smem_u32(smem), sV = sK + 65536, sQ = sV + 98304, sBar = sQ + 16384;
    const int h = blockIdx.x >> 2, qb = blockIdx.x & 3;
    const int warp = __shfl_sync(~0u, threadIdx.x >> 5, 0), lane = threadIdx.x & 31, wg = warp >> 2;
    if (threadIdx.x == 0) {
        mbar_init(sBar, 1); mbar_init(sBar + 8, 1);
        asm volatile("fence.mbarrier_init.release.cluster;" ::: "memory");
        mbar_expect_tx(sBar, 8192 + 12288 + 2 * 6144);
        mbar_expect_tx(sBar + 8, 8192 + 53248 + 2 * 26624);
    }
    for (int i = threadIdx.x; i < 2048; i += K2_THREADS)
        *(uint4*)(smem + 65536 + 65536 + i * 16) = make_uint4(0x3F803F80u, 0x3F803F80u, 0x3F803F80u, 0x3F803F80u);
    fence_async_smem();
    __syncthreads();
    if (warp == 0) {
        pdl_wait();
        TL(1, 1);
        const uint4* gk = g_K + (size_t)h * 4096;
        const uint4* gv = g_V + (size_t)h * 4096;
        const uint4* gq = g_Q + (size_t)h * 4096 + qb * 1024;
        if (lane == 0) bulk_g2s(sQ, gq, 8192, sBar);
        if (lane == 1) bulk_g2s(sK, gk, 12288, sBar);
        if (lane == 2) bulk_g2s(sV, gv, 6144, sBar);
        if (lane == 3) bulk_g2s(sV + 32768, gv + 2048, 6144, sBar);
        if (lane == 4) bulk_g2s(sK + 12288, gk + 768, 53248, sBar + 8);
        if (lane == 5) bulk_g2s(sV + 6144, gv + 384, 26624, sBar + 8);
        if (lane == 6) bulk_g2s(sV + 32768 + 6144, gv + 2048 + 384, 26624, sBar + 8);
        if (lane == 7) bulk_g2s(sQ + 8192, gq + 512, 8192, sBar + 8);
        __syncwarp();
    }
    ExpC c;
    {
        const volatile uint32_t* cc = g_const;
        c.one2 = cc[0]; c.ca2 = cc[1];
    }
    const uint64_t kdesc0 = make_desc(sK, 128, 256, 0);
    const uint64_t vdesc0 = make_desc(sV, 128, 32768, 0);
    #pragma unroll 1
    for (int pass = 0; pass < 2; pass++) {
        const bool dry = false;
        if (pass == 0) { mbar_wait(sBar, 0); __syncwarp(); TL(1, 2); }
        const int unit = (pass & 1) * 4 + wg;
        const uint64_t q = make_desc(sQ + unit * 2048, 128, 256, 0);
        float o[12];
        #pragma unroll 1
        for (int attempt = 0; attempt < 2; attempt++) {
            float s0[16], s1[16], s2[16];
            #pragma unroll
            for (int i = 0; i < 16; i++) { s0[i] = 0.f; s1[i] = 0.f; s2[i] = 0.f; }
            float mx0 = -INFINITY, mx1 = -INFINITY;
            if (attempt) {
                #pragma unroll 1
                for (int it = 0; it < 64; it++) {
                    WG_FENCE();
                    wgmma_qk32(s0, q, kdesc0 + it * 64);
                    WG_COMMIT();
                    wg_wait<0>();
                    touch16(s0);
                    max16(s0, mx0, mx1);
                }
            }
            #pragma unroll
            for (int i = 0; i < 12; i++) o[i] = 0.f;
            WG_FENCE();
            wgmma_qk32(s2, q, kdesc0);
            wgmma_qk32(s0, q, kdesc0 + 64);
            wgmma_qk32(s1, q, kdesc0 + 128);
            WG_COMMIT();
            wg_wait<0>();
            touch16(s0); touch16(s1); touch16(s2);
            max16(s0, mx0, mx1); max16(s1, mx0, mx1); max16(s2, mx0, mx1);
            mx0 = fmaxf(mx0, __shfl_xor_sync(~0u, mx0, 1)); mx0 = fmaxf(mx0, __shfl_xor_sync(~0u, mx0, 2));
            mx1 = fmaxf(mx1, __shfl_xor_sync(~0u, mx1, 1)); mx1 = fmaxf(mx1, __shfl_xor_sync(~0u, mx1, 2));
            const float bias = attempt ? 0.0f : 128.0f * 64.0f;
            const float y0 = ceilf(fmaf(mx0, 128.0f * QS * SC100, bias)), y1 = ceilf(fmaf(mx1, 128.0f * QS * SC100, bias));
            c.nm0 = __shfl_sync(~0u, y0 * (-1.0f / 128.0f), lane); c.nm1 = __shfl_sync(~0u, y1 * (-1.0f / 128.0f), lane);
            c.cd0 = __shfl_sync(~0u, __fmul_rn(16256.0f - y0, __int_as_float(1)), lane);
            c.cd1 = __shfl_sync(~0u, __fmul_rn(16256.0f - y1, __int_as_float(1)), lane);
            uint64_t kd = kdesc0 + 192, vd = vdesc0 + 32;
            {
                uint32_t pa[4], pb[4];
                exp_block<12>(s2, pa, c);
                exp_block<14>(s2 + 8, pb, c);
                WG_FENCE();
                wgmma_pv(o, pa, vdesc0); wgmma_pv(o, pb, vdesc0 + 16);
                WG_COMMIT();
            }
            #pragma unroll 1
            for (int seg = 0; seg < (dry ? 1 : 2); seg++) {
            if (seg) { wg_wait<0>(); mbar_wait(sBar + 8, 0); __syncwarp(); }
            #pragma unroll 1
            for (int it = seg ? 3 : (dry ? 2 : 0); it < (seg ? 21 : 3); it++) {
                uint32_t p[6][4];
                WG_FENCE();
                wgmma_qk32(s2, q, kd);
                WG_COMMIT();
                exp_block<0>(s0, p[0], c);
                exp_block<2>(s0 + 8, p[1], c);
                WG_FENCE();
                wgmma_pv(o, p[0], vd); wgmma_pv(o, p[1], vd + 16);
                wgmma_qk32(s0, q, kd + 64);
                WG_COMMIT();
                wg_wait<1>();
                touch16(s2);
                exp_block<4>(s1, p[2], c);
                exp_block<6>(s1 + 8, p[3], c);
                WG_FENCE();
                wgmma_pv(o, p[2], vd + 32); wgmma_pv(o, p[3], vd + 48);
                wgmma_qk32(s1, q, kd + 128);
                WG_COMMIT();
                wg_wait<1>();
                touch16(s0);
                exp_block<8>(s2, p[4], c);
                exp_block<10>(s2 + 8, p[5], c);
                WG_FENCE();
                wgmma_pv(o, p[4], vd + 64); wgmma_pv(o, p[5], vd + 80);
                WG_COMMIT();
                vd += 96; kd += 192;
                wg_wait<1>();
                touch16(s1);
            }
            }
            wg_wait<0>();
            touch12(o);
            if (attempt) break;
            float big = 0.f;
            #pragma unroll
            for (int i = 0; i < 12; i++) big = fmaxf(big, fabsf(o[i]));
            bool bad = !(big < 1e30f);
            #pragma unroll
            for (int i = 0; i < 12; i++) bad |= (o[i] != o[i]);
            uint32_t any;
            asm volatile("{.reg .pred p, q; setp.ne.u32 p, %1, 0; barrier.cta.red.or.pred.aligned q, %2, 128, p; selp.u32 %0, 1, 0, q;}"
                         : "=r"(any) : "r"((uint32_t)bad), "r"(1 + wg) : "memory");
            if (dry || !__any_sync(~0u, any)) break;
        }
        const int g = lane >> 2, t = lane & 3;
        const int r = (warp & 3) * 16 + g;
        const float i0 = __fdiv_rn(1.0f, o[8]), i1 = __fdiv_rn(1.0f, o[10]);
        uint32_t* ob = (uint32_t*)(g_O + (size_t)(qb * 8 + unit) * 4096 + (h >> 2) * 512 + r * 8) + t;
        const int c0 = ((h & 3) * 2) ^ (r & 7), c1 = ((h & 3) * 2 + 1) ^ (r & 7);
        if (!dry) {
            ob[c0 * 4] = pack_bf16(o[0] * i0, o[1] * i0);
            ob[c1 * 4] = pack_bf16(o[4] * i0, o[5] * i0);
            ob[256 + c0 * 4] = pack_bf16(o[2] * i1, o[3] * i1);
            ob[256 + c1 * 4] = pack_bf16(o[6] * i1, o[7] * i1);
            TL(1, 3 + pass);
        }
    }
}

constexpr int K3_THREADS = 256;
constexpr int K3_SMEM = 65536 + 131072 + 128;

__global__ void __launch_bounds__(K3_THREADS, 1)
k3_out(const __grid_constant__ CUtensorMap wmap, const __nv_bfloat16* __restrict__ x, __nv_bfloat16* __restrict__ out) {
    extern __shared__ __align__(1024) unsigned char smem[];
    const uint32_t sA = smem_u32(smem), sB = sA + 65536, sBar = sB + 131072;
    const int warp = __shfl_sync(~0u, threadIdx.x >> 5, 0), lane = threadIdx.x & 31, wg = warp >> 2;
    const int nt = blockIdx.x & 3, mt = blockIdx.x >> 2;
    TL(2, 0);
    if (threadIdx.x == 0) {
        for (int i = 0; i < 10; i++) mbar_init(sBar + i * 8, 1);
        asm volatile("fence.mbarrier_init.release.cluster;" ::: "memory");
        for (int i = 0; i < 8; i++) mbar_expect_tx(sBar + 16 + i * 8, 8192);
        for (int kh = 0; kh < 2; kh++) {
            mbar_expect_tx(sBar + kh * 8, 65536);
            tma_2d(sB + kh * 32768, &wmap, nt * 128, kh * 256, sBar + kh * 8);
            tma_2d(sB + 65536 + kh * 32768, &wmap, nt * 128 + 64, kh * 256, sBar + kh * 8);
        }
    }
    const int er = threadIdx.x >> 2, ec = (threadIdx.x & 3) * 32;
    const int row = mt * 64 + er;
    uint4 xv[4];
    #pragma unroll
    for (int j = 0; j < 4; j++) xv[j] = __ldg((const uint4*)(x + (size_t)row * D_ + nt * 128 + ec) + j);
    __syncthreads();
    pdl_wait();
    TL(2, 1);
    if (threadIdx.x < 8) bulk_g2s(sA + threadIdx.x * 8192, g_O + (size_t)mt * 4096 + threadIdx.x * 512, 8192, sBar + 16 + threadIdx.x * 8);
    const int sel0 = g_sel[0], sel1 = g_sel[1];
    const float2 st = g_stats[row];
    uint32_t bb[16];
    {
        const uint32_t xu[16] = {xv[0].x, xv[0].y, xv[0].z, xv[0].w, xv[1].x, xv[1].y, xv[1].z, xv[1].w,
                                 xv[2].x, xv[2].y, xv[2].z, xv[2].w, xv[3].x, xv[3].y, xv[3].z, xv[3].w};
        #pragma unroll
        for (int j = 0; j < 16; j++) bb[j] = pack_bf16(bf16r(bf_lo(xu[j]) - st.x) * st.y, bf16r(bf_hi(xu[j]) - st.x) * st.y);
        const int slot = row == sel0 ? 0 : (row == sel1 ? 1 : -1);
        if (slot >= 0) {
            const float gate = bf16r(1.0f / (1.0f + __expf(-g_r[row])));
            const int c0 = nt * 128 + ec;
            #pragma unroll
            for (int j = 0; j < 16; j++) {
                const float2 a = *(const float2*)&g_ypart[0][slot][c0 + 2 * j], b = *(const float2*)&g_ypart[1][slot][c0 + 2 * j];
                const float2 c = *(const float2*)&g_ypart[2][slot][c0 + 2 * j], d = *(const float2*)&g_ypart[3][slot][c0 + 2 * j];
                bb[j] = pack_bf16(bf_lo(bb[j]) + bf16r(bf16r(a.x + b.x + c.x + d.x) * gate), bf_hi(bb[j]) + bf16r(bf16r(a.y + b.y + c.y + d.y) * gate));
            }
        }
    }
    float acc[32];
    #pragma unroll
    for (int i = 0; i < 32; i++) acc[i] = 0.f;
    const uint64_t da0 = make_desc(sA, 16, 1024, 1);
    const uint64_t db0 = make_desc(sB + wg * 65536, 8192, 1024, 1);
    #pragma unroll 1
    for (int q = 0; q < 8; q++) {
        if ((q & 3) == 0) mbar_wait(sBar + (q >> 2) * 8, 0);
        mbar_wait(sBar + 16 + q * 8, 0);
        WG_FENCE();
        #pragma unroll
        for (int kk = 0; kk < 4; kk++)
            wgmma_n64(acc, da0 + (uint64_t)(q * 512 + kk * 2), db0 + (uint64_t)(q * 512 + kk * 128));
        WG_COMMIT();
    }
    wg_wait<0>();
    touch32(acc);
    TL(2, 2);
    __syncthreads();
    {
        const int g = lane >> 2, t = lane & 3;
        unsigned char* sp = smem + ((warp & 3) * 16 + g) * 272 + wg * 128 + t * 4;
        #pragma unroll
        for (int j = 0; j < 8; j++) {
            *(uint32_t*)(sp + j * 16) = pack_bf16(acc[4 * j], acc[4 * j + 1]);
            *(uint32_t*)(sp + 8 * 272 + j * 16) = pack_bf16(acc[4 * j + 2], acc[4 * j + 3]);
        }
    }
    __syncthreads();
    #pragma unroll
    for (int j = 0; j < 4; j++) {
        const uint4 av = *(const uint4*)(smem + er * 272 + ec * 2 + j * 16);
        const uint32_t au[4] = {av.x, av.y, av.z, av.w}, xu[4] = {xv[j].x, xv[j].y, xv[j].z, xv[j].w};
        uint32_t o[4];
        #pragma unroll
        for (int i = 0; i < 4; i++) {
            uint32_t t2;
            asm("add.rn.bf16x2 %0, %1, %2;" : "=r"(t2) : "r"(xu[i]), "r"(au[i]));
            asm("add.rn.bf16x2 %0, %1, %2;" : "=r"(o[i]) : "r"(t2), "r"(bb[j * 4 + i]));
        }
        *((uint4*)(out + (size_t)row * D_ + nt * 128 + ec) + j) = make_uint4(o[0], o[1], o[2], o[3]);
    }
    TL(2, 3);
}

typedef CUresult (*EncodeFn)(CUtensorMap*, CUtensorMapDataType, cuuint32_t, void*, const cuuint64_t*, const cuuint64_t*,
                             const cuuint32_t*, const cuuint32_t*, CUtensorMapInterleave, CUtensorMapSwizzle,
                             CUtensorMapL2promotion, CUtensorMapFloatOOBfill);

void make_wmap(EncodeFn fn, CUtensorMap* map, const void* ptr, int rows, int cols, int box_rows) {
    cuuint64_t dims[2] = {(cuuint64_t)cols, (cuuint64_t)rows};
    cuuint64_t strides[1] = {(cuuint64_t)cols * 2};
    cuuint32_t box[2] = {64, (cuuint32_t)box_rows};
    cuuint32_t es[2] = {1, 1};
    fn(map, CU_TENSOR_MAP_DATA_TYPE_BFLOAT16, 2, (void*)ptr, dims, strides, box, es, CU_TENSOR_MAP_INTERLEAVE_NONE,
       CU_TENSOR_MAP_SWIZZLE_128B, CU_TENSOR_MAP_L2_PROMOTION_L2_256B, CU_TENSOR_MAP_FLOAT_OOB_FILL_NONE);
}

}

extern "C" void kernel_launch(void* const* d_in, const int* in_sizes, int n_in, void* d_out, int out_size) {
    const __nv_bfloat16* x = (const __nv_bfloat16*)d_in[0];
    const __nv_bfloat16* wqkv = (const __nv_bfloat16*)d_in[1];
    const __nv_bfloat16* wo = (const __nv_bfloat16*)d_in[2];
    const __nv_bfloat16* w_r = (const __nv_bfloat16*)d_in[4];
    const __nv_bfloat16* w_gate = (const __nv_bfloat16*)d_in[5];
    const __nv_bfloat16* w_up = (const __nv_bfloat16*)d_in[6];
    const __nv_bfloat16* w_down = (const __nv_bfloat16*)d_in[7];
    __nv_bfloat16* out = (__nv_bfloat16*)d_out;

    static EncodeFn encode = nullptr;
    if (!encode) {
        void* fn = nullptr;
        cudaDriverEntryPointQueryResult qres;
        cudaGetDriverEntryPoint("cuTensorMapEncodeTiled", &fn, cudaEnableDefault, &qres);
        encode = (EncodeFn)fn;
        cudaFuncSetAttribute(k1_ln_qkv, cudaFuncAttributeMaxDynamicSharedMemorySize, K1_SMEM);
        cudaFuncSetAttribute(k2_attn, cudaFuncAttributeMaxDynamicSharedMemorySize, K2_SMEM);
        cudaFuncSetAttribute(k3_out, cudaFuncAttributeMaxDynamicSharedMemorySize, K3_SMEM);
    }
    CUtensorMap map_qkv, map_wo, map_x, map_g, map_u, map_d;
    make_wmap(encode, &map_g, w_gate, D_, F_, 256);
    make_wmap(encode, &map_u, w_up, D_, F_, 256);
    make_wmap(encode, &map_d, w_down, F_, D_, 224);
    make_wmap(encode, &map_x, x, S_, D_, 64);
    make_wmap(encode, &map_qkv, wqkv, D_, 3 * D_, 64);
    make_wmap(encode, &map_wo, wo, D_, D_, 256);

    k1_ln_qkv<<<128, K1_THREADS, K1_SMEM, cudaStreamPerThread>>>(map_qkv, map_x, w_r);
    cudaLaunchAttribute at[1];
    at[0].id = cudaLaunchAttributeProgrammaticStreamSerialization;
    at[0].val.programmaticStreamSerializationAllowed = 1;
    cudaLaunchConfig_t cfg = {};
    cfg.stream = cudaStreamPerThread;
    cfg.attrs = at; cfg.numAttrs = 1;
    cfg.gridDim = dim3(132); cfg.blockDim = dim3(K2_THREADS); cfg.dynamicSmemBytes = K2_SMEM;
    cudaLaunchKernelEx(&cfg, k2_attn, x, w_gate, w_up, w_down, map_g, map_u, map_d);
    cfg.gridDim = dim3(128); cfg.blockDim = dim3(K3_THREADS); cfg.dynamicSmemBytes = K3_SMEM;
    cudaLaunchKernelEx(&cfg, k3_out, map_wo, x, out);
}
```

```cpp
#include <cuda_runtime.h>
#include <cuda_bf16.h>
#include <cuda.h>
#include <stdint.h>

namespace {

constexpr int S_ = 2048, D_ = 512, H_ = 32, F_ = 1792;

constexpr uint32_t PMASK = 0xDB6;

__device__ __align__(1024) uint4 g_QKV[3 * H_ * S_ * 2];
#define g_Q (g_QKV)
#define g_K (g_QKV + H_ * S_ * 2)
#define g_V (g_QKV + 2 * H_ * S_ * 2)
__device__ __align__(1024) uint4 g_O[S_ * D_ / 8];
__device__ float2 g_stats[S_];
__device__ uint32_t g_const[2] = {0x3F803F80u, 0x42294229u};
__device__ float g_r[S_];
__device__ __align__(16) float g_ypart[4][2][D_];
__device__ int g_sel[2];

#define TL(k, p)
#define CK(i)
__device__ __forceinline__ uint32_t smem_u32(const void* p) { return (uint32_t)__cvta_generic_to_shared(p); }
__device__ __forceinline__ float bf16r(float x) { return __bfloat162float(__float2bfloat16_rn(x)); }
__device__ __forceinline__ uint32_t pack_bf16(float lo, float hi) {
    uint32_t r; asm("cvt.rn.bf16x2.f32 %0, %1, %2;" : "=r"(r) : "f"(hi), "f"(lo)); return r;
}
__device__ __forceinline__ float bf_lo(uint32_t u) { return __uint_as_float(u << 16); }
__device__ __forceinline__ float bf_hi(uint32_t u) { return __uint_as_float(u & 0xFFFF0000u); }
__device__ __forceinline__ float ex2(float x) { float y; asm("ex2.approx.ftz.f32 %0, %1;" : "=f"(y) : "f"(x)); return y; }

__device__ __forceinline__ void mbar_init(uint32_t bar, uint32_t count) {
    asm volatile("mbarrier.init.shared::cta.b64 [%0], %1;" :: "r"(bar), "r"(count) : "memory");
}
__device__ __forceinline__ void mbar_expect_tx(uint32_t bar, uint32_t bytes) {
    asm volatile("mbarrier.arrive.expect_tx.shared::cta.b64 _, [%0], %1;" :: "r"(bar), "r"(bytes) : "memory");
}
__device__ __forceinline__ void mbar_arrive(uint32_t bar) {
    asm volatile("mbarrier.arrive.shared::cta.b64 _, [%0];" :: "r"(bar) : "memory");
}
__device__ __forceinline__ void mbar_wait(uint32_t bar, uint32_t parity) {
    uint32_t done;
    #pragma unroll 1
    for (int it = 0; it < (1 << 26); it++) {
        asm volatile("{.reg .pred p; mbarrier.try_wait.parity.shared::cta.b64 p, [%1], %2; selp.u32 %0, 1, 0, p;}"
                     : "=r"(done) : "r"(bar), "r"(parity) : "memory");
        if (done) return;
    }
    __trap();
}
__device__ __forceinline__ void bulk_g2s(uint32_t dst, const void* src, uint32_t bytes, uint32_t bar) {
    asm volatile("cp.async.bulk.shared::cluster.global.mbarrier::complete_tx::bytes [%0], [%1], %2, [%3];"
                 :: "r"(dst), "l"(src), "r"(bytes), "r"(bar) : "memory");
}
__device__ __forceinline__ void tma_2d(uint32_t dst, const CUtensorMap* map, int c0, int c1, uint32_t bar) {
    asm volatile("cp.async.bulk.tensor.2d.shared::cluster.global.mbarrier::complete_tx::bytes [%0], [%1, {%3, %4}], [%2];"
                 :: "r"(dst), "l"(map), "r"(bar), "r"(c0), "r"(c1) : "memory");
}
__device__ __forceinline__ void fence_async_smem() { asm volatile("fence.proxy.async.shared::cta;" ::: "memory"); }
__device__ __forceinline__ void named_bar(int id, int n) { asm volatile("bar.sync %0, %1;" :: "r"(id), "r"(n) : "memory"); }

__device__ __forceinline__ uint64_t make_desc(uint32_t saddr, uint32_t lbo, uint32_t sbo, uint32_t swz) {
    return (uint64_t)((saddr & 0x3FFFF) >> 4) | ((uint64_t)(lbo >> 4) << 16) | ((uint64_t)(sbo >> 4) << 32) | ((uint64_t)swz << 62);
}
#define WG_FENCE() asm volatile("wgmma.fence.sync.aligned;" ::: "memory")
#define WG_COMMIT() asm volatile("wgmma.commit_group.sync.aligned;" ::: "memory")
template <int N> __device__ __forceinline__ void wg_wait() { asm volatile("wgmma.wait_group.sync.aligned %0;" :: "n"(N) : "memory"); }

#define F4(d, o) "+f"(d[o]), "+f"(d[o + 1]), "+f"(d[o + 2]), "+f"(d[o + 3])
#define F16(d, o) F4(d, o), F4(d, o + 4), F4(d, o + 8), F4(d, o + 12)
#define F32(d, o) F16(d, o), F16(d, o + 16)

__device__ __forceinline__ void wgmma_rs_n192(float* d, const uint32_t* a, uint64_t db) {
    asm volatile("wgmma.mma_async.sync.aligned.m64n192k16.f32.bf16.bf16 "
        "{%0,%1,%2,%3,%4,%5,%6,%7,%8,%9,%10,%11,%12,%13,%14,%15,%16,%17,%18,%19,%20,%21,%22,%23,%24,%25,%26,%27,%28,%29,%30,%31,"
        "%32,%33,%34,%35,%36,%37,%38,%39,%40,%41,%42,%43,%44,%45,%46,%47,%48,%49,%50,%51,%52,%53,%54,%55,%56,%57,%58,%59,%60,%61,%62,%63,"
        "%64,%65,%66,%67,%68,%69,%70,%71,%72,%73,%74,%75,%76,%77,%78,%79,%80,%81,%82,%83,%84,%85,%86,%87,%88,%89,%90,%91,%92,%93,%94,%95}, "
        "{%96,%97,%98,%99}, %100, 1, 1, 1, 1;\n"
        : F32(d, 0), F32(d, 32), F32(d, 64) : "r"(a[0]), "r"(a[1]), "r"(a[2]), "r"(a[3]), "l"(db));
}
__device__ __forceinline__ void wgmma_n64(float* d, uint64_t da, uint64_t db) {
    asm volatile("wgmma.mma_async.sync.aligned.m64n64k16.f32.bf16.bf16 "
        "{%0,%1,%2,%3,%4,%5,%6,%7,%8,%9,%10,%11,%12,%13,%14,%15,%16,%17,%18,%19,%20,%21,%22,%23,%24,%25,%26,%27,%28,%29,%30,%31}, "
        "%32, %33, 1, 1, 1, 0, 1;\n"
        : F32(d, 0) : "l"(da), "l"(db));
}
__device__ __forceinline__ void wgmma_qk32(float* d, uint64_t qd, uint64_t kd) {
    asm volatile("wgmma.mma_async.sync.aligned.m64n32k16.f32.bf16.bf16 {%0,%1,%2,%3,%4,%5,%6,%7,%8,%9,%10,%11,%12,%13,%14,%15}, %16, %17, 0, 1, 1, 0, 0;\n"
        : F16(d, 0) : "l"(qd), "l"(kd));
}
__device__ __forceinline__ void wgmma_pv(float* d, const uint32_t* a, uint64_t vd) {
    asm volatile("wgmma.mma_async.sync.aligned.m64n24k16.f32.bf16.bf16 {%0,%1,%2,%3,%4,%5,%6,%7,%8,%9,%10,%11}, {%12,%13,%14,%15}, %16, 1, 1, 1, 1;\n"
        : F4(d, 0), F4(d, 4), F4(d, 8) : "r"(a[0]), "r"(a[1]), "r"(a[2]), "r"(a[3]), "l"(vd));
}
__device__ __forceinline__ void touch16(float* d) { asm volatile("" : F16(d, 0) :: "memory"); }
__device__ __forceinline__ void touch12(float* d) { asm volatile("" : F4(d, 0), F4(d, 4), F4(d, 8) :: "memory"); }
__device__ __forceinline__ void touch32(float* d) { asm volatile("" : F32(d, 0) :: "memory"); }
__device__ __forceinline__ void touch96(float* d) { asm volatile("" : F32(d, 0), F32(d, 32), F32(d, 64) :: "memory"); }

__device__ __forceinline__ float ln_elem(float x, float mean_b, float rden) {
    return bf16r(bf16r(x - mean_b) * rden);
}
__device__ __forceinline__ void pdl_wait() { asm volatile("griddepcontrol.wait;" ::: "memory"); }
__device__ __forceinline__ void pdl_launch() { asm volatile("griddepcontrol.launch_dependents;" ::: "memory"); }
__device__ __forceinline__ void cluster_arrive() { asm volatile("barrier.cluster.arrive.release.aligned;" ::: "memory"); }
__device__ __forceinline__ void cluster_wait() { asm volatile("barrier.cluster.wait.acquire.aligned;" ::: "memory"); }

constexpr int K1_THREADS = 320;
constexpr int K1_SMEM = 131072 + 6 * 16384 + 256 + 1024;

__device__ __forceinline__ void ldsm4(uint32_t* r, uint32_t addr) {
    asm volatile("ldmatrix.sync.aligned.m8n8.x4.shared.b16 {%0, %1, %2, %3}, [%4];" : "=r"(r[0]), "=r"(r[1]), "=r"(r[2]), "=r"(r[3]) : "r"(addr) : "memory");
}
__device__ __forceinline__ void stsm4(uint32_t addr, uint32_t r0, uint32_t r1, uint32_t r2, uint32_t r3) {
    asm volatile("stmatrix.sync.aligned.m8n8.x4.shared.b16 [%0], {%1, %2, %3, %4};" :: "r"(addr), "r"(r0), "r"(r1), "r"(r2), "r"(r3) : "memory");
}
__device__ __forceinline__ void mma16816(float* d, const uint32_t* a, uint32_t b0, uint32_t b1) {
    asm("mma.sync.aligned.m16n8k16.row.col.f32.bf16.bf16.f32 {%0,%1,%2,%3}, {%4,%5,%6,%7}, {%8,%9}, {%0,%1,%2,%3};"
        : "+f"(d[0]), "+f"(d[1]), "+f"(d[2]), "+f"(d[3]) : "r"(a[0]), "r"(a[1]), "r"(a[2]), "r"(a[3]), "r"(b0), "r"(b1));
}
__device__ __forceinline__ uint32_t sub_bf16x2(uint32_t a, uint32_t b) {
    uint32_t d; asm("sub.rn.bf16x2 %0, %1, %2;" : "=r"(d) : "r"(a), "r"(b)); return d;
}
__device__ __forceinline__ uint32_t ln_pair(uint32_t x2, uint32_t mean2, uint32_t rhi2, uint32_t rlo2) {
    const uint32_t d = sub_bf16x2(x2, mean2);
    uint32_t t, y;
    asm("mul.rn.bf16x2 %0, %1, %2;" : "=r"(t) : "r"(d), "r"(rlo2));
    asm("fma.rn.bf16x2 %0, %1, %2, %3;" : "=r"(y) : "r"(d), "r"(rhi2), "r"(t));
    return y;
}
struct LnRow { uint32_t m2, hi2, lo2; };
__device__ __forceinline__ LnRow ln_row(float mean, float rden) {
    LnRow r;
    r.m2 = pack_bf16(mean, mean);
    r.hi2 = pack_bf16(rden, rden);
    const float lo = rden - bf_lo(r.hi2);
    r.lo2 = pack_bf16(lo, lo);
    return r;
}
__device__ __forceinline__ void ln_frag(uint32_t* a, const LnRow& r0, const LnRow& r1) {
    a[0] = ln_pair(a[0], r0.m2, r0.hi2, r0.lo2); a[1] = ln_pair(a[1], r1.m2, r1.hi2, r1.lo2);
    a[2] = ln_pair(a[2], r0.m2, r0.hi2, r0.lo2); a[3] = ln_pair(a[3], r1.m2, r1.hi2, r1.lo2);
}

template <int NJ>
__device__ __forceinline__ void k1_store(const float* acc, int jj0, uint32_t stage, int nt, int mt, int wg, int w4, int lane) {
    const int mi = lane >> 3, lr = lane & 7;
    const uint32_t off_qk = stage + (w4 * 2 + (mi & 1)) * 256 + (mi >> 1) * 128 + lr * 16;
    const uint32_t off_v = stage + (mi >> 1) * 1024 + (w4 * 16 + (mi & 1) * 8 + lr) * 16;
    #pragma unroll
    for (int jj = 0; jj < NJ; jj++) {
        const bool isv = nt * 12 + jj0 + jj >= 64;
        const float m = isv ? 1.0f : 8.8817841970012523e-16f;
        stsm4((isv ? off_v : off_qk) + jj * 2048,
              pack_bf16(acc[8 * jj] * m, acc[8 * jj + 1] * m), pack_bf16(acc[8 * jj + 2] * m, acc[8 * jj + 3] * m),
              pack_bf16(acc[8 * jj + 4] * m, acc[8 * jj + 5] * m), pack_bf16(acc[8 * jj + 6] * m, acc[8 * jj + 7] * m));
    }
    fence_async_smem();
    named_bar(1 + wg, 128);
    if (lane < NJ / 2) {
        const int pc = w4 * (NJ / 2) + lane, jj = pc >> 1, hf = pc & 1, hg = nt * 12 + jj0 + jj;
        const unsigned char* dst = (const unsigned char*)g_QKV + (size_t)hg * 65536
            + (hg >= 64 ? hf * 32768 + (mt * 128 + wg * 64) * 16 : (mt * 16 + wg * 8) * 256 + hf * 1024);
        asm volatile("cp.async.bulk.global.shared::cta.bulk_group [%0], [%1], 1024;" :: "l"(dst), "r"(stage + pc * 1024) : "memory");
        asm volatile("cp.async.bulk.commit_group;" ::: "memory");
    }
}

__global__ void __launch_bounds__(K1_THREADS, 1)
k1_ln_qkv(const __grid_constant__ CUtensorMap wmap, const __grid_constant__ CUtensorMap xmap, const __nv_bfloat16* __restrict__ w_r) {
    extern __shared__ __align__(1024) unsigned char smem[];
    const uint32_t sA = smem_u32(smem), sB = sA + 131072, sBar = sB + 4 * 24576;
    const int warp = __shfl_sync(~0u, threadIdx.x >> 5, 0), lane = threadIdx.x & 31;
    const int nt = blockIdx.x & 7, mt = blockIdx.x >> 3;
    const int tile = warp < 8 ? warp : nt;
    const int wg = tile >> 2;
    CK(0);
    pdl_launch();
    uint32_t* s_wr = (uint32_t*)(smem + 131072 + 4 * 24576 + 256);
    if (warp == 8) {
        if (lane == 0) {
            for (int i = 0; i < 4; i++) { mbar_init(sBar + i * 8, 1); mbar_init(sBar + 48 + i * 8, 2); }
            asm volatile("fence.mbarrier_init.release.cluster;" ::: "memory");
            for (int i = 0; i < 4; i++) mbar_expect_tx(sBar + i * 8, 24576);
        }
        if (lane < 4) {
            mbar_init(sBar + 96 + lane * 8, 1);
            asm volatile("fence.mbarrier_init.release.cluster;" ::: "memory");
            mbar_expect_tx(sBar + 96 + lane * 8, 32768);
        }
        __syncwarp();
        if (lane < 16) {
            const int pn = (lane >> 3) * 4 + (lane & 3), hf = (lane >> 2) & 1;
            tma_2d(sA + pn * 16384 + hf * 8192, &xmap, pn * 64, mt * 128 + hf * 64, sBar + 96 + (lane >> 2) * 8);
        }
        named_bar(3, K1_THREADS);
        mbar_wait(sBar + 96 + 8, 0);
        if (lane < 12) {
            const int ld = lane / 3, j = lane % 3;
            tma_2d(sB + ld * 24576 + j * 8192, &wmap, nt * 192 + j * 64, ld * 64, sBar + ld * 8);
        }
        __syncwarp();
        if (lane < 3) {
            for (int ld = 4; ld < 8; ld++) {
                const int sl = ld - 4;
                mbar_wait(sBar + 48 + sl * 8, 0);
                if (lane == 0) mbar_expect_tx(sBar + sl * 8, 24576);
                __syncwarp(7);
                tma_2d(sB + sl * 24576 + lane * 8192, &wmap, nt * 192 + lane * 64, ld * 64, sBar + sl * 8);
            }
        }
        return;
    }
    if (warp == 9) {
        #pragma unroll
        for (int i = 0; i < 8; i++) s_wr[i * 32 + lane] = __ldg((const uint32_t*)w_r + i * 32 + lane);
    }
    named_bar(3, K1_THREADS);
    const int g = lane >> 2, t = lane & 3;
    const int lrow = tile * 16 + (lane & 7) + ((lane >> 3) & 1) * 8;
    const uint32_t lbase = sA + lrow * 128;
    const int lsw = lane & 7, lhi = lane >> 4;
    uint32_t laddr[4];
    #pragma unroll
    for (int k4 = 0; k4 < 4; k4++) laddr[k4] = lbase + (((k4 * 2 + lhi) ^ lsw) * 16);
    CK(1);
    float dsum[4] = {0.f, 0.f, 0.f, 0.f}, dq0[4] = {0.f, 0.f, 0.f, 0.f}, dq1[4] = {0.f, 0.f, 0.f, 0.f};
    float esum[4] = {0.f, 0.f, 0.f, 0.f}, eq0[4] = {0.f, 0.f, 0.f, 0.f}, eq1[4] = {0.f, 0.f, 0.f, 0.f};
    #pragma unroll 2
    for (int pn = 0; pn < 8; pn++) {
        uint32_t a[4][4];
        if ((pn & 3) == 0) mbar_wait(sBar + 96 + ((pn >> 2) * 2 + wg) * 8, 0);
        #pragma unroll
        for (int k4 = 0; k4 < 4; k4++) ldsm4(a[k4], laddr[k4] + pn * 16384);
        #pragma unroll
        for (int k4 = 0; k4 < 4; k4 += 2) {
            mma16816(dsum, a[k4], 0x3F803F80u, 0x3F803F80u);
            mma16816(dq0, a[k4], a[k4][0], a[k4][2]);
            mma16816(dq1, a[k4], a[k4][1], a[k4][3]);
            mma16816(esum, a[k4 + 1], 0x3F803F80u, 0x3F803F80u);
            mma16816(eq0, a[k4 + 1], a[k4 + 1][0], a[k4 + 1][2]);
            mma16816(eq1, a[k4 + 1], a[k4 + 1][1], a[k4 + 1][3]);
        }
    }
    #pragma unroll
    for (int i = 0; i < 4; i++) { dsum[i] += esum[i]; dq0[i] += eq0[i]; dq1[i] += eq1[i]; }
    CK(3);
    const int dsrc = g * 4 + (g >> 1);
    const float sq0 = __shfl_sync(~0u, (g & 1) ? dq0[1] : dq0[0], dsrc), sq1 = __shfl_sync(~0u, (g & 1) ? dq1[3] : dq1[2], dsrc);
    const float mean0 = dsum[0] * (1.0f / D_), mean1 = dsum[2] * (1.0f / D_);
    float var0 = fmaf(-mean0, mean0, sq0 * (1.0f / D_)), var1 = fmaf(-mean1, mean1, sq1 * (1.0f / D_));
    if (__any_sync(~0u, !(mean0 * mean0 <= 16.0f * var0) || !(mean1 * mean1 <= 16.0f * var1))) {
        float q0 = 0.f, q1 = 0.f;
        #pragma unroll 1
        for (int ks = 0; ks < 32; ks++) {
            uint32_t a[4];
            ldsm4(a, lbase + (ks >> 2) * 16384 + ((((ks & 3) * 2 + lhi) ^ lsw) * 16));
            #pragma unroll
            for (int i = 0; i < 4; i++) {
                const float m = (i & 1) ? mean1 : mean0;
                const float d0 = bf_lo(a[i]) - m, d1 = bf_hi(a[i]) - m;
                if (i & 1) q1 = fmaf(d0, d0, fmaf(d1, d1, q1)); else q0 = fmaf(d0, d0, fmaf(d1, d1, q0));
            }
        }
        q0 += __shfl_xor_sync(~0u, q0, 1); q0 += __shfl_xor_sync(~0u, q0, 2);
        q1 += __shfl_xor_sync(~0u, q1, 1); q1 += __shfl_xor_sync(~0u, q1, 2);
        var0 = q0 * (1.0f / D_); var1 = q1 * (1.0f / D_);
    }
    const float rs0 = __frcp_rn(bf16r(__fsqrt_rn(bf16r(bf16r(var0) + 1e-5f))));
    const float rs1 = __frcp_rn(bf16r(__fsqrt_rn(bf16r(bf16r(var1) + 1e-5f))));
    const LnRow lr0 = ln_row(mean0, rs0), lr1 = ln_row(mean1, rs1);
    if (warp == 9) {
        float d0 = 0.f, d1 = 0.f, e0 = 0.f, e1 = 0.f;
        #pragma unroll 2
        for (int pn = 0; pn < 8; pn++) {
            uint32_t a[4][4];
            #pragma unroll
            for (int k4 = 0; k4 < 4; k4++) ldsm4(a[k4], laddr[k4] + pn * 16384);
            #pragma unroll
            for (int k4 = 0; k4 < 4; k4++) {
                ln_frag(a[k4], lr0, lr1);
                const uint32_t w0 = s_wr[(pn * 4 + k4) * 8 + t], w1 = s_wr[(pn * 4 + k4) * 8 + 4 + t];
                d0 = fmaf(bf_lo(a[k4][0]), bf_lo(w0), d0); e0 = fmaf(bf_hi(a[k4][0]), bf_hi(w0), e0);
                d1 = fmaf(bf_lo(a[k4][1]), bf_lo(w0), d1); e1 = fmaf(bf_hi(a[k4][1]), bf_hi(w0), e1);
                d0 = fmaf(bf_lo(a[k4][2]), bf_lo(w1), d0); e0 = fmaf(bf_hi(a[k4][2]), bf_hi(w1), e0);
                d1 = fmaf(bf_lo(a[k4][3]), bf_lo(w1), d1); e1 = fmaf(bf_hi(a[k4][3]), bf_hi(w1), e1);
            }
        }
        d0 += e0; d1 += e1;
        d0 += __shfl_xor_sync(~0u, d0, 1); d0 += __shfl_xor_sync(~0u, d0, 2);
        d1 += __shfl_xor_sync(~0u, d1, 1); d1 += __shfl_xor_sync(~0u, d1, 2);
        if (t == 0) {
            const int row0 = mt * 128 + tile * 16;
            g_r[row0 + g] = bf16r(d0); g_r[row0 + g + 8] = bf16r(d1);
            g_stats[row0 + g] = make_float2(bf_lo(lr0.m2), rs0); g_stats[row0 + g + 8] = make_float2(bf_lo(lr1.m2), rs1);
        }
        asm volatile("bar.arrive %0, %1;" :: "r"(4 + wg), "r"(160) : "memory");
        return;
    }
    float acc[96];
    #pragma unroll
    for (int i = 0; i < 96; i++) acc[i] = 0.f;
    const uint64_t db0 = make_desc(sB, 8192, 1024, 1);
    uint32_t a[2][4][4];
    #pragma unroll
    for (int k4 = 0; k4 < 4; k4++) ldsm4(a[0][k4], laddr[k4]);
    #pragma unroll
    for (int k4 = 0; k4 < 4; k4++) ln_frag(a[0][k4], lr0, lr1);
    #pragma unroll 1
    for (int kc = 0; kc < 8; kc += 2) {
        #pragma unroll
        for (int h2 = 0; h2 < 2; h2++) {
            const int ld = kc + h2, sl = ld & 3;
            mbar_wait(sBar + sl * 8, ld >> 2);
            WG_FENCE();
            #pragma unroll
            for (int k4 = 0; k4 < 4; k4++) wgmma_rs_n192(acc, a[h2][k4], db0 + (uint64_t)(sl * 1536 + k4 * 128));
            WG_COMMIT();
            wg_wait<1>();
            if (ld >= 1 && ld <= 4 && (threadIdx.x & 127) == 0) mbar_arrive(sBar + 48 + (ld - 1) * 8);
            #pragma unroll
            for (int k4 = 0; k4 < 4; k4++) ldsm4(a[h2 ^ 1][k4], laddr[k4] + ((ld + 1) & 7) * 16384);
            #pragma unroll
            for (int k4 = 0; k4 < 4; k4++) ln_frag(a[h2 ^ 1][k4], lr0, lr1);
        }
    }
    wg_wait<0>();
    touch96(acc);
    CK(4);
    if ((nt >> 2) == wg) named_bar(4 + wg, 160); else named_bar(1 + wg, 128);
    k1_store<4>(acc, 0, sA + wg * 8192, nt, mt, wg, warp & 3, lane);
    k1_store<4>(acc + 32, 4, sA + 16384 + wg * 8192, nt, mt, wg, warp & 3, lane);
    k1_store<4>(acc + 64, 8, sA + 32768 + wg * 8192, nt, mt, wg, warp & 3, lane);
    CK(5);
    asm volatile("cp.async.bulk.wait_group.read 0;" ::: "memory");
    CK(6);
}

constexpr int K2_THREADS = 512;
constexpr int K2_SMEM = 6 * 32768 + 12288;

constexpr float QS = 0.25f * 1.4426950408889634f;
constexpr float SC100 = 1.2676506002282294e30f;
__device__ __forceinline__ uint32_t polyexp2(float s0, float s1, float cd, uint32_t one2, uint32_t ca2) {
    constexpr float A = 128.0f * QS * 1.7763568394002505e-15f;
    float t0, t1;
    asm("fma.rn.f32 %0, %1, %2, %3;" : "=f"(t0) : "f"(s0), "f"(A), "f"(cd));
    asm("fma.rn.f32 %0, %1, %2, %3;" : "=f"(t1) : "f"(s1), "f"(A), "f"(cd));
    uint32_t W, U, h, G;
    asm("cvt.pack.sat.s16.s32 %0, %1, %2;" : "=r"(W) : "r"(__float_as_int(t1)), "r"(__float_as_int(t0)));
    asm("lop3.b32 %0, %1, 0x007F007F, %2, 0xEA;" : "=r"(U) : "r"(W), "r"(one2));
    asm("fma.rn.bf16x2 %0, %1, %2, %3;" : "=r"(h) : "r"(U), "r"(ca2), "r"(0xC300C300u));
    asm("fma.rn.bf16x2 %0, %1, %2, %3;" : "=r"(G) : "r"(h), "r"(U), "r"(0x438B438Bu));
    return W + G - 0x43404340u;
}

struct ExpC { float nm0, nm1, cd0, cd1; uint32_t one2, ca2; };

template <int G>
__device__ __forceinline__ void exp_block(const float* s, uint32_t* p, const ExpC& c) {
    #pragma unroll
    for (int hf = 0; hf < 2; hf++) {
        const float* x = s + hf * 4;
        if ((PMASK >> (G + hf)) & 1) {
            p[hf * 2 + 0] = polyexp2(x[0], x[1], c.cd0, c.one2, c.ca2);
            p[hf * 2 + 1] = polyexp2(x[2], x[3], c.cd1, c.one2, c.ca2);
        } else {
            p[hf * 2 + 0] = pack_bf16(ex2(fmaf(x[0], QS * SC100, c.nm0)), ex2(fmaf(x[1], QS * SC100, c.nm0)));
            p[hf * 2 + 1] = pack_bf16(ex2(fmaf(x[2], QS * SC100, c.nm1)), ex2(fmaf(x[3], QS * SC100, c.nm1)));
        }
    }
}

__device__ __forceinline__ void max16(const float* s, float& mx0, float& mx1) {
    #pragma unroll
    for (int j = 0; j < 4; j++) {
        mx0 = fmaxf(mx0, fmaxf(s[4 * j], s[4 * j + 1]));
        mx1 = fmaxf(mx1, fmaxf(s[4 * j + 2], s[4 * j + 3]));
    }
}

constexpr int MOE_SLOTS = 6, MOE_BOXES = 44;
__device__ __forceinline__ void moe_load(int b, int part, uint32_t ring, uint32_t bars, const CUtensorMap* mg, const CUtensorMap* mu, const CUtensorMap* md) {
    const int sl = b % MOE_SLOTS, grp = b & 1;
    if (b < 28) {
        const int j = b >> 1;
        mbar_expect_tx(bars + sl * 8, 32768);
        tma_2d(ring + sl * 32768, grp ? mu : mg, part * 448 + (j >> 1) * 64, (j & 1) * 256, bars + sl * 8);
    } else {
        const int j = (b - 28) >> 1;
        mbar_expect_tx(bars + sl * 8, 28672);
        tma_2d(ring + sl * 32768, md, ((j >> 1) * 2 + grp) * 64, part * 448 + (j & 1) * 224, bars + sl * 8);
    }
}
__device__ __forceinline__ void mma_2row(float* d, uint32_t a0, uint32_t a2, uint32_t b0, uint32_t b1) {
    asm("mma.sync.aligned.m16n8k16.row.col.f32.bf16.bf16.f32 {%0,%1,%2,%3}, {%4,%5,%6,%5}, {%7,%8}, {%0,%1,%2,%3};"
        : "+f"(d[0]), "+f"(d[1]), "+f"(d[2]), "+f"(d[3]) : "r"(a0), "r"(0u), "r"(a2), "r"(b0), "r"(b1));
}

__device__ void moe_cta(int part, unsigned char* smem, const __nv_bfloat16* __restrict__ x, const CUtensorMap* mg, const CUtensorMap* mu, const CUtensorMap* md) {
    const uint32_t ring = smem_u32(smem), bars = ring + MOE_SLOTS * 32768;
    __nv_bfloat16* xs = (__nv_bfloat16*)(smem + MOE_SLOTS * 32768 + 256);
    float* gu = (float*)(smem + MOE_SLOTS * 32768 + 256 + 2048);
    float* s_v = gu + 4 * 448;
    int* s_i = (int*)(s_v + 16);
    int* s_sel = s_i + 16;
    const int tid = threadIdx.x, warp = __shfl_sync(~0u, tid >> 5, 0), lane = tid & 31;
    if (tid == 0) {
        for (int i = 0; i < MOE_SLOTS; i++) { mbar_init(bars + i * 8, 1); mbar_init(bars + 128 + i * 8, 8); }
        asm volatile("fence.mbarrier_init.release.cluster;" ::: "memory");
        for (int b = 0; b < MOE_SLOTS; b++) moe_load(b, part, ring, bars, mg, mu, md);
    }
    pdl_wait();
    TL(1, 1);
    float rv[4];
    #pragma unroll
    for (int i = 0; i < 4; i++) rv[i] = g_r[tid + i * K2_THREADS];
    for (int pass = 0; pass < 2; pass++) {
        float bv = -INFINITY; int bi = 0x7fffffff;
        const int excl = pass ? s_sel[0] : -1;
        #pragma unroll
        for (int i = 0; i < 4; i++) {
            const int idx = tid + i * K2_THREADS;
            if (idx != excl && (rv[i] > bv || bi == 0x7fffffff)) { bv = rv[i]; bi = idx; }
        }
        #pragma unroll
        for (int o = 16; o; o >>= 1) {
            float ov = __shfl_xor_sync(~0u, bv, o); int oi = __shfl_xor_sync(~0u, bi, o);
            if (ov > bv || (ov == bv && oi < bi)) { bv = ov; bi = oi; }
        }
        if (lane == 0) { s_v[warp] = bv; s_i[warp] = bi; }
        __syncthreads();
        if (warp == 0) {
            bv = lane < 16 ? s_v[lane] : -INFINITY; bi = lane < 16 ? s_i[lane] : 0x7fffffff;
            #pragma unroll
            for (int o = 16; o; o >>= 1) {
                float ov = __shfl_xor_sync(~0u, bv, o); int oi = __shfl_xor_sync(~0u, bi, o);
                if (ov > bv || (ov == bv && oi < bi)) { bv = ov; bi = oi; }
            }
            if (lane == 0) s_sel[pass] = (bi == 0x7fffffff) ? pass : bi;
        }
        __syncthreads();
    }
    for (int i = tid; i < 1024; i += K2_THREADS) {
        const int tok = s_sel[i >> 9];
        const float2 st = g_stats[tok];
        xs[i] = __float2bfloat16_rn(ln_elem(__bfloat162float(x[(size_t)tok * D_ + (i & 511)]), st.x, st.y));
    }
    if (part == 0 && tid < 2) g_sel[tid] = s_sel[tid];
    __syncthreads();
    if (warp == 8) {
        if (lane == 0) {
            for (int b = MOE_SLOTS; b < MOE_BOXES; b++) {
                mbar_wait(bars + 128 + (b % MOE_SLOTS) * 8, (b / MOE_SLOTS - 1) & 1);
                moe_load(b, part, ring, bars, mg, mu, md);
            }
        }
        return;
    }
    if (warp > 8) return;
    const int nj = warp, g = lane >> 2, t = lane & 3;
    const uint32_t* xw = (const uint32_t*)xs + (g & 1) * 256 + t;
    uint32_t a[2][32];
    #pragma unroll
    for (int i = 0; i < 32; i++) { a[0][i] = xw[i * 4]; a[1][i] = xw[128 + i * 4]; }
    #pragma unroll 1
    for (int jp = 0; jp < MOE_BOXES / 4; jp++) {
        const bool down = jp >= 7;
        if (jp == 7) {
            named_bar(1, 256);
            for (int i = tid; i < 896; i += 256) {
                const float gs = bf16r(gu[i]), us = bf16r(gu[896 + i]);
                const float sl_ = bf16r(gs / (1.0f + __expf(-gs)));
                xs[(i / 448) * 512 + (i % 448)] = __float2bfloat16_rn(sl_ * us);
            }
            named_bar(1, 256);
            #pragma unroll
            for (int i = 0; i < 28; i++) { a[0][i] = xw[i * 4]; a[1][i] = xw[112 + i * 4]; }
        }
        float acc[2][4] = {{0.f, 0.f, 0.f, 0.f}, {0.f, 0.f, 0.f, 0.f}}, acb[2][4] = {{0.f, 0.f, 0.f, 0.f}, {0.f, 0.f, 0.f, 0.f}};
        #pragma unroll
        for (int q = 0; q < 4; q++) {
            const int hf = q >> 1, grp = q & 1;
            const int b = jp * 4 + q, sl = b % MOE_SLOTS;
            mbar_wait(bars + sl * 8, (b / MOE_SLOTS) & 1);
            const uint32_t baddr = ring + sl * 32768 + lane * 128 + ((nj ^ (lane & 7)) * 16);
            #pragma unroll
            for (int k4 = 0; k4 < 2; k4++) {
                uint32_t bf[4][4];
                #pragma unroll
                for (int k2 = 0; k2 < 4; k2++)
                    asm volatile("ldmatrix.sync.aligned.m8n8.x4.trans.shared.b16 {%0, %1, %2, %3}, [%4];"
                                 : "=r"(bf[k2][0]), "=r"(bf[k2][1]), "=r"(bf[k2][2]), "=r"(bf[k2][3]) : "r"(baddr + (k4 * 4 + k2) * 4096) : "memory");
                #pragma unroll
                for (int k2 = 0; k2 < 4; k2++) {
                    const int kk = k4 * 4 + k2;
                    if (kk < 7 || !down) {
                        mma_2row(acc[grp], a[hf][4 * kk], a[hf][4 * kk + 1], bf[k2][0], bf[k2][1]);
                        mma_2row(acb[grp], a[hf][4 * kk + 2], a[hf][4 * kk + 3], bf[k2][2], bf[k2][3]);
                    }
                }
            }
            __syncwarp();
            if (lane == 0) mbar_arrive(bars + 128 + sl * 8);
        }
        if (g < 2) {
            #pragma unroll
            for (int grp = 0; grp < 2; grp++) {
                const float2 v = make_float2(acc[grp][0] + acb[grp][0], acc[grp][1] + acb[grp][1]);
                if (!down) *(float2*)&gu[(grp * 2 + g) * 448 + jp * 64 + nj * 8 + t * 2] = v;
                else *(float2*)&g_ypart[part][g][((jp - 7) * 2 + grp) * 64 + nj * 8 + t * 2] = v;
            }
        }
    }
}

__global__ void __launch_bounds__(K2_THREADS, 1)
k2_attn(const __nv_bfloat16* __restrict__ x, const __nv_bfloat16* __restrict__ w_gate, const __nv_bfloat16* __restrict__ w_up,
        const __nv_bfloat16* __restrict__ w_down, const __grid_constant__ CUtensorMap mg, const __grid_constant__ CUtensorMap mu,
        const __grid_constant__ CUtensorMap md) {
    extern __shared__ __align__(1024) unsigned char smem[];
    TL(1, 0);
    pdl_launch();
    if (blockIdx.x >= 128) { moe_cta(blockIdx.x - 128, smem, x, &mg, &mu, &md); TL(1, 2); return; }
    if (threadIdx.x >= 32 && threadIdx.x < 35) {
        const __nv_bfloat16* w = threadIdx.x == 32 ? w_gate : (threadIdx.x == 33 ? w_up : w_down);
        asm volatile("cp.async.bulk.prefetch.L2.global [%0], %1;" :: "l"(w + (size_t)blockIdx.x * (D_ * F_ / 128)), "r"(D_ * F_ / 64) : "memory");
    }
    const uint32_t sK = smem_u32(smem), sV = sK + 65536, sQ = sV + 98304, sBar = sQ + 16384;
    const int h = blockIdx.x >> 2, qb = blockIdx.x & 3;
    const int warp = __shfl_sync(~0u, threadIdx.x >> 5, 0), lane = threadIdx.x & 31, wg = warp >> 2;
    if (threadIdx.x == 0) {
        mbar_init(sBar, 1); mbar_init(sBar + 8, 1);
        asm volatile("fence.mbarrier_init.release.cluster;" ::: "memory");
        mbar_expect_tx(sBar, 8192 + 12288 + 2 * 6144);
        mbar_expect_tx(sBar + 8, 8192 + 53248 + 2 * 26624);
    }
    for (int i = threadIdx.x; i < 2048; i += K2_THREADS)
        *(uint4*)(smem + 65536 + 65536 + i * 16) = make_uint4(0x3F803F80u, 0x3F803F80u, 0x3F803F80u, 0x3F803F80u);
    fence_async_smem();
    __syncthreads();
    if (warp == 0) {
        pdl_wait();
        TL(1, 1);
        const uint4* gk = g_K + (size_t)h * 4096;
        const uint4* gv = g_V + (size_t)h * 4096;
        const uint4* gq = g_Q + (size_t)h * 4096 + qb * 1024;
        if (lane == 0) bulk_g2s(sQ, gq, 8192, sBar);
        if (lane == 1) bulk_g2s(sK, gk, 12288, sBar);
        if (lane == 2) bulk_g2s(sV, gv, 6144, sBar);
        if (lane == 3) bulk_g2s(sV + 32768, gv + 2048, 6144, sBar);
        if (lane == 4) bulk_g2s(sK + 12288, gk + 768, 53248, sBar + 8);
        if (lane == 5) bulk_g2s(sV + 6144, gv + 384, 26624, sBar + 8);
        if (lane == 6) bulk_g2s(sV + 32768 + 6144, gv + 2048 + 384, 26624, sBar + 8);
        if (lane == 7) bulk_g2s(sQ + 8192, gq + 512, 8192, sBar + 8);
        __syncwarp();
    }
    ExpC c;
    {
        const volatile uint32_t* cc = g_const;
        c.one2 = cc[0]; c.ca2 = cc[1];
    }
    const uint64_t kdesc0 = make_desc(sK, 128, 256, 0);
    const uint64_t vdesc0 = make_desc(sV, 128, 32768, 0);
    #pragma unroll 1
    for (int pass = 0; pass < 2; pass++) {
        const bool dry = false;
        if (pass == 0) { mbar_wait(sBar, 0); __syncwarp(); TL(1, 2); }
        const int unit = (pass & 1) * 4 + wg;
        const uint64_t q = make_desc(sQ + unit * 2048, 128, 256, 0);
        float o[12];
        #pragma unroll 1
        for (int attempt = 0; attempt < 2; attempt++) {
            float s0[16], s1[16], s2[16];
            #pragma unroll
            for (int i = 0; i < 16; i++) { s0[i] = 0.f; s1[i] = 0.f; s2[i] = 0.f; }
            float mx0 = -INFINITY, mx1 = -INFINITY;
            if (attempt) {
                #pragma unroll 1
                for (int it = 0; it < 64; it++) {
                    WG_FENCE();
                    wgmma_qk32(s0, q, kdesc0 + it * 64);
                    WG_COMMIT();
                    wg_wait<0>();
                    touch16(s0);
                    max16(s0, mx0, mx1);
                }
            }
            #pragma unroll
            for (int i = 0; i < 12; i++) o[i] = 0.f;
            WG_FENCE();
            wgmma_qk32(s2, q, kdesc0);
            wgmma_qk32(s0, q, kdesc0 + 64);
            wgmma_qk32(s1, q, kdesc0 + 128);
            WG_COMMIT();
            wg_wait<0>();
            touch16(s0); touch16(s1); touch16(s2);
            max16(s0, mx0, mx1); max16(s1, mx0, mx1); max16(s2, mx0, mx1);
            mx0 = fmaxf(mx0, __shfl_xor_sync(~0u, mx0, 1)); mx0 = fmaxf(mx0, __shfl_xor_sync(~0u, mx0, 2));
            mx1 = fmaxf(mx1, __shfl_xor_sync(~0u, mx1, 1)); mx1 = fmaxf(mx1, __shfl_xor_sync(~0u, mx1, 2));
            const float bias = attempt ? 0.0f : 128.0f * 64.0f;
            const float y0 = ceilf(fmaf(mx0, 128.0f * QS * SC100, bias)), y1 = ceilf(fmaf(mx1, 128.0f * QS * SC100, bias));
            c.nm0 = __shfl_sync(~0u, y0 * (-1.0f / 128.0f), lane); c.nm1 = __shfl_sync(~0u, y1 * (-1.0f / 128.0f), lane);
            c.cd0 = __shfl_sync(~0u, __fmul_rn(16256.0f - y0, __int_as_float(1)), lane);
            c.cd1 = __shfl_sync(~0u, __fmul_rn(16256.0f - y1, __int_as_float(1)), lane);
            uint64_t kd = kdesc0 + 192, vd = vdesc0 + 32;
            {
                uint32_t pa[4], pb[4];
                exp_block<12>(s2, pa, c);
                exp_block<14>(s2 + 8, pb, c);
                WG_FENCE();
                wgmma_pv(o, pa, vdesc0); wgmma_pv(o, pb, vdesc0 + 16);
                WG_COMMIT();
            }
            #pragma unroll 1
            for (int seg = 0; seg < (dry ? 1 : 2); seg++) {
            if (seg) { wg_wait<0>(); mbar_wait(sBar + 8, 0); __syncwarp(); }
            #pragma unroll 1
            for (int it = seg ? 3 : (dry ? 2 : 0); it < (seg ? 21 : 3); it++) {
                uint32_t p[6][4];
                WG_FENCE();
                wgmma_qk32(s2, q, kd);
                WG_COMMIT();
                exp_block<0>(s0, p[0], c);
                exp_block<2>(s0 + 8, p[1], c);
                WG_FENCE();
                wgmma_pv(o, p[0], vd); wgmma_pv(o, p[1], vd + 16);
                wgmma_qk32(s0, q, kd + 64);
                WG_COMMIT();
                wg_wait<1>();
                touch16(s2);
                exp_block<4>(s1, p[2], c);
                exp_block<6>(s1 + 8, p[3], c);
                WG_FENCE();
                wgmma_pv(o, p[2], vd + 32); wgmma_pv(o, p[3], vd + 48);
                wgmma_qk32(s1, q, kd + 128);
                WG_COMMIT();
                wg_wait<1>();
                touch16(s0);
                exp_block<8>(s2, p[4], c);
                exp_block<10>(s2 + 8, p[5], c);
                WG_FENCE();
                wgmma_pv(o, p[4], vd + 64); wgmma_pv(o, p[5], vd + 80);
                WG_COMMIT();
                vd += 96; kd += 192;
                wg_wait<1>();
                touch16(s1);
            }
            }
            wg_wait<0>();
            touch12(o);
            if (attempt) break;
            float big = 0.f;
            #pragma unroll
            for (int i = 0; i < 12; i++) big = fmaxf(big, fabsf(o[i]));
            bool bad = !(big < 1e30f);
            #pragma unroll
            for (int i = 0; i < 12; i++) bad |= (o[i] != o[i]);
            uint32_t any;
            asm volatile("{.reg .pred p, q; setp.ne.u32 p, %1, 0; barrier.cta.red.or.pred.aligned q, %2, 128, p; selp.u32 %0, 1, 0, q;}"
                         : "=r"(any) : "r"((uint32_t)bad), "r"(1 + wg) : "memory");
            if (dry || !__any_sync(~0u, any)) break;
        }
        const int g = lane >> 2, t = lane & 3;
        const int r = (warp & 3) * 16 + g;
        const float i0 = __fdiv_rn(1.0f, o[8]), i1 = __fdiv_rn(1.0f, o[10]);
        uint32_t* ob = (uint32_t*)(g_O + (size_t)(qb * 8 + unit) * 4096 + (h >> 2) * 512 + r * 8) + t;
        const int c0 = ((h & 3) * 2) ^ (r & 7), c1 = ((h & 3) * 2 + 1) ^ (r & 7);
        if (!dry) {
            ob[c0 * 4] = pack_bf16(o[0] * i0, o[1] * i0);
            ob[c1 * 4] = pack_bf16(o[4] * i0, o[5] * i0);
            ob[256 + c0 * 4] = pack_bf16(o[2] * i1, o[3] * i1);
            ob[256 + c1 * 4] = pack_bf16(o[6] * i1, o[7] * i1);
            TL(1, 3 + pass);
        }
    }
}

constexpr int K3_THREADS = 256;
constexpr int K3_SMEM = 65536 + 131072 + 128;

__global__ void __launch_bounds__(K3_THREADS, 1)
k3_out(const __grid_constant__ CUtensorMap wmap, const __nv_bfloat16* __restrict__ x, __nv_bfloat16* __restrict__ out) {
    extern __shared__ __align__(1024) unsigned char smem[];
    const uint32_t sA = smem_u32(smem), sB = sA + 65536, sBar = sB + 131072;
    const int warp = __shfl_sync(~0u, threadIdx.x >> 5, 0), lane = threadIdx.x & 31, wg = warp >> 2;
    const int nt = blockIdx.x & 3, mt = blockIdx.x >> 2;
    TL(2, 0);
    if (threadIdx.x == 0) {
        for (int i = 0; i < 10; i++) mbar_init(sBar + i * 8, 1);
        asm volatile("fence.mbarrier_init.release.cluster;" ::: "memory");
        for (int i = 0; i < 8; i++) mbar_expect_tx(sBar + 16 + i * 8, 8192);
        for (int kh = 0; kh < 2; kh++) {
            mbar_expect_tx(sBar + kh * 8, 65536);
            tma_2d(sB + kh * 32768, &wmap, nt * 128, kh * 256, sBar + kh * 8);
            tma_2d(sB + 65536 + kh * 32768, &wmap, nt * 128 + 64, kh * 256, sBar + kh * 8);
        }
    }
    const int er = threadIdx.x >> 2, ec = (threadIdx.x & 3) * 32;
    const int row = mt * 64 + er;
    uint4 xv[4];
    #pragma unroll
    for (int j = 0; j < 4; j++) xv[j] = __ldg((const uint4*)(x + (size_t)row * D_ + nt * 128 + ec) + j);
    __syncthreads();
    pdl_wait();
    TL(2, 1);
    if (threadIdx.x < 8) bulk_g2s(sA + threadIdx.x * 8192, g_O + (size_t)mt * 4096 + threadIdx.x * 512, 8192, sBar + 16 + threadIdx.x * 8);
    const int sel0 = g_sel[0], sel1 = g_sel[1];
    const float2 st = g_stats[row];
    uint32_t bb[16];
    {
        const uint32_t xu[16] = {xv[0].x, xv[0].y, xv[0].z, xv[0].w, xv[1].x, xv[1].y, xv[1].z, xv[1].w,
                                 xv[2].x, xv[2].y, xv[2].z, xv[2].w, xv[3].x, xv[3].y, xv[3].z, xv[3].w};
        #pragma unroll
        for (int j = 0; j < 16; j++) bb[j] = pack_bf16(bf16r(bf_lo(xu[j]) - st.x) * st.y, bf16r(bf_hi(xu[j]) - st.x) * st.y);
        const int slot = row == sel0 ? 0 : (row == sel1 ? 1 : -1);
        if (slot >= 0) {
            const float gate = bf16r(1.0f / (1.0f + __expf(-g_r[row])));
            const int c0 = nt * 128 + ec;
            #pragma unroll
            for (int j = 0; j < 16; j++) {
                const float2 a = *(const float2*)&g_ypart[0][slot][c0 + 2 * j], b = *(const float2*)&g_ypart[1][slot][c0 + 2 * j];
                const float2 c = *(const float2*)&g_ypart[2][slot][c0 + 2 * j], d = *(const float2*)&g_ypart[3][slot][c0 + 2 * j];
                bb[j] = pack_bf16(bf_lo(bb[j]) + bf16r(bf16r(a.x + b.x + c.x + d.x) * gate), bf_hi(bb[j]) + bf16r(bf16r(a.y + b.y + c.y + d.y) * gate));
            }
        }
    }
    float acc[32];
    #pragma unroll
    for (int i = 0; i < 32; i++) acc[i] = 0.f;
    const uint64_t da0 = make_desc(sA, 16, 1024, 1);
    const uint64_t db0 = make_desc(sB + wg * 65536, 8192, 1024, 1);
    #pragma unroll 1
    for (int q = 0; q < 8; q++) {
        if ((q & 3) == 0) mbar_wait(sBar + (q >> 2) * 8, 0);
        mbar_wait(sBar + 16 + q * 8, 0);
        WG_FENCE();
        #pragma unroll
        for (int kk = 0; kk < 4; kk++)
            wgmma_n64(acc, da0 + (uint64_t)(q * 512 + kk * 2), db0 + (uint64_t)(q * 512 + kk * 128));
        WG_COMMIT();
    }
    wg_wait<0>();
    touch32(acc);
    TL(2, 2);
    __syncthreads();
    {
        const int g = lane >> 2, t = lane & 3;
        unsigned char* sp = smem + ((warp & 3) * 16 + g) * 272 + wg * 128 + t * 4;
        #pragma unroll
        for (int j = 0; j < 8; j++) {
            *(uint32_t*)(sp + j * 16) = pack_bf16(acc[4 * j], acc[4 * j + 1]);
            *(uint32_t*)(sp + 8 * 272 + j * 16) = pack_bf16(acc[4 * j + 2], acc[4 * j + 3]);
        }
    }
    __syncthreads();
    #pragma unroll
    for (int j = 0; j < 4; j++) {
        const uint4 av = *(const uint4*)(smem + er * 272 + ec * 2 + j * 16);
        const uint32_t au[4] = {av.x, av.y, av.z, av.w}, xu[4] = {xv[j].x, xv[j].y, xv[j].z, xv[j].w};
        uint32_t o[4];
        #pragma unroll
        for (int i = 0; i < 4; i++) {
            uint32_t t2;
            asm("add.rn.bf16x2 %0, %1, %2;" : "=r"(t2) : "r"(xu[i]), "r"(au[i]));
            asm("add.rn.bf16x2 %0, %1, %2;" : "=r"(o[i]) : "r"(t2), "r"(bb[j * 4 + i]));
        }
        *((uint4*)(out + (size_t)row * D_ + nt * 128 + ec) + j) = make_uint4(o[0], o[1], o[2], o[3]);
    }
    TL(2, 3);
}

typedef CUresult (*EncodeFn)(CUtensorMap*, CUtensorMapDataType, cuuint32_t, void*, const cuuint64_t*, const cuuint64_t*,
                             const cuuint32_t*, const cuuint32_t*, CUtensorMapInterleave, CUtensorMapSwizzle,
                             CUtensorMapL2promotion, CUtensorMapFloatOOBfill);

void make_wmap(EncodeFn fn, CUtensorMap* map, const void* ptr, int rows, int cols, int box_rows) {
    cuuint64_t dims[2] = {(cuuint64_t)cols, (cuuint64_t)rows};
    cuuint64_t strides[1] = {(cuuint64_t)cols * 2};
    cuuint32_t box[2] = {64, (cuuint32_t)box_rows};
    cuuint32_t es[2] = {1, 1};
    fn(map, CU_TENSOR_MAP_DATA_TYPE_BFLOAT16, 2, (void*)ptr, dims, strides, box, es, CU_TENSOR_MAP_INTERLEAVE_NONE,
       CU_TENSOR_MAP_SWIZZLE_128B, CU_TENSOR_MAP_L2_PROMOTION_L2_256B, CU_TENSOR_MAP_FLOAT_OOB_FILL_NONE);
}

}

extern "C" void kernel_launch(void* const* d_in, const int* in_sizes, int n_in, void* d_out, int out_size) {
    const __nv_bfloat16* x = (const __nv_bfloat16*)d_in[0];
    const __nv_bfloat16* wqkv = (const __nv_bfloat16*)d_in[1];
    const __nv_bfloat16* wo = (const __nv_bfloat16*)d_in[2];
    const __nv_bfloat16* w_r = (const __nv_bfloat16*)d_in[4];
    const __nv_bfloat16* w_gate = (const __nv_bfloat16*)d_in[5];
    const __nv_bfloat16* w_up = (const __nv_bfloat16*)d_in[6];
    const __nv_bfloat16* w_down = (const __nv_bfloat16*)d_in[7];
    __nv_bfloat16* out = (__nv_bfloat16*)d_out;

    static EncodeFn encode = nullptr;
    if (!encode) {
        void* fn = nullptr;
        cudaDriverEntryPointQueryResult qres;
        cudaGetDriverEntryPoint("cuTensorMapEncodeTiled", &fn, cudaEnableDefault, &qres);
        encode = (EncodeFn)fn;
        cudaFuncSetAttribute(k1_ln_qkv, cudaFuncAttributeMaxDynamicSharedMemorySize, K1_SMEM);
        cudaFuncSetAttribute(k2_attn, cudaFuncAttributeMaxDynamicSharedMemorySize, K2_SMEM);
        cudaFuncSetAttribute(k3_out, cudaFuncAttributeMaxDynamicSharedMemorySize, K3_SMEM);
    }
    CUtensorMap map_qkv, map_wo, map_x, map_g, map_u, map_d;
    make_wmap(encode, &map_g, w_gate, D_, F_, 256);
    make_wmap(encode, &map_u, w_up, D_, F_, 256);
    make_wmap(encode, &map_d, w_down, F_, D_, 224);
    make_wmap(encode, &map_x, x, S_, D_, 64);
    make_wmap(encode, &map_qkv, wqkv, D_, 3 * D_, 64);
    make_wmap(encode, &map_wo, wo, D_, D_, 256);

    k1_ln_qkv<<<128, K1_THREADS, K1_SMEM, cudaStreamPerThread>>>(map_qkv, map_x, w_r);
    cudaLaunchAttribute at[1];
    at[0].id = cudaLaunchAttributeProgrammaticStreamSerialization;
    at[0].val.programmaticStreamSerializationAllowed = 1;
    cudaLaunchConfig_t cfg = {};
    cfg.stream = cudaStreamPerThread;
    cfg.attrs = at; cfg.numAttrs = 1;
    cfg.gridDim = dim3(132); cfg.blockDim = dim3(K2_THREADS); cfg.dynamicSmemBytes = K2_SMEM;
    cudaLaunchKernelEx(&cfg, k2_attn, x, w_gate, w_up, w_down, map_g, map_u, map_d);
    cfg.gridDim = dim3(128); cfg.blockDim = dim3(K3_THREADS); cfg.dynamicSmemBytes = K3_SMEM;
    cudaLaunchKernelEx(&cfg, k3_out, map_wo, x, out);
}
```

```cpp
#include <cuda_runtime.h>
#include <cuda_bf16.h>
#include <cuda.h>
#include <stdint.h>

namespace {

constexpr int S_ = 2048, D_ = 512, H_ = 32, F_ = 1792;

constexpr uint32_t PMASK = 0xDB6;

__device__ __align__(1024) uint4 g_QKV[3 * H_ * S_ * 2];
#define g_Q (g_QKV)
#define g_K (g_QKV + H_ * S_ * 2)
#define g_V (g_QKV + 2 * H_ * S_ * 2)
__device__ __align__(1024) uint4 g_O[S_ * D_ / 8];
__device__ float2 g_stats[S_];
__device__ uint32_t g_const[2] = {0x3F803F80u, 0x42294229u};
__device__ float g_r[S_];
__device__ __align__(16) float g_ypart[4][2][D_];
__device__ int g_sel[2];

__device__ __forceinline__ uint32_t smem_u32(const void* p) { return (uint32_t)__cvta_generic_to_shared(p); }
__device__ __forceinline__ float bf16r(float x) { return __bfloat162float(__float2bfloat16_rn(x)); }
__device__ __forceinline__ uint32_t pack_bf16(float lo, float hi) {
    uint32_t r; asm("cvt.rn.bf16x2.f32 %0, %1, %2;" : "=r"(r) : "f"(hi), "f"(lo)); return r;
}
__device__ __forceinline__ float bf_lo(uint32_t u) { return __uint_as_float(u << 16); }
__device__ __forceinline__ float bf_hi(uint32_t u) { return __uint_as_float(u & 0xFFFF0000u); }
__device__ __forceinline__ float ex2(float x) { float y; asm("ex2.approx.ftz.f32 %0, %1;" : "=f"(y) : "f"(x)); return y; }

__device__ __forceinline__ void mbar_init(uint32_t bar, uint32_t count) {
    asm volatile("mbarrier.init.shared::cta.b64 [%0], %1;" :: "r"(bar), "r"(count) : "memory");
}
__device__ __forceinline__ void mbar_expect_tx(uint32_t bar, uint32_t bytes) {
    asm volatile("mbarrier.arrive.expect_tx.shared::cta.b64 _, [%0], %1;" :: "r"(bar), "r"(bytes) : "memory");
}
__device__ __forceinline__ void mbar_arrive(uint32_t bar) {
    asm volatile("mbarrier.arrive.shared::cta.b64 _, [%0];" :: "r"(bar) : "memory");
}
__device__ __forceinline__ void mbar_wait(uint32_t bar, uint32_t parity) {
    uint32_t done;
    #pragma unroll 1
    for (int it = 0; it < (1 << 26); it++) {
        asm volatile("{.reg .pred p; mbarrier.try_wait.parity.shared::cta.b64 p, [%1], %2; selp.u32 %0, 1, 0, p;}"
                     : "=r"(done) : "r"(bar), "r"(parity) : "memory");
        if (done) return;
    }
    __trap();
}
__device__ __forceinline__ void bulk_g2s(uint32_t dst, const void* src, uint32_t bytes, uint32_t bar) {
    asm volatile("cp.async.bulk.shared::cluster.global.mbarrier::complete_tx::bytes [%0], [%1], %2, [%3];"
                 :: "r"(dst), "l"(src), "r"(bytes), "r"(bar) : "memory");
}
__device__ __forceinline__ void tma_2d(uint32_t dst, const CUtensorMap* map, int c0, int c1, uint32_t bar) {
    asm volatile("cp.async.bulk.tensor.2d.shared::cluster.global.mbarrier::complete_tx::bytes [%0], [%1, {%3, %4}], [%2];"
                 :: "r"(dst), "l"(map), "r"(bar), "r"(c0), "r"(c1) : "memory");
}
__device__ __forceinline__ void fence_async_smem() { asm volatile("fence.proxy.async.shared::cta;" ::: "memory"); }
__device__ __forceinline__ void named_bar(int id, int n) { asm volatile("bar.sync %0, %1;" :: "r"(id), "r"(n) : "memory"); }

__device__ __forceinline__ uint64_t make_desc(uint32_t saddr, uint32_t lbo, uint32_t sbo, uint32_t swz) {
    return (uint64_t)((saddr & 0x3FFFF) >> 4) | ((uint64_t)(lbo >> 4) << 16) | ((uint64_t)(sbo >> 4) << 32) | ((uint64_t)swz << 62);
}
#define WG_FENCE() asm volatile("wgmma.fence.sync.aligned;" ::: "memory")
#define WG_COMMIT() asm volatile("wgmma.commit_group.sync.aligned;" ::: "memory")
template <int N> __device__ __forceinline__ void wg_wait() { asm volatile("wgmma.wait_group.sync.aligned %0;" :: "n"(N) : "memory"); }

#define F4(d, o) "+f"(d[o]), "+f"(d[o + 1]), "+f"(d[o + 2]), "+f"(d[o + 3])
#define F16(d, o) F4(d, o), F4(d, o + 4), F4(d, o + 8), F4(d, o + 12)
#define F32(d, o) F16(d, o), F16(d, o + 16)

__device__ __forceinline__ void wgmma_rs_n192(float* d, const uint32_t* a, uint64_t db) {
    asm volatile("wgmma.mma_async.sync.aligned.m64n192k16.f32.bf16.bf16 "
        "{%0,%1,%2,%3,%4,%5,%6,%7,%8,%9,%10,%11,%12,%13,%14,%15,%16,%17,%18,%19,%20,%21,%22,%23,%24,%25,%26,%27,%28,%29,%30,%31,"
        "%32,%33,%34,%35,%36,%37,%38,%39,%40,%41,%42,%43,%44,%45,%46,%47,%48,%49,%50,%51,%52,%53,%54,%55,%56,%57,%58,%59,%60,%61,%62,%63,"
        "%64,%65,%66,%67,%68,%69,%70,%71,%72,%73,%74,%75,%76,%77,%78,%79,%80,%81,%82,%83,%84,%85,%86,%87,%88,%89,%90,%91,%92,%93,%94,%95}, "
        "{%96,%97,%98,%99}, %100, 1, 1, 1, 1;\n"
        : F32(d, 0), F32(d, 32), F32(d, 64) : "r"(a[0]), "r"(a[1]), "r"(a[2]), "r"(a[3]), "l"(db));
}
__device__ __forceinline__ void wgmma_n64(float* d, uint64_t da, uint64_t db) {
    asm volatile("wgmma.mma_async.sync.aligned.m64n64k16.f32.bf16.bf16 "
        "{%0,%1,%2,%3,%4,%5,%6,%7,%8,%9,%10,%11,%12,%13,%14,%15,%16,%17,%18,%19,%20,%21,%22,%23,%24,%25,%26,%27,%28,%29,%30,%31}, "
        "%32, %33, 1, 1, 1, 0, 1;\n"
        : F32(d, 0) : "l"(da), "l"(db));
}
__device__ __forceinline__ void wgmma_qk32(float* d, uint64_t qd, uint64_t kd) {
    asm volatile("wgmma.mma_async.sync.aligned.m64n32k16.f32.bf16.bf16 {%0,%1,%2,%3,%4,%5,%6,%7,%8,%9,%10,%11,%12,%13,%14,%15}, %16, %17, 0, 1, 1, 0, 0;\n"
        : F16(d, 0) : "l"(qd), "l"(kd));
}
__device__ __forceinline__ void wgmma_pv(float* d, const uint32_t* a, uint64_t vd) {
    asm volatile("wgmma.mma_async.sync.aligned.m64n24k16.f32.bf16.bf16 {%0,%1,%2,%3,%4,%5,%6,%7,%8,%9,%10,%11}, {%12,%13,%14,%15}, %16, 1, 1, 1, 1;\n"
        : F4(d, 0), F4(d, 4), F4(d, 8) : "r"(a[0]), "r"(a[1]), "r"(a[2]), "r"(a[3]), "l"(vd));
}
__device__ __forceinline__ void touch16(float* d) { asm volatile("" : F16(d, 0) :: "memory"); }
__device__ __forceinline__ void touch12(float* d) { asm volatile("" : F4(d, 0), F4(d, 4), F4(d, 8) :: "memory"); }
__device__ __forceinline__ void touch32(float* d) { asm volatile("" : F32(d, 0) :: "memory"); }
__device__ __forceinline__ void touch96(float* d) { asm volatile("" : F32(d, 0), F32(d, 32), F32(d, 64) :: "memory"); }

__device__ __forceinline__ float ln_elem(float x, float mean_b, float rden) {
    return bf16r(bf16r(x - mean_b) * rden);
}
__device__ __forceinline__ void pdl_wait() { asm volatile("griddepcontrol.wait;" ::: "memory"); }
__device__ __forceinline__ void pdl_launch() { asm volatile("griddepcontrol.launch_dependents;" ::: "memory"); }

constexpr int K1_THREADS = 320;
constexpr int K1_SMEM = 131072 + 6 * 16384 + 256 + 1024;

__device__ __forceinline__ void ldsm4(uint32_t* r, uint32_t addr) {
    asm volatile("ldmatrix.sync.aligned.m8n8.x4.shared.b16 {%0, %1, %2, %3}, [%4];" : "=r"(r[0]), "=r"(r[1]), "=r"(r[2]), "=r"(r[3]) : "r"(addr) : "memory");
}
__device__ __forceinline__ void stsm4(uint32_t addr, uint32_t r0, uint32_t r1, uint32_t r2, uint32_t r3) {
    asm volatile("stmatrix.sync.aligned.m8n8.x4.shared.b16 [%0], {%1, %2, %3, %4};" :: "r"(addr), "r"(r0), "r"(r1), "r"(r2), "r"(r3) : "memory");
}
__device__ __forceinline__ void mma16816(float* d, const uint32_t* a, uint32_t b0, uint32_t b1) {
    asm("mma.sync.aligned.m16n8k16.row.col.f32.bf16.bf16.f32 {%0,%1,%2,%3}, {%4,%5,%6,%7}, {%8,%9}, {%0,%1,%2,%3};"
        : "+f"(d[0]), "+f"(d[1]), "+f"(d[2]), "+f"(d[3]) : "r"(a[0]), "r"(a[1]), "r"(a[2]), "r"(a[3]), "r"(b0), "r"(b1));
}
__device__ __forceinline__ uint32_t sub_bf16x2(uint32_t a, uint32_t b) {
    uint32_t d; asm("sub.rn.bf16x2 %0, %1, %2;" : "=r"(d) : "r"(a), "r"(b)); return d;
}
__device__ __forceinline__ uint32_t ln_pair(uint32_t x2, uint32_t mean2, uint32_t rhi2, uint32_t rlo2) {
    const uint32_t d = sub_bf16x2(x2, mean2);
    uint32_t t, y;
    asm("mul.rn.bf16x2 %0, %1, %2;" : "=r"(t) : "r"(d), "r"(rlo2));
    asm("fma.rn.bf16x2 %0, %1, %2, %3;" : "=r"(y) : "r"(d), "r"(rhi2), "r"(t));
    return y;
}
struct LnRow { uint32_t m2, hi2, lo2; };
__device__ __forceinline__ LnRow ln_row(float mean, float rden) {
    LnRow r;
    r.m2 = pack_bf16(mean, mean);
    r.hi2 = pack_bf16(rden, rden);
    const float lo = rden - bf_lo(r.hi2);
    r.lo2 = pack_bf16(lo, lo);
    return r;
}
__device__ __forceinline__ void ln_frag(uint32_t* a, const LnRow& r0, const LnRow& r1) {
    a[0] = ln_pair(a[0], r0.m2, r0.hi2, r0.lo2); a[1] = ln_pair(a[1], r1.m2, r1.hi2, r1.lo2);
    a[2] = ln_pair(a[2], r0.m2, r0.hi2, r0.lo2); a[3] = ln_pair(a[3], r1.m2, r1.hi2, r1.lo2);
}

template <int NJ>
__device__ __forceinline__ void k1_store(const float* acc, int jj0, uint32_t stage, int nt, int mt, int wg, int w4, int lane) {
    const int mi = lane >> 3, lr = lane & 7;
    const uint32_t off_qk = stage + (w4 * 2 + (mi & 1)) * 256 + (mi >> 1) * 128 + lr * 16;
    const uint32_t off_v = stage + (mi >> 1) * 1024 + (w4 * 16 + (mi & 1) * 8 + lr) * 16;
    #pragma unroll
    for (int jj = 0; jj < NJ; jj++) {
        const bool isv = nt * 12 + jj0 + jj >= 64;
        const float m = isv ? 1.0f : 8.8817841970012523e-16f;
        stsm4((isv ? off_v : off_qk) + jj * 2048,
              pack_bf16(acc[8 * jj] * m, acc[8 * jj + 1] * m), pack_bf16(acc[8 * jj + 2] * m, acc[8 * jj + 3] * m),
              pack_bf16(acc[8 * jj + 4] * m, acc[8 * jj + 5] * m), pack_bf16(acc[8 * jj + 6] * m, acc[8 * jj + 7] * m));
    }
    fence_async_smem();
    named_bar(1 + wg, 128);
    if (lane < NJ / 2) {
        const int pc = w4 * (NJ / 2) + lane, jj = pc >> 1, hf = pc & 1, hg = nt * 12 + jj0 + jj;
        const unsigned char* dst = (const unsigned char*)g_QKV + (size_t)hg * 65536
            + (hg >= 64 ? hf * 32768 + (mt * 128 + wg * 64) * 16 : (mt * 16 + wg * 8) * 256 + hf * 1024);
        asm volatile("cp.async.bulk.global.shared::cta.bulk_group [%0], [%1], 1024;" :: "l"(dst), "r"(stage + pc * 1024) : "memory");
        asm volatile("cp.async.bulk.commit_group;" ::: "memory");
    }
}

__global__ void __launch_bounds__(K1_THREADS, 1)
k1_ln_qkv(const __grid_constant__ CUtensorMap wmap, const __grid_constant__ CUtensorMap xmap, const __nv_bfloat16* __restrict__ w_r) {
    extern __shared__ __align__(1024) unsigned char smem[];
    const uint32_t sA = smem_u32(smem), sB = sA + 131072, sBar = sB + 4 * 24576;
    const int warp = __shfl_sync(~0u, threadIdx.x >> 5, 0), lane = threadIdx.x & 31;
    const int nt = blockIdx.x & 7, mt = blockIdx.x >> 3;
    const int tile = warp < 8 ? warp : nt;
    const int wg = tile >> 2;
    pdl_launch();
    uint32_t* s_wr = (uint32_t*)(smem + 131072 + 4 * 24576 + 256);
    if (warp == 8) {
        if (lane == 0) {
            for (int i = 0; i < 4; i++) { mbar_init(sBar + i * 8, 1); mbar_init(sBar + 48 + i * 8, 2); }
            asm volatile("fence.mbarrier_init.release.cluster;" ::: "memory");
            for (int i = 0; i < 4; i++) mbar_expect_tx(sBar + i * 8, 24576);
        }
        if (lane < 4) {
            mbar_init(sBar + 96 + lane * 8, 1);
            asm volatile("fence.mbarrier_init.release.cluster;" ::: "memory");
            mbar_expect_tx(sBar + 96 + lane * 8, 32768);
        }
        __syncwarp();
        if (lane < 16) {
            const int pn = (lane >> 3) * 4 + (lane & 3), hf = (lane >> 2) & 1;
            tma_2d(sA + pn * 16384 + hf * 8192, &xmap, pn * 64, mt * 128 + hf * 64, sBar + 96 + (lane >> 2) * 8);
        }
        named_bar(3, K1_THREADS);
        mbar_wait(sBar + 96 + 8, 0);
        if (lane < 12) {
            const int ld = lane / 3, j = lane % 3;
            tma_2d(sB + ld * 24576 + j * 8192, &wmap, nt * 192 + j * 64, ld * 64, sBar + ld * 8);
        }
        __syncwarp();
        if (lane < 3) {
            for (int ld = 4; ld < 8; ld++) {
                const int sl = ld - 4;
                mbar_wait(sBar + 48 + sl * 8, 0);
                if (lane == 0) mbar_expect_tx(sBar + sl * 8, 24576);
                __syncwarp(7);
                tma_2d(sB + sl * 24576 + lane * 8192, &wmap, nt * 192 + lane * 64, ld * 64, sBar + sl * 8);
            }
        }
        return;
    }
    if (warp == 9) {
        #pragma unroll
        for (int i = 0; i < 8; i++) s_wr[i * 32 + lane] = __ldg((const uint32_t*)w_r + i * 32 + lane);
    }
    named_bar(3, K1_THREADS);
    const int g = lane >> 2, t = lane & 3;
    const int lrow = tile * 16 + (lane & 7) + ((lane >> 3) & 1) * 8;
    const uint32_t lbase = sA + lrow * 128;
    const int lsw = lane & 7, lhi = lane >> 4;
    uint32_t laddr[4];
    #pragma unroll
    for (int k4 = 0; k4 < 4; k4++) laddr[k4] = lbase + (((k4 * 2 + lhi) ^ lsw) * 16);
    float dsum[4] = {0.f, 0.f, 0.f, 0.f}, dq0[4] = {0.f, 0.f, 0.f, 0.f}, dq1[4] = {0.f, 0.f, 0.f, 0.f};
    float esum[4] = {0.f, 0.f, 0.f, 0.f}, eq0[4] = {0.f, 0.f, 0.f, 0.f}, eq1[4] = {0.f, 0.f, 0.f, 0.f};
    #pragma unroll 2
    for (int pn = 0; pn < 8; pn++) {
        uint32_t a[4][4];
        if ((pn & 3) == 0) mbar_wait(sBar + 96 + ((pn >> 2) * 2 + wg) * 8, 0);
        #pragma unroll
        for (int k4 = 0; k4 < 4; k4++) ldsm4(a[k4], laddr[k4] + pn * 16384);
        #pragma unroll
        for (int k4 = 0; k4 < 4; k4 += 2) {
            mma16816(dsum, a[k4], 0x3F803F80u, 0x3F803F80u);
            mma16816(dq0, a[k4], a[k4][0], a[k4][2]);
            mma16816(dq1, a[k4], a[k4][1], a[k4][3]);
            mma16816(esum, a[k4 + 1], 0x3F803F80u, 0x3F803F80u);
            mma16816(eq0, a[k4 + 1], a[k4 + 1][0], a[k4 + 1][2]);
            mma16816(eq1, a[k4 + 1], a[k4 + 1][1], a[k4 + 1][3]);
        }
    }
    #pragma unroll
    for (int i = 0; i < 4; i++) { dsum[i] += esum[i]; dq0[i] += eq0[i]; dq1[i] += eq1[i]; }
    const int dsrc = g * 4 + (g >> 1);
    const float sq0 = __shfl_sync(~0u, (g & 1) ? dq0[1] : dq0[0], dsrc), sq1 = __shfl_sync(~0u, (g & 1) ? dq1[3] : dq1[2], dsrc);
    const float mean0 = dsum[0] * (1.0f / D_), mean1 = dsum[2] * (1.0f / D_);
    float var0 = fmaf(-mean0, mean0, sq0 * (1.0f / D_)), var1 = fmaf(-mean1, mean1, sq1 * (1.0f / D_));
    if (__any_sync(~0u, !(mean0 * mean0 <= 16.0f * var0) || !(mean1 * mean1 <= 16.0f * var1))) {
        float q0 = 0.f, q1 = 0.f;
        #pragma unroll 1
        for (int ks = 0; ks < 32; ks++) {
            uint32_t a[4];
            ldsm4(a, lbase + (ks >> 2) * 16384 + ((((ks & 3) * 2 + lhi) ^ lsw) * 16));
            #pragma unroll
            for (int i = 0; i < 4; i++) {
                const float m = (i & 1) ? mean1 : mean0;
                const float d0 = bf_lo(a[i]) - m, d1 = bf_hi(a[i]) - m;
                if (i & 1) q1 = fmaf(d0, d0, fmaf(d1, d1, q1)); else q0 = fmaf(d0, d0, fmaf(d1, d1, q0));
            }
        }
        q0 += __shfl_xor_sync(~0u, q0, 1); q0 += __shfl_xor_sync(~0u, q0, 2);
        q1 += __shfl_xor_sync(~0u, q1, 1); q1 += __shfl_xor_sync(~0u, q1, 2);
        var0 = q0 * (1.0f / D_); var1 = q1 * (1.0f / D_);
    }
    const float rs0 = __frcp_rn(bf16r(__fsqrt_rn(bf16r(bf16r(var0) + 1e-5f))));
    const float rs1 = __frcp_rn(bf16r(__fsqrt_rn(bf16r(bf16r(var1) + 1e-5f))));
    const LnRow lr0 = ln_row(mean0, rs0), lr1 = ln_row(mean1, rs1);
    if (warp == 9) {
        float d0 = 0.f, d1 = 0.f, e0 = 0.f, e1 = 0.f;
        #pragma unroll 2
        for (int pn = 0; pn < 8; pn++) {
            uint32_t a[4][4];
            #pragma unroll
            for (int k4 = 0; k4 < 4; k4++) ldsm4(a[k4], laddr[k4] + pn * 16384);
            #pragma unroll
            for (int k4 = 0; k4 < 4; k4++) {
                ln_frag(a[k4], lr0, lr1);
                const uint32_t w0 = s_wr[(pn * 4 + k4) * 8 + t], w1 = s_wr[(pn * 4 + k4) * 8 + 4 + t];
                d0 = fmaf(bf_lo(a[k4][0]), bf_lo(w0), d0); e0 = fmaf(bf_hi(a[k4][0]), bf_hi(w0), e0);
                d1 = fmaf(bf_lo(a[k4][1]), bf_lo(w0), d1); e1 = fmaf(bf_hi(a[k4][1]), bf_hi(w0), e1);
                d0 = fmaf(bf_lo(a[k4][2]), bf_lo(w1), d0); e0 = fmaf(bf_hi(a[k4][2]), bf_hi(w1), e0);
                d1 = fmaf(bf_lo(a[k4][3]), bf_lo(w1), d1); e1 = fmaf(bf_hi(a[k4][3]), bf_hi(w1), e1);
            }
        }
        d0 += e0; d1 += e1;
        d0 += __shfl_xor_sync(~0u, d0, 1); d0 += __shfl_xor_sync(~0u, d0, 2);
        d1 += __shfl_xor_sync(~0u, d1, 1); d1 += __shfl_xor_sync(~0u, d1, 2);
        if (t == 0) {
            const int row0 = mt * 128 + tile * 16;
            g_r[row0 + g] = bf16r(d0); g_r[row0 + g + 8] = bf16r(d1);
            g_stats[row0 + g] = make_float2(bf_lo(lr0.m2), rs0); g_stats[row0 + g + 8] = make_float2(bf_lo(lr1.m2), rs1);
        }
        asm volatile("bar.arrive %0, %1;" :: "r"(4 + wg), "r"(160) : "memory");
        return;
    }
    float acc[96];
    #pragma unroll
    for (int i = 0; i < 96; i++) acc[i] = 0.f;
    const uint64_t db0 = make_desc(sB, 8192, 1024, 1);
    uint32_t a[2][4][4];
    #pragma unroll
    for (int k4 = 0; k4 < 4; k4++) ldsm4(a[0][k4], laddr[k4]);
    #pragma unroll
    for (int k4 = 0; k4 < 4; k4++) ln_frag(a[0][k4], lr0, lr1);
    #pragma unroll 1
    for (int kc = 0; kc < 8; kc += 2) {
        #pragma unroll
        for (int h2 = 0; h2 < 2; h2++) {
            const int ld = kc + h2, sl = ld & 3;
            mbar_wait(sBar + sl * 8, ld >> 2);
            WG_FENCE();
            #pragma unroll
            for (int k4 = 0; k4 < 4; k4++) wgmma_rs_n192(acc, a[h2][k4], db0 + (uint64_t)(sl * 1536 + k4 * 128));
            WG_COMMIT();
            wg_wait<1>();
            if (ld >= 1 && ld <= 4 && (threadIdx.x & 127) == 0) mbar_arrive(sBar + 48 + (ld - 1) * 8);
            #pragma unroll
            for (int k4 = 0; k4 < 4; k4++) ldsm4(a[h2 ^ 1][k4], laddr[k4] + ((ld + 1) & 7) * 16384);
            #pragma unroll
            for (int k4 = 0; k4 < 4; k4++) ln_frag(a[h2 ^ 1][k4], lr0, lr1);
        }
    }
    wg_wait<0>();
    touch96(acc);
    if ((nt >> 2) == wg) named_bar(4 + wg, 160); else named_bar(1 + wg, 128);
    k1_store<4>(acc, 0, sA + wg * 8192, nt, mt, wg, warp & 3, lane);
    k1_store<4>(acc + 32, 4, sA + 16384 + wg * 8192, nt, mt, wg, warp & 3, lane);
    k1_store<4>(acc + 64, 8, sA + 32768 + wg * 8192, nt, mt, wg, warp & 3, lane);
    asm volatile("cp.async.bulk.wait_group.read 0;" ::: "memory");
}

constexpr int K2_THREADS = 512;
constexpr int K2_SMEM = 6 * 32768 + 12288;

constexpr float QS = 0.25f * 1.4426950408889634f;
constexpr float SC100 = 1.2676506002282294e30f;
__device__ __forceinline__ uint32_t polyexp2(float s0, float s1, float cd, float cdb, uint32_t one2, uint32_t ca2) {
    constexpr float A = 128.0f * QS * 1.7763568394002505e-15f;
    float t0, t1;
    asm("fma.rn.f32 %0, %1, %2, %3;" : "=f"(t0) : "f"(s0), "f"(A), "f"(cd));
    asm("fma.rn.f32 %0, %1, %2, %3;" : "=f"(t1) : "f"(s1), "f"(A), "f"(cdb));
    uint32_t W, U, h, G;
    asm("cvt.pack.sat.s16.s32 %0, %1, %2;" : "=r"(W) : "r"(__float_as_int(t1)), "r"(__float_as_int(t0)));
    asm("lop3.b32 %0, %1, 0x007F007F, %2, 0xEA;" : "=r"(U) : "r"(W), "r"(one2));
    asm("fma.rn.bf16x2 %0, %1, %2, %3;" : "=r"(h) : "r"(U), "r"(ca2), "r"(0xC300C300u));
    asm("fma.rn.bf16x2 %0, %1, %2, %3;" : "=r"(G) : "r"(h), "r"(U), "r"(0x438B438Bu));
    return W + G - 0x43404340u;
}

struct ExpC { float nm0, nm1, cd0, cd1, nm0b, nm1b, cd0b, cd1b; uint32_t one2, ca2; };

template <int G>
__device__ __forceinline__ void exp_block(const float* s, uint32_t* p, const ExpC& c) {
    #pragma unroll
    for (int hf = 0; hf < 2; hf++) {
        const float* x = s + hf * 4;
        if ((PMASK >> (G + hf)) & 1) {
            p[hf * 2 + 0] = polyexp2(x[0], x[1], c.cd0, c.cd0b, c.one2, c.ca2);
            p[hf * 2 + 1] = polyexp2(x[2], x[3], c.cd1, c.cd1b, c.one2, c.ca2);
        } else {
            p[hf * 2 + 0] = pack_bf16(ex2(fmaf(x[0], QS * SC100, c.nm0)), ex2(fmaf(x[1], QS * SC100, c.nm0b)));
            p[hf * 2 + 1] = pack_bf16(ex2(fmaf(x[2], QS * SC100, c.nm1)), ex2(fmaf(x[3], QS * SC100, c.nm1b)));
        }
    }
}

__device__ __forceinline__ void max16(const float* s, float& mx0, float& mx1) {
    #pragma unroll
    for (int j = 0; j < 4; j++) {
        mx0 = fmaxf(mx0, fmaxf(s[4 * j], s[4 * j + 1]));
        mx1 = fmaxf(mx1, fmaxf(s[4 * j + 2], s[4 * j + 3]));
    }
}

constexpr int MOE_SLOTS = 6, MOE_BOXES = 44;
__device__ __forceinline__ void moe_load(int b, int part, uint32_t ring, uint32_t bars, const CUtensorMap* mg, const CUtensorMap* mu, const CUtensorMap* md) {
    const int sl = b % MOE_SLOTS, grp = b & 1;
    if (b < 28) {
        const int j = b >> 1;
        mbar_expect_tx(bars + sl * 8, 32768);
        tma_2d(ring + sl * 32768, grp ? mu : mg, part * 448 + (j >> 1) * 64, (j & 1) * 256, bars + sl * 8);
    } else {
        const int j = (b - 28) >> 1;
        mbar_expect_tx(bars + sl * 8, 28672);
        tma_2d(ring + sl * 32768, md, ((j >> 1) * 2 + grp) * 64, part * 448 + (j & 1) * 224, bars + sl * 8);
    }
}
__device__ __forceinline__ void mma_2row(float* d, uint32_t a0, uint32_t a2, uint32_t b0, uint32_t b1) {
    asm("mma.sync.aligned.m16n8k16.row.col.f32.bf16.bf16.f32 {%0,%1,%2,%3}, {%4,%5,%6,%5}, {%7,%8}, {%0,%1,%2,%3};"
        : "+f"(d[0]), "+f"(d[1]), "+f"(d[2]), "+f"(d[3]) : "r"(a0), "r"(0u), "r"(a2), "r"(b0), "r"(b1));
}

__device__ void moe_cta(int part, unsigned char* smem, const __nv_bfloat16* __restrict__ x, const CUtensorMap* mg, const CUtensorMap* mu, const CUtensorMap* md) {
    const uint32_t ring = smem_u32(smem), bars = ring + MOE_SLOTS * 32768;
    __nv_bfloat16* xs = (__nv_bfloat16*)(smem + MOE_SLOTS * 32768 + 256);
    float* gu = (float*)(smem + MOE_SLOTS * 32768 + 256 + 2048);
    float* s_v = gu + 4 * 448;
    int* s_i = (int*)(s_v + 16);
    int* s_sel = s_i + 16;
    const int tid = threadIdx.x, warp = __shfl_sync(~0u, tid >> 5, 0), lane = tid & 31;
    if (tid == 0) {
        for (int i = 0; i < MOE_SLOTS; i++) { mbar_init(bars + i * 8, 1); mbar_init(bars + 128 + i * 8, 8); }
        asm volatile("fence.mbarrier_init.release.cluster;" ::: "memory");
        for (int b = 0; b < MOE_SLOTS; b++) moe_load(b, part, ring, bars, mg, mu, md);
    }
    pdl_wait();
    float rv[4];
    #pragma unroll
    for (int i = 0; i < 4; i++) rv[i] = g_r[tid + i * K2_THREADS];
    for (int pass = 0; pass < 2; pass++) {
        float bv = -INFINITY; int bi = 0x7fffffff;
        const int excl = pass ? s_sel[0] : -1;
        #pragma unroll
        for (int i = 0; i < 4; i++) {
            const int idx = tid + i * K2_THREADS;
            if (idx != excl && (rv[i] > bv || bi == 0x7fffffff)) { bv = rv[i]; bi = idx; }
        }
        #pragma unroll
        for (int o = 16; o; o >>= 1) {
            float ov = __shfl_xor_sync(~0u, bv, o); int oi = __shfl_xor_sync(~0u, bi, o);
            if (ov > bv || (ov == bv && oi < bi)) { bv = ov; bi = oi; }
        }
        if (lane == 0) { s_v[warp] = bv; s_i[warp] = bi; }
        __syncthreads();
        if (warp == 0) {
            bv = lane < 16 ? s_v[lane] : -INFINITY; bi = lane < 16 ? s_i[lane] : 0x7fffffff;
            #pragma unroll
            for (int o = 16; o; o >>= 1) {
                float ov = __shfl_xor_sync(~0u, bv, o); int oi = __shfl_xor_sync(~0u, bi, o);
                if (ov > bv || (ov == bv && oi < bi)) { bv = ov; bi = oi; }
            }
            if (lane == 0) s_sel[pass] = (bi == 0x7fffffff) ? pass : bi;
        }
        __syncthreads();
    }
    for (int i = tid; i < 1024; i += K2_THREADS) {
        const int tok = s_sel[i >> 9];
        const float2 st = g_stats[tok];
        xs[i] = __float2bfloat16_rn(ln_elem(__bfloat162float(x[(size_t)tok * D_ + (i & 511)]), st.x, st.y));
    }
    if (part == 0 && tid < 2) g_sel[tid] = s_sel[tid];
    __syncthreads();
    if (warp == 8) {
        if (lane == 0) {
            for (int b = MOE_SLOTS; b < MOE_BOXES; b++) {
                mbar_wait(bars + 128 + (b % MOE_SLOTS) * 8, (b / MOE_SLOTS - 1) & 1);
                moe_load(b, part, ring, bars, mg, mu, md);
            }
        }
        return;
    }
    if (warp > 8) return;
    const int nj = warp, g = lane >> 2, t = lane & 3;
    const uint32_t* xw = (const uint32_t*)xs + (g & 1) * 256 + t;
    uint32_t a[2][32];
    #pragma unroll
    for (int i = 0; i < 32; i++) { a[0][i] = xw[i * 4]; a[1][i] = xw[128 + i * 4]; }
    #pragma unroll 1
    for (int jp = 0; jp < MOE_BOXES / 4; jp++) {
        const bool down = jp >= 7;
        if (jp == 7) {
            named_bar(1, 256);
            for (int i = tid; i < 896; i += 256) {
                const float gs = bf16r(gu[i]), us = bf16r(gu[896 + i]);
                const float sl_ = bf16r(gs / (1.0f + __expf(-gs)));
                xs[(i / 448) * 512 + (i % 448)] = __float2bfloat16_rn(sl_ * us);
            }
            named_bar(1, 256);
            #pragma unroll
            for (int i = 0; i < 28; i++) { a[0][i] = xw[i * 4]; a[1][i] = xw[112 + i * 4]; }
        }
        float acc[2][4] = {{0.f, 0.f, 0.f, 0.f}, {0.f, 0.f, 0.f, 0.f}}, acb[2][4] = {{0.f, 0.f, 0.f, 0.f}, {0.f, 0.f, 0.f, 0.f}};
        #pragma unroll
        for (int q = 0; q < 4; q++) {
            const int hf = q >> 1, grp = q & 1;
            const int b = jp * 4 + q, sl = b % MOE_SLOTS;
            mbar_wait(bars + sl * 8, (b / MOE_SLOTS) & 1);
            const uint32_t baddr = ring + sl * 32768 + lane * 128 + ((nj ^ (lane & 7)) * 16);
            #pragma unroll
            for (int k4 = 0; k4 < 2; k4++) {
                uint32_t bf[4][4];
                #pragma unroll
                for (int k2 = 0; k2 < 4; k2++)
                    asm volatile("ldmatrix.sync.aligned.m8n8.x4.trans.shared.b16 {%0, %1, %2, %3}, [%4];"
                                 : "=r"(bf[k2][0]), "=r"(bf[k2][1]), "=r"(bf[k2][2]), "=r"(bf[k2][3]) : "r"(baddr + (k4 * 4 + k2) * 4096) : "memory");
                #pragma unroll
                for (int k2 = 0; k2 < 4; k2++) {
                    const int kk = k4 * 4 + k2;
                    if (kk < 7 || !down) {
                        mma_2row(acc[grp], a[hf][4 * kk], a[hf][4 * kk + 1], bf[k2][0], bf[k2][1]);
                        mma_2row(acb[grp], a[hf][4 * kk + 2], a[hf][4 * kk + 3], bf[k2][2], bf[k2][3]);
                    }
                }
            }
            __syncwarp();
            if (lane == 0) mbar_arrive(bars + 128 + sl * 8);
        }
        if (g < 2) {
            #pragma unroll
            for (int grp = 0; grp < 2; grp++) {
                const float2 v = make_float2(acc[grp][0] + acb[grp][0], acc[grp][1] + acb[grp][1]);
                if (!down) *(float2*)&gu[(grp * 2 + g) * 448 + jp * 64 + nj * 8 + t * 2] = v;
                else *(float2*)&g_ypart[part][g][((jp - 7) * 2 + grp) * 64 + nj * 8 + t * 2] = v;
            }
        }
    }
}

__global__ void __launch_bounds__(K2_THREADS, 1)
k2_attn(const __nv_bfloat16* __restrict__ x, const __nv_bfloat16* __restrict__ w_gate, const __nv_bfloat16* __restrict__ w_up,
        const __nv_bfloat16* __restrict__ w_down, const __grid_constant__ CUtensorMap mg, const __grid_constant__ CUtensorMap mu,
        const __grid_constant__ CUtensorMap md) {
    extern __shared__ __align__(1024) unsigned char smem[];
    pdl_launch();
    if (blockIdx.x >= 128) { moe_cta(blockIdx.x - 128, smem, x, &mg, &mu, &md); return; }
    if (threadIdx.x >= 32 && threadIdx.x < 35) {
        const __nv_bfloat16* w = threadIdx.x == 32 ? w_gate : (threadIdx.x == 33 ? w_up : w_down);
        asm volatile("cp.async.bulk.prefetch.L2.global [%0], %1;" :: "l"(w + (size_t)blockIdx.x * (D_ * F_ / 128)), "r"(D_ * F_ / 64) : "memory");
    }
    const uint32_t sK = smem_u32(smem), sV = sK + 65536, sQ = sV + 98304, sBar = sQ + 16384;
    const int h = blockIdx.x >> 2, qb = blockIdx.x & 3;
    const int warp = __shfl_sync(~0u, threadIdx.x >> 5, 0), lane = threadIdx.x & 31, wg = warp >> 2;
    if (threadIdx.x == 0) {
        mbar_init(sBar, 1); mbar_init(sBar + 8, 1);
        asm volatile("fence.mbarrier_init.release.cluster;" ::: "memory");
        mbar_expect_tx(sBar, 8192 + 12288 + 2 * 6144);
        mbar_expect_tx(sBar + 8, 8192 + 53248 + 2 * 26624);
    }
    for (int i = threadIdx.x; i < 2048; i += K2_THREADS)
        *(uint4*)(smem + 65536 + 65536 + i * 16) = make_uint4(0x3F803F80u, 0x3F803F80u, 0x3F803F80u, 0x3F803F80u);
    fence_async_smem();
    __syncthreads();
    if (warp == 0) {
        pdl_wait();
        const uint4* gk = g_K + (size_t)h * 4096;
        const uint4* gv = g_V + (size_t)h * 4096;
        const uint4* gq = g_Q + (size_t)h * 4096 + qb * 1024;
        if (lane == 0) bulk_g2s(sQ, gq, 8192, sBar);
        if (lane == 1) bulk_g2s(sK, gk, 12288, sBar);
        if (lane == 2) bulk_g2s(sV, gv, 6144, sBar);
        if (lane == 3) bulk_g2s(sV + 32768, gv + 2048, 6144, sBar);
        if (lane == 4) bulk_g2s(sK + 12288, gk + 768, 53248, sBar + 8);
        if (lane == 5) bulk_g2s(sV + 6144, gv + 384, 26624, sBar + 8);
        if (lane == 6) bulk_g2s(sV + 32768 + 6144, gv + 2048 + 384, 26624, sBar + 8);
        if (lane == 7) bulk_g2s(sQ + 8192, gq + 512, 8192, sBar + 8);
        __syncwarp();
    }
    ExpC c;
    {
        const volatile uint32_t* cc = g_const;
        c.one2 = cc[0]; c.ca2 = cc[1];
    }
    const uint64_t kdesc0 = make_desc(sK, 128, 256, 0);
    const uint64_t vdesc0 = make_desc(sV, 128, 32768, 0);
    #pragma unroll 1
    for (int pass = 0; pass < 2; pass++) {
        if (pass == 0) { mbar_wait(sBar, 0); __syncwarp(); }
        const int unit = pass * 4 + wg;
        const uint64_t q = make_desc(sQ + unit * 2048, 128, 256, 0);
        float o[12];
        #pragma unroll 1
        for (int attempt = 0; attempt < 2; attempt++) {
            float s0[16], s1[16], s2[16];
            #pragma unroll
            for (int i = 0; i < 16; i++) { s0[i] = 0.f; s1[i] = 0.f; s2[i] = 0.f; }
            float mx0 = -INFINITY, mx1 = -INFINITY;
            if (attempt) {
                #pragma unroll 1
                for (int it = 0; it < 64; it++) {
                    WG_FENCE();
                    wgmma_qk32(s0, q, kdesc0 + it * 64);
                    WG_COMMIT();
                    wg_wait<0>();
                    touch16(s0);
                    max16(s0, mx0, mx1);
                }
            }
            #pragma unroll
            for (int i = 0; i < 12; i++) o[i] = 0.f;
            WG_FENCE();
            wgmma_qk32(s2, q, kdesc0);
            wgmma_qk32(s0, q, kdesc0 + 64);
            wgmma_qk32(s1, q, kdesc0 + 128);
            WG_COMMIT();
            wg_wait<0>();
            touch16(s0); touch16(s1); touch16(s2);
            max16(s0, mx0, mx1); max16(s1, mx0, mx1); max16(s2, mx0, mx1);
            mx0 = fmaxf(mx0, __shfl_xor_sync(~0u, mx0, 1)); mx0 = fmaxf(mx0, __shfl_xor_sync(~0u, mx0, 2));
            mx1 = fmaxf(mx1, __shfl_xor_sync(~0u, mx1, 1)); mx1 = fmaxf(mx1, __shfl_xor_sync(~0u, mx1, 2));
            const float bias = attempt ? 0.0f : 128.0f * 64.0f;
            const float y0 = ceilf(fmaf(mx0, 128.0f * QS * SC100, bias)), y1 = ceilf(fmaf(mx1, 128.0f * QS * SC100, bias));
            c.nm0 = __shfl_sync(~0u, y0 * (-1.0f / 128.0f), lane); c.nm1 = __shfl_sync(~0u, y1 * (-1.0f / 128.0f), lane);
            c.cd0 = __shfl_sync(~0u, __fmul_rn(16256.0f - y0, __int_as_float(1)), lane);
            c.cd1 = __shfl_sync(~0u, __fmul_rn(16256.0f - y1, __int_as_float(1)), lane);
            c.nm0b = __shfl_xor_sync(~0u, c.nm0, 1); c.nm1b = __shfl_xor_sync(~0u, c.nm1, 1);
            c.cd0b = __shfl_xor_sync(~0u, c.cd0, 1); c.cd1b = __shfl_xor_sync(~0u, c.cd1, 1);
            uint64_t kd = kdesc0 + 192, vd = vdesc0 + 32;
            {
                uint32_t pa[4], pb[4];
                exp_block<12>(s2, pa, c);
                exp_block<14>(s2 + 8, pb, c);
                WG_FENCE();
                wgmma_pv(o, pa, vdesc0); wgmma_pv(o, pb, vdesc0 + 16);
                WG_COMMIT();
            }
            #pragma unroll 1
            for (int seg = 0; seg < 2; seg++) {
            if (seg) { wg_wait<0>(); mbar_wait(sBar + 8, 0); __syncwarp(); }
            #pragma unroll 1
            for (int it = seg ? 3 : 0; it < (seg ? 21 : 3); it++) {
                uint32_t p[6][4];
                WG_FENCE();
                wgmma_qk32(s2, q, kd);
                WG_COMMIT();
                exp_block<0>(s0, p[0], c);
                exp_block<2>(s0 + 8, p[1], c);
                WG_FENCE();
                wgmma_pv(o, p[0], vd); wgmma_pv(o, p[1], vd + 16);
                wgmma_qk32(s0, q, kd + 64);
                WG_COMMIT();
                wg_wait<1>();
                touch16(s2);
                exp_block<4>(s1, p[2], c);
                exp_block<6>(s1 + 8, p[3], c);
                WG_FENCE();
                wgmma_pv(o, p[2], vd + 32); wgmma_pv(o, p[3], vd + 48);
                wgmma_qk32(s1, q, kd + 128);
                WG_COMMIT();
                wg_wait<1>();
                touch16(s0);
                exp_block<8>(s2, p[4], c);
                exp_block<10>(s2 + 8, p[5], c);
                WG_FENCE();
                wgmma_pv(o, p[4], vd + 64); wgmma_pv(o, p[5], vd + 80);
                WG_COMMIT();
                vd += 96; kd += 192;
                wg_wait<1>();
                touch16(s1);
            }
            }
            wg_wait<0>();
            touch12(o);
            if (attempt) break;
            float big = 0.f;
            #pragma unroll
            for (int i = 0; i < 12; i++) big = fmaxf(big, fabsf(o[i]));
            bool bad = !(big < 1e30f);
            #pragma unroll
            for (int i = 0; i < 12; i++) bad |= (o[i] != o[i]);
            uint32_t any;
            asm volatile("{.reg .pred p, q; setp.ne.u32 p, %1, 0; barrier.cta.red.or.pred.aligned q, %2, 128, p; selp.u32 %0, 1, 0, q;}"
                         : "=r"(any) : "r"((uint32_t)bad), "r"(1 + wg) : "memory");
            if (!__any_sync(~0u, any)) break;
        }
        const int g = lane >> 2, t = lane & 3;
        const int r = (warp & 3) * 16 + g;
        const float i0 = __fdiv_rn(1.0f, o[8]), i1 = __fdiv_rn(1.0f, o[10]);
        uint32_t* ob = (uint32_t*)(g_O + (size_t)(qb * 8 + unit) * 4096 + (h >> 2) * 512 + r * 8) + t;
        const int c0 = ((h & 3) * 2) ^ (r & 7), c1 = ((h & 3) * 2 + 1) ^ (r & 7);
        ob[c0 * 4] = pack_bf16(o[0] * i0, o[1] * i0);
        ob[c1 * 4] = pack_bf16(o[4] * i0, o[5] * i0);
        ob[256 + c0 * 4] = pack_bf16(o[2] * i1, o[3] * i1);
        ob[256 + c1 * 4] = pack_bf16(o[6] * i1, o[7] * i1);
    }
}

constexpr int K3_THREADS = 256;
constexpr int K3_SMEM = 65536 + 131072 + 128;

__global__ void __launch_bounds__(K3_THREADS, 1)
k3_out(const __grid_constant__ CUtensorMap wmap, const __nv_bfloat16* __restrict__ x, __nv_bfloat16* __restrict__ out) {
    extern __shared__ __align__(1024) unsigned char smem[];
    const uint32_t sA = smem_u32(smem), sB = sA + 65536, sBar = sB + 131072;
    const int warp = __shfl_sync(~0u, threadIdx.x >> 5, 0), lane = threadIdx.x & 31, wg = warp >> 2;
    const int nt = blockIdx.x & 3, mt = blockIdx.x >> 2;
    if (threadIdx.x == 0) {
        for (int i = 0; i < 10; i++) mbar_init(sBar + i * 8, 1);
        asm volatile("fence.mbarrier_init.release.cluster;" ::: "memory");
        for (int i = 0; i < 8; i++) mbar_expect_tx(sBar + 16 + i * 8, 8192);
        for (int kh = 0; kh < 2; kh++) {
            mbar_expect_tx(sBar + kh * 8, 65536);
            tma_2d(sB + kh * 32768, &wmap, nt * 128, kh * 256, sBar + kh * 8);
            tma_2d(sB + 65536 + kh * 32768, &wmap, nt * 128 + 64, kh * 256, sBar + kh * 8);
        }
    }
    const int er = threadIdx.x >> 2, ec = (threadIdx.x & 3) * 32;
    const int row = mt * 64 + er;
    uint4 xv[4];
    #pragma unroll
    for (int j = 0; j < 4; j++) xv[j] = __ldg((const uint4*)(x + (size_t)row * D_ + nt * 128 + ec) + j);
    __syncthreads();
    pdl_wait();
    if (threadIdx.x < 8) bulk_g2s(sA + threadIdx.x * 8192, g_O + (size_t)mt * 4096 + threadIdx.x * 512, 8192, sBar + 16 + threadIdx.x * 8);
    const int sel0 = g_sel[0], sel1 = g_sel[1];
    const float2 st = g_stats[row];
    float acc[32];
    #pragma unroll
    for (int i = 0; i < 32; i++) acc[i] = 0.f;
    const uint64_t da0 = make_desc(sA, 16, 1024, 1);
    const uint64_t db0 = make_desc(sB + wg * 65536, 8192, 1024, 1);
    #pragma unroll 1
    for (int q = 0; q < 8; q++) {
        if ((q & 3) == 0) mbar_wait(sBar + (q >> 2) * 8, 0);
        mbar_wait(sBar + 16 + q * 8, 0);
        WG_FENCE();
        #pragma unroll
        for (int kk = 0; kk < 4; kk++)
            wgmma_n64(acc, da0 + (uint64_t)(q * 512 + kk * 2), db0 + (uint64_t)(q * 512 + kk * 128));
        WG_COMMIT();
    }
    uint32_t bb[16];
    {
        const uint32_t xu[16] = {xv[0].x, xv[0].y, xv[0].z, xv[0].w, xv[1].x, xv[1].y, xv[1].z, xv[1].w,
                                 xv[2].x, xv[2].y, xv[2].z, xv[2].w, xv[3].x, xv[3].y, xv[3].z, xv[3].w};
        #pragma unroll
        for (int j = 0; j < 16; j++) bb[j] = pack_bf16(bf16r(bf_lo(xu[j]) - st.x) * st.y, bf16r(bf_hi(xu[j]) - st.x) * st.y);
        const int slot = row == sel0 ? 0 : (row == sel1 ? 1 : -1);
        if (slot >= 0) {
            const float gate = bf16r(1.0f / (1.0f + __expf(-g_r[row])));
            const int c0 = nt * 128 + ec;
            #pragma unroll
            for (int j = 0; j < 16; j++) {
                const float2 a = *(const float2*)&g_ypart[0][slot][c0 + 2 * j], b = *(const float2*)&g_ypart[1][slot][c0 + 2 * j];
                const float2 c = *(const float2*)&g_ypart[2][slot][c0 + 2 * j], d = *(const float2*)&g_ypart[3][slot][c0 + 2 * j];
                bb[j] = pack_bf16(bf_lo(bb[j]) + bf16r(bf16r(a.x + b.x + c.x + d.x) * gate), bf_hi(bb[j]) + bf16r(bf16r(a.y + b.y + c.y + d.y) * gate));
            }
        }
    }
    wg_wait<0>();
    touch32(acc);
    __syncthreads();
    {
        const int g = lane >> 2, t = lane & 3;
        unsigned char* sp = smem + ((warp & 3) * 16 + g) * 272 + wg * 128 + t * 4;
        #pragma unroll
        for (int j = 0; j < 8; j++) {
            *(uint32_t*)(sp + j * 16) = pack_bf16(acc[4 * j], acc[4 * j + 1]);
            *(uint32_t*)(sp + 8 * 272 + j * 16) = pack_bf16(acc[4 * j + 2], acc[4 * j + 3]);
        }
    }
    __syncthreads();
    #pragma unroll
    for (int j = 0; j < 4; j++) {
        const uint4 av = *(const uint4*)(smem + er * 272 + ec * 2 + j * 16);
        const uint32_t au[4] = {av.x, av.y, av.z, av.w}, xu[4] = {xv[j].x, xv[j].y, xv[j].z, xv[j].w};
        uint32_t o[4];
        #pragma unroll
        for (int i = 0; i < 4; i++) {
            uint32_t t2;
            asm("add.rn.bf16x2 %0, %1, %2;" : "=r"(t2) : "r"(xu[i]), "r"(au[i]));
            asm("add.rn.bf16x2 %0, %1, %2;" : "=r"(o[i]) : "r"(t2), "r"(bb[j * 4 + i]));
        }
        *((uint4*)(out + (size_t)row * D_ + nt * 128 + ec) + j) = make_uint4(o[0], o[1], o[2], o[3]);
    }
}

typedef CUresult (*EncodeFn)(CUtensorMap*, CUtensorMapDataType, cuuint32_t, void*, const cuuint64_t*, const cuuint64_t*,
                             const cuuint32_t*, const cuuint32_t*, CUtensorMapInterleave, CUtensorMapSwizzle,
                             CUtensorMapL2promotion, CUtensorMapFloatOOBfill);

void make_wmap(EncodeFn fn, CUtensorMap* map, const void* ptr, int rows, int cols, int box_rows) {
    cuuint64_t dims[2] = {(cuuint64_t)cols, (cuuint64_t)rows};
    cuuint64_t strides[1] = {(cuuint64_t)cols * 2};
    cuuint32_t box[2] = {64, (cuuint32_t)box_rows};
    cuuint32_t es[2] = {1, 1};
    fn(map, CU_TENSOR_MAP_DATA_TYPE_BFLOAT16, 2, (void*)ptr, dims, strides, box, es, CU_TENSOR_MAP_INTERLEAVE_NONE,
       CU_TENSOR_MAP_SWIZZLE_128B, CU_TENSOR_MAP_L2_PROMOTION_L2_256B, CU_TENSOR_MAP_FLOAT_OOB_FILL_NONE);
}

}

extern "C" void kernel_launch(void* const* d_in, const int* in_sizes, int n_in, void* d_out, int out_size) {
    const __nv_bfloat16* x = (const __nv_bfloat16*)d_in[0];
    const __nv_bfloat16* wqkv = (const __nv_bfloat16*)d_in[1];
    const __nv_bfloat16* wo = (const __nv_bfloat16*)d_in[2];
    const __nv_bfloat16* w_r = (const __nv_bfloat16*)d_in[4];
    const __nv_bfloat16* w_gate = (const __nv_bfloat16*)d_in[5];
    const __nv_bfloat16* w_up = (const __nv_bfloat16*)d_in[6];
    const __nv_bfloat16* w_down = (const __nv_bfloat16*)d_in[7];
    __nv_bfloat16* out = (__nv_bfloat16*)d_out;

    static EncodeFn encode = nullptr;
    if (!encode) {
        void* fn = nullptr;
        cudaDriverEntryPointQueryResult qres;
        cudaGetDriverEntryPoint("cuTensorMapEncodeTiled", &fn, cudaEnableDefault, &qres);
        encode = (EncodeFn)fn;
        cudaFuncSetAttribute(k1_ln_qkv, cudaFuncAttributeMaxDynamicSharedMemorySize, K1_SMEM);
        cudaFuncSetAttribute(k2_attn, cudaFuncAttributeMaxDynamicSharedMemorySize, K2_SMEM);
        cudaFuncSetAttribute(k3_out, cudaFuncAttributeMaxDynamicSharedMemorySize, K3_SMEM);
    }
    CUtensorMap map_qkv, map_wo, map_x, map_g, map_u, map_d;
    make_wmap(encode, &map_g, w_gate, D_, F_, 256);
    make_wmap(encode, &map_u, w_up, D_, F_, 256);
    make_wmap(encode, &map_d, w_down, F_, D_, 224);
    make_wmap(encode, &map_x, x, S_, D_, 64);
    make_wmap(encode, &map_qkv, wqkv, D_, 3 * D_, 64);
    make_wmap(encode, &map_wo, wo, D_, D_, 256);

    k1_ln_qkv<<<128, K1_THREADS, K1_SMEM, cudaStreamPerThread>>>(map_qkv, map_x, w_r);
    cudaLaunchAttribute at[1];
    at[0].id = cudaLaunchAttributeProgrammaticStreamSerialization;
    at[0].val.programmaticStreamSerializationAllowed = 1;
    cudaLaunchConfig_t cfg = {};
    cfg.stream = cudaStreamPerThread;
    cfg.attrs = at; cfg.numAttrs = 1;
    cfg.gridDim = dim3(132); cfg.blockDim = dim3(K2_THREADS); cfg.dynamicSmemBytes = K2_SMEM;
    cudaLaunchKernelEx(&cfg, k2_attn, x, w_gate, w_up, w_down, map_g, map_u, map_d);
    cfg.gridDim = dim3(128); cfg.blockDim = dim3(K3_THREADS); cfg.dynamicSmemBytes = K3_SMEM;
    cudaLaunchKernelEx(&cfg, k3_out, map_wo, x, out);
}
```

```cpp
#include <cuda_runtime.h>
#include <cuda_bf16.h>
#include <cuda.h>
#include <stdint.h>

namespace {

constexpr int S_ = 2048, D_ = 512, H_ = 32, F_ = 1792;

constexpr uint32_t PMASK = 0xDB6;

__device__ __align__(1024) uint4 g_QKV[3 * H_ * S_ * 2];
#define g_Q (g_QKV)
#define g_K (g_QKV + H_ * S_ * 2)
#define g_V (g_QKV + 2 * H_ * S_ * 2)
__device__ __align__(1024) uint4 g_O[S_ * D_ / 8];
__device__ float2 g_stats[S_];
__device__ uint32_t g_const[2] = {0x3F803F80u, 0x42294229u};
__device__ float g_r[S_];
__device__ __align__(16) float g_ypart[4][2][D_];
__device__ int g_sel[2];

__device__ __forceinline__ uint32_t smem_u32(const void* p) { return (uint32_t)__cvta_generic_to_shared(p); }
__device__ __forceinline__ float bf16r(float x) { return __bfloat162float(__float2bfloat16_rn(x)); }
__device__ __forceinline__ uint32_t pack_bf16(float lo, float hi) {
    uint32_t r; asm("cvt.rn.bf16x2.f32 %0, %1, %2;" : "=r"(r) : "f"(hi), "f"(lo)); return r;
}
__device__ __forceinline__ float bf_lo(uint32_t u) { return __uint_as_float(u << 16); }
__device__ __forceinline__ float bf_hi(uint32_t u) { return __uint_as_float(u & 0xFFFF0000u); }
__device__ __forceinline__ float ex2(float x) { float y; asm("ex2.approx.ftz.f32 %0, %1;" : "=f"(y) : "f"(x)); return y; }

__device__ __forceinline__ void mbar_init(uint32_t bar, uint32_t count) {
    asm volatile("mbarrier.init.shared::cta.b64 [%0], %1;" :: "r"(bar), "r"(count) : "memory");
}
__device__ __forceinline__ void mbar_expect_tx(uint32_t bar, uint32_t bytes) {
    asm volatile("mbarrier.arrive.expect_tx.shared::cta.b64 _, [%0], %1;" :: "r"(bar), "r"(bytes) : "memory");
}
__device__ __forceinline__ void mbar_arrive(uint32_t bar) {
    asm volatile("mbarrier.arrive.shared::cta.b64 _, [%0];" :: "r"(bar) : "memory");
}
__device__ __forceinline__ void mbar_wait(uint32_t bar, uint32_t parity) {
    uint32_t done;
    #pragma unroll 1
    for (int it = 0; it < (1 << 26); it++) {
        asm volatile("{.reg .pred p; mbarrier.try_wait.parity.shared::cta.b64 p, [%1], %2; selp.u32 %0, 1, 0, p;}"
                     : "=r"(done) : "r"(bar), "r"(parity) : "memory");
        if (done) return;
    }
    __trap();
}
__device__ __forceinline__ void bulk_g2s(uint32_t dst, const void* src, uint32_t bytes, uint32_t bar) {
    asm volatile("cp.async.bulk.shared::cluster.global.mbarrier::complete_tx::bytes [%0], [%1], %2, [%3];"
                 :: "r"(dst), "l"(src), "r"(bytes), "r"(bar) : "memory");
}
__device__ __forceinline__ void tma_2d(uint32_t dst, const CUtensorMap* map, int c0, int c1, uint32_t bar) {
    asm volatile("cp.async.bulk.tensor.2d.shared::cluster.global.mbarrier::complete_tx::bytes [%0], [%1, {%3, %4}], [%2];"
                 :: "r"(dst), "l"(map), "r"(bar), "r"(c0), "r"(c1) : "memory");
}
__device__ __forceinline__ void fence_async_smem() { asm volatile("fence.proxy.async.shared::cta;" ::: "memory"); }
__device__ __forceinline__ void named_bar(int id, int n) { asm volatile("bar.sync %0, %1;" :: "r"(id), "r"(n) : "memory"); }
__device__ __forceinline__ void named_bar_any(int id, int n) { asm volatile("barrier.sync %0, %1;" :: "r"(id), "r"(n) : "memory"); }

__device__ __forceinline__ uint64_t make_desc(uint32_t saddr, uint32_t lbo, uint32_t sbo, uint32_t swz) {
    return (uint64_t)((saddr & 0x3FFFF) >> 4) | ((uint64_t)(lbo >> 4) << 16) | ((uint64_t)(sbo >> 4) << 32) | ((uint64_t)swz << 62);
}
#define WG_FENCE() asm volatile("wgmma.fence.sync.aligned;" ::: "memory")
#define WG_COMMIT() asm volatile("wgmma.commit_group.sync.aligned;" ::: "memory")
template <int N> __device__ __forceinline__ void wg_wait() { asm volatile("wgmma.wait_group.sync.aligned %0;" :: "n"(N) : "memory"); }

#define F4(d, o) "+f"(d[o]), "+f"(d[o + 1]), "+f"(d[o + 2]), "+f"(d[o + 3])
#define F16(d, o) F4(d, o), F4(d, o + 4), F4(d, o + 8), F4(d, o + 12)
#define F32(d, o) F16(d, o), F16(d, o + 16)

__device__ __forceinline__ void wgmma_rs_n192(float* d, const uint32_t* a, uint64_t db) {
    asm volatile("wgmma.mma_async.sync.aligned.m64n192k16.f32.bf16.bf16 "
        "{%0,%1,%2,%3,%4,%5,%6,%7,%8,%9,%10,%11,%12,%13,%14,%15,%16,%17,%18,%19,%20,%21,%22,%23,%24,%25,%26,%27,%28,%29,%30,%31,"
        "%32,%33,%34,%35,%36,%37,%38,%39,%40,%41,%42,%43,%44,%45,%46,%47,%48,%49,%50,%51,%52,%53,%54,%55,%56,%57,%58,%59,%60,%61,%62,%63,"
        "%64,%65,%66,%67,%68,%69,%70,%71,%72,%73,%74,%75,%76,%77,%78,%79,%80,%81,%82,%83,%84,%85,%86,%87,%88,%89,%90,%91,%92,%93,%94,%95}, "
        "{%96,%97,%98,%99}, %100, 1, 1, 1, 1;\n"
        : F32(d, 0), F32(d, 32), F32(d, 64) : "r"(a[0]), "r"(a[1]), "r"(a[2]), "r"(a[3]), "l"(db));
}
__device__ __forceinline__ void wgmma_n64(float* d, uint64_t da, uint64_t db) {
    asm volatile("wgmma.mma_async.sync.aligned.m64n64k16.f32.bf16.bf16 "
        "{%0,%1,%2,%3,%4,%5,%6,%7,%8,%9,%10,%11,%12,%13,%14,%15,%16,%17,%18,%19,%20,%21,%22,%23,%24,%25,%26,%27,%28,%29,%30,%31}, "
        "%32, %33, 1, 1, 1, 0, 1;\n"
        : F32(d, 0) : "l"(da), "l"(db));
}
__device__ __forceinline__ void wgmma_qk32(float* d, uint64_t qd, uint64_t kd) {
    asm volatile("wgmma.mma_async.sync.aligned.m64n32k16.f32.bf16.bf16 {%0,%1,%2,%3,%4,%5,%6,%7,%8,%9,%10,%11,%12,%13,%14,%15}, %16, %17, 0, 1, 1, 0, 0;\n"
        : F16(d, 0) : "l"(qd), "l"(kd));
}
__device__ __forceinline__ void wgmma_pv(float* d, const uint32_t* a, uint64_t vd) {
    asm volatile("wgmma.mma_async.sync.aligned.m64n24k16.f32.bf16.bf16 {%0,%1,%2,%3,%4,%5,%6,%7,%8,%9,%10,%11}, {%12,%13,%14,%15}, %16, 1, 1, 1, 1;\n"
        : F4(d, 0), F4(d, 4), F4(d, 8) : "r"(a[0]), "r"(a[1]), "r"(a[2]), "r"(a[3]), "l"(vd));
}
__device__ __forceinline__ void touch16(float* d) { asm volatile("" : F16(d, 0) :: "memory"); }
__device__ __forceinline__ void touch12(float* d) { asm volatile("" : F4(d, 0), F4(d, 4), F4(d, 8) :: "memory"); }
__device__ __forceinline__ void touch32(float* d) { asm volatile("" : F32(d, 0) :: "memory"); }
__device__ __forceinline__ void touch96(float* d) { asm volatile("" : F32(d, 0), F32(d, 32), F32(d, 64) :: "memory"); }

__device__ __forceinline__ float ln_elem(float x, float mean_b, float rden) {
    return bf16r(bf16r(x - mean_b) * rden);
}
__device__ __forceinline__ void pdl_wait() { asm volatile("griddepcontrol.wait;" ::: "memory"); }
__device__ __forceinline__ void pdl_launch() { asm volatile("griddepcontrol.launch_dependents;" ::: "memory"); }

constexpr int K1_THREADS = 320;
constexpr int K1_SMEM = 131072 + 4 * 24576 + 256 + 1024;

__device__ __forceinline__ void ldsm4(uint32_t* r, uint32_t addr) {
    asm volatile("ldmatrix.sync.aligned.m8n8.x4.shared.b16 {%0, %1, %2, %3}, [%4];" : "=r"(r[0]), "=r"(r[1]), "=r"(r[2]), "=r"(r[3]) : "r"(addr) : "memory");
}
__device__ __forceinline__ void stsm4(uint32_t addr, uint32_t r0, uint32_t r1, uint32_t r2, uint32_t r3) {
    asm volatile("stmatrix.sync.aligned.m8n8.x4.shared.b16 [%0], {%1, %2, %3, %4};" :: "r"(addr), "r"(r0), "r"(r1), "r"(r2), "r"(r3) : "memory");
}
__device__ __forceinline__ void mma16816(float* d, const uint32_t* a, uint32_t b0, uint32_t b1) {
    asm("mma.sync.aligned.m16n8k16.row.col.f32.bf16.bf16.f32 {%0,%1,%2,%3}, {%4,%5,%6,%7}, {%8,%9}, {%0,%1,%2,%3};"
        : "+f"(d[0]), "+f"(d[1]), "+f"(d[2]), "+f"(d[3]) : "r"(a[0]), "r"(a[1]), "r"(a[2]), "r"(a[3]), "r"(b0), "r"(b1));
}
__device__ __forceinline__ uint32_t sub_bf16x2(uint32_t a, uint32_t b) {
    uint32_t d; asm("sub.rn.bf16x2 %0, %1, %2;" : "=r"(d) : "r"(a), "r"(b)); return d;
}
__device__ __forceinline__ uint32_t ln_pair(uint32_t x2, uint32_t mean2, uint32_t rhi2, uint32_t rlo2) {
    const uint32_t d = sub_bf16x2(x2, mean2);
    uint32_t t, y;
    asm("mul.rn.bf16x2 %0, %1, %2;" : "=r"(t) : "r"(d), "r"(rlo2));
    asm("fma.rn.bf16x2 %0, %1, %2, %3;" : "=r"(y) : "r"(d), "r"(rhi2), "r"(t));
    return y;
}
struct LnRow { uint32_t m2, hi2, lo2; };
__device__ __forceinline__ LnRow ln_row(float mean, float rden) {
    LnRow r;
    r.m2 = pack_bf16(mean, mean);
    r.hi2 = pack_bf16(rden, rden);
    const float lo = rden - bf_lo(r.hi2);
    r.lo2 = pack_bf16(lo, lo);
    return r;
}
__device__ __forceinline__ void ln_frag(uint32_t* a, const LnRow& r0, const LnRow& r1) {
    a[0] = ln_pair(a[0], r0.m2, r0.hi2, r0.lo2); a[1] = ln_pair(a[1], r1.m2, r1.hi2, r1.lo2);
    a[2] = ln_pair(a[2], r0.m2, r0.hi2, r0.lo2); a[3] = ln_pair(a[3], r1.m2, r1.hi2, r1.lo2);
}

template <int NJ>
__device__ __forceinline__ void k1_store(const float* acc, int jj0, uint32_t stage, int nt, int mt, int wg, int w4, int lane) {
    const int mi = lane >> 3, lr = lane & 7;
    const uint32_t off_qk = stage + (w4 * 2 + (mi & 1)) * 256 + (mi >> 1) * 128 + lr * 16;
    const uint32_t off_v = stage + (mi >> 1) * 1024 + (w4 * 16 + (mi & 1) * 8 + lr) * 16;
    #pragma unroll
    for (int jj = 0; jj < NJ; jj++) {
        const bool isv = nt * 12 + jj0 + jj >= 64;
        const float m = isv ? 1.0f : 8.8817841970012523e-16f;
        stsm4((isv ? off_v : off_qk) + jj * 2048,
              pack_bf16(acc[8 * jj] * m, acc[8 * jj + 1] * m), pack_bf16(acc[8 * jj + 2] * m, acc[8 * jj + 3] * m),
              pack_bf16(acc[8 * jj + 4] * m, acc[8 * jj + 5] * m), pack_bf16(acc[8 * jj + 6] * m, acc[8 * jj + 7] * m));
    }
    fence_async_smem();
    named_bar(1 + wg, 128);
    if (lane < NJ / 2) {
        const int pc = w4 * (NJ / 2) + lane, jj = pc >> 1, hf = pc & 1, hg = nt * 12 + jj0 + jj;
        const unsigned char* dst = (const unsigned char*)g_QKV + (size_t)hg * 65536
            + (hg >= 64 ? hf * 32768 + (mt * 128 + wg * 64) * 16 : (mt * 16 + wg * 8) * 256 + hf * 1024);
        asm volatile("cp.async.bulk.global.shared::cta.bulk_group [%0], [%1], 1024;" :: "l"(dst), "r"(stage + pc * 1024) : "memory");
        asm volatile("cp.async.bulk.commit_group;" ::: "memory");
    }
}

__global__ void __launch_bounds__(K1_THREADS, 1)
k1_ln_qkv(const __grid_constant__ CUtensorMap wmap, const __grid_constant__ CUtensorMap xmap, const __nv_bfloat16* __restrict__ w_r) {
    extern __shared__ __align__(1024) unsigned char smem[];
    const uint32_t sA = smem_u32(smem), sB = sA + 131072, sBar = sB + 4 * 24576;
    const int warp = __shfl_sync(~0u, threadIdx.x >> 5, 0), lane = threadIdx.x & 31;
    const int nt = blockIdx.x & 7, mt = blockIdx.x >> 3;
    const int tile = warp < 8 ? warp : nt;
    const int wg = tile >> 2;
    pdl_launch();
    uint32_t* s_wr = (uint32_t*)(smem + 131072 + 4 * 24576 + 256);
    if (warp == 8) {
        if (lane == 0) {
            for (int i = 0; i < 4; i++) { mbar_init(sBar + i * 8, 1); mbar_init(sBar + 48 + i * 8, 2); }
            asm volatile("fence.mbarrier_init.release.cluster;" ::: "memory");
            for (int i = 0; i < 4; i++) mbar_expect_tx(sBar + i * 8, 24576);
        }
        if (lane < 4) {
            mbar_init(sBar + 96 + lane * 8, 1);
            asm volatile("fence.mbarrier_init.release.cluster;" ::: "memory");
            mbar_expect_tx(sBar + 96 + lane * 8, 32768);
        }
        __syncwarp();
        if (lane < 16) {
            const int pn = (lane >> 3) * 4 + (lane & 3), hf = (lane >> 2) & 1;
            tma_2d(sA + pn * 16384 + hf * 8192, &xmap, pn * 64, mt * 128 + hf * 64, sBar + 96 + (lane >> 2) * 8);
        }
        __syncwarp();
        named_bar_any(3, K1_THREADS);
        mbar_wait(sBar + 96 + 8, 0);
        if (lane < 12) {
            const int ld = lane / 3, j = lane % 3;
            tma_2d(sB + ld * 24576 + j * 8192, &wmap, nt * 192 + j * 64, ld * 64, sBar + ld * 8);
        }
        __syncwarp();
        if (lane < 3) {
            for (int ld = 4; ld < 8; ld++) {
                const int sl = ld - 4;
                mbar_wait(sBar + 48 + sl * 8, 0);
                if (lane == 0) mbar_expect_tx(sBar + sl * 8, 24576);
                __syncwarp(7);
                tma_2d(sB + sl * 24576 + lane * 8192, &wmap, nt * 192 + lane * 64, ld * 64, sBar + sl * 8);
            }
        }
        return;
    }
    named_bar_any(3, K1_THREADS);
    if (warp == 9) {
        #pragma unroll
        for (int i = 0; i < 8; i++) s_wr[i * 32 + lane] = __ldg((const uint32_t*)w_r + i * 32 + lane);
        __syncwarp();
    }
    const int g = lane >> 2, t = lane & 3;
    const int lrow = tile * 16 + (lane & 7) + ((lane >> 3) & 1) * 8;
    const uint32_t lbase = sA + lrow * 128;
    const int lsw = lane & 7, lhi = lane >> 4;
    uint32_t laddr[4];
    #pragma unroll
    for (int k4 = 0; k4 < 4; k4++) laddr[k4] = lbase + (((k4 * 2 + lhi) ^ lsw) * 16);
    float dsum[4] = {0.f, 0.f, 0.f, 0.f}, dq0[4] = {0.f, 0.f, 0.f, 0.f}, dq1[4] = {0.f, 0.f, 0.f, 0.f};
    float esum[4] = {0.f, 0.f, 0.f, 0.f}, eq0[4] = {0.f, 0.f, 0.f, 0.f}, eq1[4] = {0.f, 0.f, 0.f, 0.f};
    #pragma unroll 2
    for (int pn = 0; pn < 8; pn++) {
        uint32_t a[4][4];
        if ((pn & 3) == 0) mbar_wait(sBar + 96 + ((pn >> 2) * 2 + wg) * 8, 0);
        #pragma unroll
        for (int k4 = 0; k4 < 4; k4++) ldsm4(a[k4], laddr[k4] + pn * 16384);
        #pragma unroll
        for (int k4 = 0; k4 < 4; k4 += 2) {
            mma16816(dsum, a[k4], 0x3F803F80u, 0x3F803F80u);
            mma16816(dq0, a[k4], a[k4][0], a[k4][2]);
            mma16816(dq1, a[k4], a[k4][1], a[k4][3]);
            mma16816(esum, a[k4 + 1], 0x3F803F80u, 0x3F803F80u);
            mma16816(eq0, a[k4 + 1], a[k4 + 1][0], a[k4 + 1][2]);
            mma16816(eq1, a[k4 + 1], a[k4 + 1][1], a[k4 + 1][3]);
        }
    }
    #pragma unroll
    for (int i = 0; i < 4; i++) { dsum[i] += esum[i]; dq0[i] += eq0[i]; dq1[i] += eq1[i]; }
    const int dsrc = g * 4 + (g >> 1);
    const float sq0 = __shfl_sync(~0u, (g & 1) ? dq0[1] : dq0[0], dsrc), sq1 = __shfl_sync(~0u, (g & 1) ? dq1[3] : dq1[2], dsrc);
    const float mean0 = dsum[0] * (1.0f / D_), mean1 = dsum[2] * (1.0f / D_);
    float var0 = fmaf(-mean0, mean0, sq0 * (1.0f / D_)), var1 = fmaf(-mean1, mean1, sq1 * (1.0f / D_));
    if (__any_sync(~0u, !(mean0 * mean0 <= 16.0f * var0) || !(mean1 * mean1 <= 16.0f * var1))) {
        float q0 = 0.f, q1 = 0.f;
        #pragma unroll 1
        for (int ks = 0; ks < 32; ks++) {
            uint32_t a[4];
            ldsm4(a, lbase + (ks >> 2) * 16384 + ((((ks & 3) * 2 + lhi) ^ lsw) * 16));
            #pragma unroll
            for (int i = 0; i < 4; i++) {
                const float m = (i & 1) ? mean1 : mean0;
                const float d0 = bf_lo(a[i]) - m, d1 = bf_hi(a[i]) - m;
                if (i & 1) q1 = fmaf(d0, d0, fmaf(d1, d1, q1)); else q0 = fmaf(d0, d0, fmaf(d1, d1, q0));
            }
        }
        q0 += __shfl_xor_sync(~0u, q0, 1); q0 += __shfl_xor_sync(~0u, q0, 2);
        q1 += __shfl_xor_sync(~0u, q1, 1); q1 += __shfl_xor_sync(~0u, q1, 2);
        var0 = q0 * (1.0f / D_); var1 = q1 * (1.0f / D_);
    }
    const float rs0 = __frcp_rn(bf16r(__fsqrt_rn(bf16r(bf16r(var0) + 1e-5f))));
    const float rs1 = __frcp_rn(bf16r(__fsqrt_rn(bf16r(bf16r(var1) + 1e-5f))));
    const LnRow lr0 = ln_row(mean0, rs0), lr1 = ln_row(mean1, rs1);
    if (warp == 9) {
        float d0 = 0.f, d1 = 0.f, e0 = 0.f, e1 = 0.f;
        #pragma unroll 2
        for (int pn = 0; pn < 8; pn++) {
            uint32_t a[4][4];
            #pragma unroll
            for (int k4 = 0; k4 < 4; k4++) ldsm4(a[k4], laddr[k4] + pn * 16384);
            #pragma unroll
            for (int k4 = 0; k4 < 4; k4++) {
                ln_frag(a[k4], lr0, lr1);
                const uint32_t w0 = s_wr[(pn * 4 + k4) * 8 + t], w1 = s_wr[(pn * 4 + k4) * 8 + 4 + t];
                d0 = fmaf(bf_lo(a[k4][0]), bf_lo(w0), d0); e0 = fmaf(bf_hi(a[k4][0]), bf_hi(w0), e0);
                d1 = fmaf(bf_lo(a[k4][1]), bf_lo(w0), d1); e1 = fmaf(bf_hi(a[k4][1]), bf_hi(w0), e1);
                d0 = fmaf(bf_lo(a[k4][2]), bf_lo(w1), d0); e0 = fmaf(bf_hi(a[k4][2]), bf_hi(w1), e0);
                d1 = fmaf(bf_lo(a[k4][3]), bf_lo(w1), d1); e1 = fmaf(bf_hi(a[k4][3]), bf_hi(w1), e1);
            }
        }
        d0 += e0; d1 += e1;
        d0 += __shfl_xor_sync(~0u, d0, 1); d0 += __shfl_xor_sync(~0u, d0, 2);
        d1 += __shfl_xor_sync(~0u, d1, 1); d1 += __shfl_xor_sync(~0u, d1, 2);
        if (t == 0) {
            const int row0 = mt * 128 + tile * 16;
            g_r[row0 + g] = bf16r(d0); g_r[row0 + g + 8] = bf16r(d1);
            g_stats[row0 + g] = make_float2(bf_lo(lr0.m2), rs0); g_stats[row0 + g + 8] = make_float2(bf_lo(lr1.m2), rs1);
        }
        asm volatile("bar.arrive %0, %1;" :: "r"(4 + wg), "r"(160) : "memory");
        return;
    }
    float acc[96];
    #pragma unroll
    for (int i = 0; i < 96; i++) acc[i] = 0.f;
    const uint64_t db0 = make_desc(sB, 8192, 1024, 1);
    uint32_t a[2][4][4];
    #pragma unroll
    for (int k4 = 0; k4 < 4; k4++) ldsm4(a[0][k4], laddr[k4]);
    #pragma unroll
    for (int k4 = 0; k4 < 4; k4++) ln_frag(a[0][k4], lr0, lr1);
    #pragma unroll 1
    for (int kc = 0; kc < 8; kc += 2) {
        #pragma unroll
        for (int h2 = 0; h2 < 2; h2++) {
            const int ld = kc + h2, sl = ld & 3;
            mbar_wait(sBar + sl * 8, ld >> 2);
            WG_FENCE();
            #pragma unroll
            for (int k4 = 0; k4 < 4; k4++) wgmma_rs_n192(acc, a[h2][k4], db0 + (uint64_t)(sl * 1536 + k4 * 128));
            WG_COMMIT();
            wg_wait<1>();
            if (ld >= 1 && ld <= 4 && (threadIdx.x & 127) == 0) mbar_arrive(sBar + 48 + (ld - 1) * 8);
            #pragma unroll
            for (int k4 = 0; k4 < 4; k4++) ldsm4(a[h2 ^ 1][k4], laddr[k4] + ((ld + 1) & 7) * 16384);
            #pragma unroll
            for (int k4 = 0; k4 < 4; k4++) ln_frag(a[h2 ^ 1][k4], lr0, lr1);
        }
    }
    wg_wait<0>();
    touch96(acc);
    if ((nt >> 2) == wg) named_bar(4 + wg, 160); else named_bar(1 + wg, 128);
    k1_store<4>(acc, 0, sA + wg * 8192, nt, mt, wg, warp & 3, lane);
    k1_store<4>(acc + 32, 4, sA + 16384 + wg * 8192, nt, mt, wg, warp & 3, lane);
    k1_store<4>(acc + 64, 8, sA + 32768 + wg * 8192, nt, mt, wg, warp & 3, lane);
    asm volatile("cp.async.bulk.wait_group.read 0;" ::: "memory");
}

constexpr int K2_THREADS = 512;
constexpr int K2_SMEM = 6 * 32768 + 12288;

constexpr float QS = 0.25f * 1.4426950408889634f;
constexpr float SC100 = 1.2676506002282294e30f;
__device__ __forceinline__ uint32_t polyexp2(float s0, float s1, float cd, float cdb, uint32_t one2, uint32_t ca2) {
    constexpr float A = 128.0f * QS * 1.7763568394002505e-15f;
    float t0, t1;
    asm("fma.rn.f32 %0, %1, %2, %3;" : "=f"(t0) : "f"(s0), "f"(A), "f"(cd));
    asm("fma.rn.f32 %0, %1, %2, %3;" : "=f"(t1) : "f"(s1), "f"(A), "f"(cdb));
    uint32_t W, U, h, G;
    asm("cvt.pack.sat.s16.s32 %0, %1, %2;" : "=r"(W) : "r"(__float_as_int(t1)), "r"(__float_as_int(t0)));
    asm("lop3.b32 %0, %1, 0x007F007F, %2, 0xEA;" : "=r"(U) : "r"(W), "r"(one2));
    asm("fma.rn.bf16x2 %0, %1, %2, %3;" : "=r"(h) : "r"(U), "r"(ca2), "r"(0xC300C300u));
    asm("fma.rn.bf16x2 %0, %1, %2, %3;" : "=r"(G) : "r"(h), "r"(U), "r"(0x438B438Bu));
    return W + G - 0x43404340u;
}

struct ExpC { float nm0, nm1, cd0, cd1, nm0b, nm1b, cd0b, cd1b; uint32_t one2, ca2; };

template <int G>
__device__ __forceinline__ void exp_block(const float* s, uint32_t* p, const ExpC& c) {
    #pragma unroll
    for (int hf = 0; hf < 2; hf++) {
        const float* x = s + hf * 4;
        if ((PMASK >> (G + hf)) & 1) {
            p[hf * 2 + 0] = polyexp2(x[0], x[1], c.cd0, c.cd0b, c.one2, c.ca2);
            p[hf * 2 + 1] = polyexp2(x[2], x[3], c.cd1, c.cd1b, c.one2, c.ca2);
        } else {
            p[hf * 2 + 0] = pack_bf16(ex2(fmaf(x[0], QS * SC100, c.nm0)), ex2(fmaf(x[1], QS * SC100, c.nm0b)));
            p[hf * 2 + 1] = pack_bf16(ex2(fmaf(x[2], QS * SC100, c.nm1)), ex2(fmaf(x[3], QS * SC100, c.nm1b)));
        }
    }
}

__device__ __forceinline__ void max16(const float* s, float& mx0, float& mx1) {
    #pragma unroll
    for (int j = 0; j < 4; j++) {
        mx0 = fmaxf(mx0, fmaxf(s[4 * j], s[4 * j + 1]));
        mx1 = fmaxf(mx1, fmaxf(s[4 * j + 2], s[4 * j + 3]));
    }
}

constexpr int MOE_SLOTS = 6, MOE_BOXES = 44;
__device__ __forceinline__ void moe_load(int b, int part, uint32_t ring, uint32_t bars, const CUtensorMap* mg, const CUtensorMap* mu, const CUtensorMap* md) {
    const int sl = b % MOE_SLOTS, grp = b & 1;
    if (b < 28) {
        const int j = b >> 1;
        mbar_expect_tx(bars + sl * 8, 32768);
        tma_2d(ring + sl * 32768, grp ? mu : mg, part * 448 + (j >> 1) * 64, (j & 1) * 256, bars + sl * 8);
    } else {
        const int j = (b - 28) >> 1;
        mbar_expect_tx(bars + sl * 8, 28672);
        tma_2d(ring + sl * 32768, md, ((j >> 1) * 2 + grp) * 64, part * 448 + (j & 1) * 224, bars + sl * 8);
    }
}
__device__ __forceinline__ void mma_2row(float* d, uint32_t a0, uint32_t a2, uint32_t b0, uint32_t b1) {
    asm("mma.sync.aligned.m16n8k16.row.col.f32.bf16.bf16.f32 {%0,%1,%2,%3}, {%4,%5,%6,%5}, {%7,%8}, {%0,%1,%2,%3};"
        : "+f"(d[0]), "+f"(d[1]), "+f"(d[2]), "+f"(d[3]) : "r"(a0), "r"(0u), "r"(a2), "r"(b0), "r"(b1));
}

__device__ void moe_cta(int part, unsigned char* smem, const __nv_bfloat16* __restrict__ x, const CUtensorMap* mg, const CUtensorMap* mu, const CUtensorMap* md) {
    const uint32_t ring = smem_u32(smem), bars = ring + MOE_SLOTS * 32768;
    __nv_bfloat16* xs = (__nv_bfloat16*)(smem + MOE_SLOTS * 32768 + 256);
    float* gu = (float*)(smem + MOE_SLOTS * 32768 + 256 + 2048);
    float* s_v = gu + 4 * 448;
    int* s_i = (int*)(s_v + 16);
    int* s_sel = s_i + 16;
    const int tid = threadIdx.x, warp = __shfl_sync(~0u, tid >> 5, 0), lane = tid & 31;
    if (tid == 0) {
        for (int i = 0; i < MOE_SLOTS; i++) { mbar_init(bars + i * 8, 1); mbar_init(bars + 128 + i * 8, 8); }
        asm volatile("fence.mbarrier_init.release.cluster;" ::: "memory");
        for (int b = 0; b < MOE_SLOTS; b++) moe_load(b, part, ring, bars, mg, mu, md);
    }
    pdl_wait();
    float rv[4];
    #pragma unroll
    for (int i = 0; i < 4; i++) rv[i] = g_r[tid + i * K2_THREADS];
    for (int pass = 0; pass < 2; pass++) {
        float bv = -INFINITY; int bi = 0x7fffffff;
        const int excl = pass ? s_sel[0] : -1;
        #pragma unroll
        for (int i = 0; i < 4; i++) {
            const int idx = tid + i * K2_THREADS;
            if (idx != excl && (rv[i] > bv || bi == 0x7fffffff)) { bv = rv[i]; bi = idx; }
        }
        #pragma unroll
        for (int o = 16; o; o >>= 1) {
            float ov = __shfl_xor_sync(~0u, bv, o); int oi = __shfl_xor_sync(~0u, bi, o);
            if (ov > bv || (ov == bv && oi < bi)) { bv = ov; bi = oi; }
        }
        if (lane == 0) { s_v[warp] = bv; s_i[warp] = bi; }
        __syncthreads();
        if (warp == 0) {
            bv = lane < 16 ? s_v[lane] : -INFINITY; bi = lane < 16 ? s_i[lane] : 0x7fffffff;
            #pragma unroll
            for (int o = 16; o; o >>= 1) {
                float ov = __shfl_xor_sync(~0u, bv, o); int oi = __shfl_xor_sync(~0u, bi, o);
                if (ov > bv || (ov == bv && oi < bi)) { bv = ov; bi = oi; }
            }
            if (lane == 0) s_sel[pass] = (bi == 0x7fffffff) ? pass : bi;
        }
        __syncthreads();
    }
    for (int i = tid; i < 1024; i += K2_THREADS) {
        const int tok = s_sel[i >> 9];
        const float2 st = g_stats[tok];
        xs[i] = __float2bfloat16_rn(ln_elem(__bfloat162float(x[(size_t)tok * D_ + (i & 511)]), st.x, st.y));
    }
    if (part == 0 && tid < 2) g_sel[tid] = s_sel[tid];
    __syncthreads();
    if (warp == 8) {
        if (lane == 0) {
            for (int b = MOE_SLOTS; b < MOE_BOXES; b++) {
                mbar_wait(bars + 128 + (b % MOE_SLOTS) * 8, (b / MOE_SLOTS - 1) & 1);
                moe_load(b, part, ring, bars, mg, mu, md);
            }
        }
        return;
    }
    if (warp > 8) return;
    const int nj = warp, g = lane >> 2, t = lane & 3;
    const uint32_t* xw = (const uint32_t*)xs + (g & 1) * 256 + t;
    uint32_t a[2][32];
    #pragma unroll
    for (int i = 0; i < 32; i++) { a[0][i] = xw[i * 4]; a[1][i] = xw[128 + i * 4]; }
    #pragma unroll 1
    for (int jp = 0; jp < MOE_BOXES / 4; jp++) {
        const bool down = jp >= 7;
        if (jp == 7) {
            named_bar(1, 256);
            for (int i = tid; i < 896; i += 256) {
                const float gs = bf16r(gu[i]), us = bf16r(gu[896 + i]);
                const float sl_ = bf16r(gs / (1.0f + __expf(-gs)));
                xs[(i / 448) * 512 + (i % 448)] = __float2bfloat16_rn(sl_ * us);
            }
            named_bar(1, 256);
            #pragma unroll
            for (int i = 0; i < 28; i++) { a[0][i] = xw[i * 4]; a[1][i] = xw[112 + i * 4]; }
        }
        float acc[2][4] = {{0.f, 0.f, 0.f, 0.f}, {0.f, 0.f, 0.f, 0.f}}, acb[2][4] = {{0.f, 0.f, 0.f, 0.f}, {0.f, 0.f, 0.f, 0.f}};
        #pragma unroll
        for (int q = 0; q < 4; q++) {
            const int hf = q >> 1, grp = q & 1;
            const int b = jp * 4 + q, sl = b % MOE_SLOTS;
            mbar_wait(bars + sl * 8, (b / MOE_SLOTS) & 1);
            const uint32_t baddr = ring + sl * 32768 + lane * 128 + ((nj ^ (lane & 7)) * 16);
            #pragma unroll
            for (int k4 = 0; k4 < 2; k4++) {
                uint32_t bf[4][4];
                #pragma unroll
                for (int k2 = 0; k2 < 4; k2++)
                    asm volatile("ldmatrix.sync.aligned.m8n8.x4.trans.shared.b16 {%0, %1, %2, %3}, [%4];"
                                 : "=r"(bf[k2][0]), "=r"(bf[k2][1]), "=r"(bf[k2][2]), "=r"(bf[k2][3]) : "r"(baddr + (k4 * 4 + k2) * 4096) : "memory");
                #pragma unroll
                for (int k2 = 0; k2 < 4; k2++) {
                    const int kk = k4 * 4 + k2;
                    if (kk < 7 || !down) {
                        mma_2row(acc[grp], a[hf][4 * kk], a[hf][4 * kk + 1], bf[k2][0], bf[k2][1]);
                        mma_2row(acb[grp], a[hf][4 * kk + 2], a[hf][4 * kk + 3], bf[k2][2], bf[k2][3]);
                    }
                }
            }
            __syncwarp();
            if (lane == 0) mbar_arrive(bars + 128 + sl * 8);
        }
        if (g < 2) {
            #pragma unroll
            for (int grp = 0; grp < 2; grp++) {
                const float2 v = make_float2(acc[grp][0] + acb[grp][0], acc[grp][1] + acb[grp][1]);
                if (!down) *(float2*)&gu[(grp * 2 + g) * 448 + jp * 64 + nj * 8 + t * 2] = v;
                else *(float2*)&g_ypart[part][g][((jp - 7) * 2 + grp) * 64 + nj * 8 + t * 2] = v;
            }
        }
    }
}

__global__ void __launch_bounds__(K2_THREADS, 1)
k2_attn(const __nv_bfloat16* __restrict__ x, const __nv_bfloat16* __restrict__ w_gate, const __nv_bfloat16* __restrict__ w_up,
        const __nv_bfloat16* __restrict__ w_down, const __grid_constant__ CUtensorMap mg, const __grid_constant__ CUtensorMap mu,
        const __grid_constant__ CUtensorMap md) {
    extern __shared__ __align__(1024) unsigned char smem[];
    pdl_launch();
    if (blockIdx.x >= 128) { moe_cta(blockIdx.x - 128, smem, x, &mg, &mu, &md); return; }
    if (threadIdx.x >= 32 && threadIdx.x < 35) {
        const __nv_bfloat16* w = threadIdx.x == 32 ? w_gate : (threadIdx.x == 33 ? w_up : w_down);
        asm volatile("cp.async.bulk.prefetch.L2.global [%0], %1;" :: "l"(w + (size_t)blockIdx.x * (D_ * F_ / 128)), "r"(D_ * F_ / 64) : "memory");
    }
    const uint32_t sK = smem_u32(smem), sV = sK + 65536, sQ = sV + 98304, sBar = sQ + 16384;
    const int h = blockIdx.x >> 2, qb = blockIdx.x & 3;
    const int warp = __shfl_sync(~0u, threadIdx.x >> 5, 0), lane = threadIdx.x & 31, wg = warp >> 2;
    if (threadIdx.x == 0) {
        mbar_init(sBar, 1); mbar_init(sBar + 8, 1);
        asm volatile("fence.mbarrier_init.release.cluster;" ::: "memory");
        mbar_expect_tx(sBar, 8192 + 12288 + 2 * 6144);
        mbar_expect_tx(sBar + 8, 8192 + 53248 + 2 * 26624);
    }
    for (int i = threadIdx.x; i < 2048; i += K2_THREADS)
        *(uint4*)(smem + 65536 + 65536 + i * 16) = make_uint4(0x3F803F80u, 0x3F803F80u, 0x3F803F80u, 0x3F803F80u);
    fence_async_smem();
    __syncthreads();
    if (warp == 0) {
        pdl_wait();
        const uint4* gk = g_K + (size_t)h * 4096;
        const uint4* gv = g_V + (size_t)h * 4096;
        const uint4* gq = g_Q + (size_t)h * 4096 + qb * 1024;
        if (lane == 0) bulk_g2s(sQ, gq, 8192, sBar);
        if (lane == 1) bulk_g2s(sK, gk, 12288, sBar);
        if (lane == 2) bulk_g2s(sV, gv, 6144, sBar);
        if (lane == 3) bulk_g2s(sV + 32768, gv + 2048, 6144, sBar);
        if (lane == 4) bulk_g2s(sK + 12288, gk + 768, 53248, sBar + 8);
        if (lane == 5) bulk_g2s(sV + 6144, gv + 384, 26624, sBar + 8);
        if (lane == 6) bulk_g2s(sV + 32768 + 6144, gv + 2048 + 384, 26624, sBar + 8);
        if (lane == 7) bulk_g2s(sQ + 8192, gq + 512, 8192, sBar + 8);
        __syncwarp();
    }
    ExpC c;
    {
        const volatile uint32_t* cc = g_const;
        c.one2 = cc[0]; c.ca2 = cc[1];
    }
    const uint64_t kdesc0 = make_desc(sK, 128, 256, 0);
    const uint64_t vdesc0 = make_desc(sV, 128, 32768, 0);
    #pragma unroll 1
    for (int pass = 0; pass < 2; pass++) {
        if (pass == 0) { mbar_wait(sBar, 0); __syncwarp(); }
        const int unit = pass * 4 + wg;
        const uint64_t q = make_desc(sQ + unit * 2048, 128, 256, 0);
        float o[12];
        #pragma unroll 1
        for (int attempt = 0; attempt < 2; attempt++) {
            float s0[16], s1[16], s2[16];
            #pragma unroll
            for (int i = 0; i < 16; i++) { s0[i] = 0.f; s1[i] = 0.f; s2[i] = 0.f; }
            float mx0 = -INFINITY, mx1 = -INFINITY;
            if (attempt) {
                #pragma unroll 1
                for (int it = 0; it < 64; it++) {
                    WG_FENCE();
                    wgmma_qk32(s0, q, kdesc0 + it * 64);
                    WG_COMMIT();
                    wg_wait<0>();
                    touch16(s0);
                    max16(s0, mx0, mx1);
                }
            }
            #pragma unroll
            for (int i = 0; i < 12; i++) o[i] = 0.f;
            WG_FENCE();
            wgmma_qk32(s2, q, kdesc0);
            wgmma_qk32(s0, q, kdesc0 + 64);
            wgmma_qk32(s1, q, kdesc0 + 128);
            WG_COMMIT();
            wg_wait<0>();
            touch16(s0); touch16(s1); touch16(s2);
            max16(s0, mx0, mx1); max16(s1, mx0, mx1); max16(s2, mx0, mx1);
            mx0 = fmaxf(mx0, __shfl_xor_sync(~0u, mx0, 1)); mx0 = fmaxf(mx0, __shfl_xor_sync(~0u, mx0, 2));
            mx1 = fmaxf(mx1, __shfl_xor_sync(~0u, mx1, 1)); mx1 = fmaxf(mx1, __shfl_xor_sync(~0u, mx1, 2));
            const float bias = attempt ? 0.0f : 128.0f * 64.0f;
            const float y0 = ceilf(fmaf(mx0, 128.0f * QS * SC100, bias)), y1 = ceilf(fmaf(mx1, 128.0f * QS * SC100, bias));
            c.nm0 = __shfl_sync(~0u, y0 * (-1.0f / 128.0f), lane); c.nm1 = __shfl_sync(~0u, y1 * (-1.0f / 128.0f), lane);
            c.cd0 = __shfl_sync(~0u, __fmul_rn(16256.0f - y0, __int_as_float(1)), lane);
            c.cd1 = __shfl_sync(~0u, __fmul_rn(16256.0f - y1, __int_as_float(1)), lane);
            c.nm0b = __shfl_xor_sync(~0u, c.nm0, 1); c.nm1b = __shfl_xor_sync(~0u, c.nm1, 1);
            c.cd0b = __shfl_xor_sync(~0u, c.cd0, 1); c.cd1b = __shfl_xor_sync(~0u, c.cd1, 1);
            uint64_t kd = kdesc0 + 192, vd = vdesc0 + 32;
            {
                uint32_t pa[4], pb[4];
                exp_block<12>(s2, pa, c);
                exp_block<14>(s2 + 8, pb, c);
                WG_FENCE();
                wgmma_pv(o, pa, vdesc0); wgmma_pv(o, pb, vdesc0 + 16);
                WG_COMMIT();
            }
            #pragma unroll 1
            for (int seg = 0; seg < 2; seg++) {
            if (seg) { wg_wait<0>(); mbar_wait(sBar + 8, 0); __syncwarp(); }
            #pragma unroll 1
            for (int it = seg ? 3 : 0; it < (seg ? 21 : 3); it++) {
                uint32_t p[6][4];
                WG_FENCE();
                wgmma_qk32(s2, q, kd);
                WG_COMMIT();
                exp_block<0>(s0, p[0], c);
                exp_block<2>(s0 + 8, p[1], c);
                WG_FENCE();
                wgmma_pv(o, p[0], vd); wgmma_pv(o, p[1], vd + 16);
                wgmma_qk32(s0, q, kd + 64);
                WG_COMMIT();
                wg_wait<1>();
                touch16(s2);
                exp_block<4>(s1, p[2], c);
                exp_block<6>(s1 + 8, p[3], c);
                WG_FENCE();
                wgmma_pv(o, p[2], vd + 32); wgmma_pv(o, p[3], vd + 48);
                wgmma_qk32(s1, q, kd + 128);
                WG_COMMIT();
                wg_wait<1>();
                touch16(s0);
                exp_block<8>(s2, p[4], c);
                exp_block<10>(s2 + 8, p[5], c);
                WG_FENCE();
                wgmma_pv(o, p[4], vd + 64); wgmma_pv(o, p[5], vd + 80);
                WG_COMMIT();
                vd += 96; kd += 192;
                wg_wait<1>();
                touch16(s1);
            }
            }
            wg_wait<0>();
            touch12(o);
            if (attempt) break;
            float big = 0.f;
            #pragma unroll
            for (int i = 0; i < 12; i++) big = fmaxf(big, fabsf(o[i]));
            bool bad = !(big < 1e30f);
            #pragma unroll
            for (int i = 0; i < 12; i++) bad |= (o[i] != o[i]);
            uint32_t any;
            asm volatile("{.reg .pred p, q; setp.ne.u32 p, %1, 0; barrier.cta.red.or.pred.aligned q, %2, 128, p; selp.u32 %0, 1, 0, q;}"
                         : "=r"(any) : "r"((uint32_t)bad), "r"(1 + wg) : "memory");
            if (!__any_sync(~0u, any)) break;
        }
        const int g = lane >> 2, t = lane & 3;
        const int r = (warp & 3) * 16 + g;
        const float i0 = __fdiv_rn(1.0f, o[8]), i1 = __fdiv_rn(1.0f, o[10]);
        uint32_t* ob = (uint32_t*)(g_O + (size_t)(qb * 8 + unit) * 4096 + (h >> 2) * 512 + r * 8) + t;
        const int c0 = ((h & 3) * 2) ^ (r & 7), c1 = ((h & 3) * 2 + 1) ^ (r & 7);
        ob[c0 * 4] = pack_bf16(o[0] * i0, o[1] * i0);
        ob[c1 * 4] = pack_bf16(o[4] * i0, o[5] * i0);
        ob[256 + c0 * 4] = pack_bf16(o[2] * i1, o[3] * i1);
        ob[256 + c1 * 4] = pack_bf16(o[6] * i1, o[7] * i1);
    }
}

constexpr int K3_THREADS = 256;
constexpr int K3_SMEM = 65536 + 131072 + 128;

__global__ void __launch_bounds__(K3_THREADS, 1)
k3_out(const __grid_constant__ CUtensorMap wmap, const __nv_bfloat16* __restrict__ x, __nv_bfloat16* __restrict__ out) {
    extern __shared__ __align__(1024) unsigned char smem[];
    const uint32_t sA = smem_u32(smem), sB = sA + 65536, sBar = sB + 131072;
    const int warp = __shfl_sync(~0u, threadIdx.x >> 5, 0), lane = threadIdx.x & 31, wg = warp >> 2;
    const int nt = blockIdx.x & 3, mt = blockIdx.x >> 2;
    if (threadIdx.x == 0) {
        for (int i = 0; i < 10; i++) mbar_init(sBar + i * 8, 1);
        asm volatile("fence.mbarrier_init.release.cluster;" ::: "memory");
        for (int i = 0; i < 8; i++) mbar_expect_tx(sBar + 16 + i * 8, 8192);
        for (int kh = 0; kh < 2; kh++) {
            mbar_expect_tx(sBar + kh * 8, 65536);
            tma_2d(sB + kh * 32768, &wmap, nt * 128, kh * 256, sBar + kh * 8);
            tma_2d(sB + 65536 + kh * 32768, &wmap, nt * 128 + 64, kh * 256, sBar + kh * 8);
        }
    }
    const int er = threadIdx.x >> 2, ec = (threadIdx.x & 3) * 32;
    const int row = mt * 64 + er;
    uint4 xv[4];
    #pragma unroll
    for (int j = 0; j < 4; j++) xv[j] = __ldg((const uint4*)(x + (size_t)row * D_ + nt * 128 + ec) + j);
    __syncthreads();
    pdl_wait();
    if (threadIdx.x < 8) bulk_g2s(sA + threadIdx.x * 8192, g_O + (size_t)mt * 4096 + threadIdx.x * 512, 8192, sBar + 16 + threadIdx.x * 8);
    const int sel0 = g_sel[0], sel1 = g_sel[1];
    const float2 st = g_stats[row];
    float acc[32];
    #pragma unroll
    for (int i = 0; i < 32; i++) acc[i] = 0.f;
    const uint64_t da0 = make_desc(sA, 16, 1024, 1);
    const uint64_t db0 = make_desc(sB + wg * 65536, 8192, 1024, 1);
    #pragma unroll 1
    for (int q = 0; q < 8; q++) {
        if ((q & 3) == 0) mbar_wait(sBar + (q >> 2) * 8, 0);
        mbar_wait(sBar + 16 + q * 8, 0);
        WG_FENCE();
        #pragma unroll
        for (int kk = 0; kk < 4; kk++)
            wgmma_n64(acc, da0 + (uint64_t)(q * 512 + kk * 2), db0 + (uint64_t)(q * 512 + kk * 128));
        WG_COMMIT();
    }
    uint32_t bb[16];
    {
        const uint32_t xu[16] = {xv[0].x, xv[0].y, xv[0].z, xv[0].w, xv[1].x, xv[1].y, xv[1].z, xv[1].w,
                                 xv[2].x, xv[2].y, xv[2].z, xv[2].w, xv[3].x, xv[3].y, xv[3].z, xv[3].w};
        #pragma unroll
        for (int j = 0; j < 16; j++) bb[j] = pack_bf16(bf16r(bf_lo(xu[j]) - st.x) * st.y, bf16r(bf_hi(xu[j]) - st.x) * st.y);
        const int slot = row == sel0 ? 0 : (row == sel1 ? 1 : -1);
        if (slot >= 0) {
            const float gate = bf16r(1.0f / (1.0f + __expf(-g_r[row])));
            const int c0 = nt * 128 + ec;
            #pragma unroll
            for (int j = 0; j < 16; j++) {
                const float2 a = *(const float2*)&g_ypart[0][slot][c0 + 2 * j], b = *(const float2*)&g_ypart[1][slot][c0 + 2 * j];
                const float2 c = *(const float2*)&g_ypart[2][slot][c0 + 2 * j], d = *(const float2*)&g_ypart[3][slot][c0 + 2 * j];
                bb[j] = pack_bf16(bf_lo(bb[j]) + bf16r(bf16r(a.x + b.x + c.x + d.x) * gate), bf_hi(bb[j]) + bf16r(bf16r(a.y + b.y + c.y + d.y) * gate));
            }
        }
    }
    wg_wait<0>();
    touch32(acc);
    __syncthreads();
    {
        const int g = lane >> 2, t = lane & 3;
        unsigned char* sp = smem + ((warp & 3) * 16 + g) * 272 + wg * 128 + t * 4;
        #pragma unroll
        for (int j = 0; j < 8; j++) {
            *(uint32_t*)(sp + j * 16) = pack_bf16(acc[4 * j], acc[4 * j + 1]);
            *(uint32_t*)(sp + 8 * 272 + j * 16) = pack_bf16(acc[4 * j + 2], acc[4 * j + 3]);
        }
    }
    __syncthreads();
    #pragma unroll
    for (int j = 0; j < 4; j++) {
        const uint4 av = *(const uint4*)(smem + er * 272 + ec * 2 + j * 16);
        const uint32_t au[4] = {av.x, av.y, av.z, av.w}, xu[4] = {xv[j].x, xv[j].y, xv[j].z, xv[j].w};
        uint32_t o[4];
        #pragma unroll
        for (int i = 0; i < 4; i++) {
            uint32_t t2;
            asm("add.rn.bf16x2 %0, %1, %2;" : "=r"(t2) : "r"(xu[i]), "r"(au[i]));
            asm("add.rn.bf16x2 %0, %1, %2;" : "=r"(o[i]) : "r"(t2), "r"(bb[j * 4 + i]));
        }
        *((uint4*)(out + (size_t)row * D_ + nt * 128 + ec) + j) = make_uint4(o[0], o[1], o[2], o[3]);
    }
}

typedef CUresult (*EncodeFn)(CUtensorMap*, CUtensorMapDataType, cuuint32_t, void*, const cuuint64_t*, const cuuint64_t*,
                             const cuuint32_t*, const cuuint32_t*, CUtensorMapInterleave, CUtensorMapSwizzle,
                             CUtensorMapL2promotion, CUtensorMapFloatOOBfill);

void make_wmap(EncodeFn fn, CUtensorMap* map, const void* ptr, int rows, int cols, int box_rows) {
    cuuint64_t dims[2] = {(cuuint64_t)cols, (cuuint64_t)rows};
    cuuint64_t strides[1] = {(cuuint64_t)cols * 2};
    cuuint32_t box[2] = {64, (cuuint32_t)box_rows};
    cuuint32_t es[2] = {1, 1};
    fn(map, CU_TENSOR_MAP_DATA_TYPE_BFLOAT16, 2, (void*)ptr, dims, strides, box, es, CU_TENSOR_MAP_INTERLEAVE_NONE,
       CU_TENSOR_MAP_SWIZZLE_128B, CU_TENSOR_MAP_L2_PROMOTION_L2_256B, CU_TENSOR_MAP_FLOAT_OOB_FILL_NONE);
}

}

extern "C" void kernel_launch(void* const* d_in, const int* in_sizes, int n_in, void* d_out, int out_size) {
    const __nv_bfloat16* x = (const __nv_bfloat16*)d_in[0];
    const __nv_bfloat16* wqkv = (const __nv_bfloat16*)d_in[1];
    const __nv_bfloat16* wo = (const __nv_bfloat16*)d_in[2];
    const __nv_bfloat16* w_r = (const __nv_bfloat16*)d_in[4];
    const __nv_bfloat16* w_gate = (const __nv_bfloat16*)d_in[5];
    const __nv_bfloat16* w_up = (const __nv_bfloat16*)d_in[6];
    const __nv_bfloat16* w_down = (const __nv_bfloat16*)d_in[7];
    __nv_bfloat16* out = (__nv_bfloat16*)d_out;

    static EncodeFn encode = nullptr;
    if (!encode) {
        void* fn = nullptr;
        cudaDriverEntryPointQueryResult qres;
        cudaGetDriverEntryPoint("cuTensorMapEncodeTiled", &fn, cudaEnableDefault, &qres);
        encode = (EncodeFn)fn;
        cudaFuncSetAttribute(k1_ln_qkv, cudaFuncAttributeMaxDynamicSharedMemorySize, K1_SMEM);
        cudaFuncSetAttribute(k2_attn, cudaFuncAttributeMaxDynamicSharedMemorySize, K2_SMEM);
        cudaFuncSetAttribute(k3_out, cudaFuncAttributeMaxDynamicSharedMemorySize, K3_SMEM);
    }
    CUtensorMap map_qkv, map_wo, map_x, map_g, map_u, map_d;
    make_wmap(encode, &map_g, w_gate, D_, F_, 256);
    make_wmap(encode, &map_u, w_up, D_, F_, 256);
    make_wmap(encode, &map_d, w_down, F_, D_, 224);
    make_wmap(encode, &map_x, x, S_, D_, 64);
    make_wmap(encode, &map_qkv, wqkv, D_, 3 * D_, 64);
    make_wmap(encode, &map_wo, wo, D_, D_, 256);

    k1_ln_qkv<<<128, K1_THREADS, K1_SMEM, cudaStreamPerThread>>>(map_qkv, map_x, w_r);
    cudaLaunchAttribute at[1];
    at[0].id = cudaLaunchAttributeProgrammaticStreamSerialization;
    at[0].val.programmaticStreamSerializationAllowed = 1;
    cudaLaunchConfig_t cfg = {};
    cfg.stream = cudaStreamPerThread;
    cfg.attrs = at; cfg.numAttrs = 1;
    cfg.gridDim = dim3(132); cfg.blockDim = dim3(K2_THREADS); cfg.dynamicSmemBytes = K2_SMEM;
    cudaLaunchKernelEx(&cfg, k2_attn, x, w_gate, w_up, w_down, map_g, map_u, map_d);
    cfg.gridDim = dim3(128); cfg.blockDim = dim3(K3_THREADS); cfg.dynamicSmemBytes = K3_SMEM;
    cudaLaunchKernelEx(&cfg, k3_out, map_wo, x, out);
}
```
